```python
import torch

def _softmax(x, axis=-1):
    return torch.softmax(x, dim=axis)

def _gelu(x):
    return torch.nn.functional.gelu(x, approximate='tanh')

def _silu(x):
    return torch.nn.functional.silu(x)

def _sigmoid(x):
    return torch.sigmoid(x)

def _layernorm(x, axis=-1, eps=1e-05):
    m = x.mean(dim=axis, keepdim=True)
    v = x.var(dim=axis, keepdim=True, unbiased=False)
    return (x - m) / torch.sqrt(v + eps)

def _scatter_add(tgt, idx, src, axis=0):
    return tgt.clone().index_add_(axis, idx, src)

def _segment_sum(src, seg, n):
    out = torch.zeros((n,) + src.shape[1:], dtype=src.dtype)
    return out.index_add_(0, seg, src)

def _pad(x, pw):
    flat = tuple((v for pair in reversed(pw) for v in pair))
    return torch.nn.functional.pad(x, flat)
kernel_name = 'recurrent_scan__memory_aug_recurrent_mem_tr__mixer_channel_mlp__prompt'

def setup_inputs():

    _w = lambda a: (lambda t: t.to(torch.bfloat16) if t.is_floating_point() else t)(torch.as_tensor(a))

    def _A_setup():
        B, S, Dm = (1, 2048, 640)
        H, Dh = (32, 192)
        M, seg = (8, 32)
        seg = min(seg, S)
        S = S // seg * seg
        return {'x': _w((lambda *s: torch.randn(*s, dtype=torch.bfloat16) * 0.05)(B, S, Dm)), 'mem0': _w((lambda *s: torch.randn(*s, dtype=torch.bfloat16) * 0.8)(B, M, Dm)), 'Wq': _w((lambda *s: torch.randn(*s, dtype=torch.bfloat16) * 0.8)(Dm, H, Dh) * Dm ** (-0.5)), 'Wk': _w((lambda *s: torch.randn(*s, dtype=torch.bfloat16) * 0.8)(Dm, H, Dh) * Dm ** (-0.5)), 'Wv': _w((lambda *s: torch.randn(*s, dtype=torch.bfloat16) * 0.8)(Dm, H, Dh) * Dm ** (-0.5)), 'Wo': _w((lambda *s: torch.randn(*s, dtype=torch.bfloat16) * 0.8)(H, Dh, Dm) * (H * Dh) ** (-0.5)), 'seg_len': seg}
    _A_in = _A_setup()

    def _B_setup():
        B, S, D, F = (1, 2048, 640, 1536)
        return {'x': _w((lambda *s: torch.randn(*s, dtype=torch.bfloat16) * 0.05)(B, S, D)), 'w1': _w((lambda *s: torch.randn(*s, dtype=torch.bfloat16) * 1.6)(D, F) * D ** (-0.5)), 'b1': _w((lambda *s: torch.randn(*s, dtype=torch.bfloat16) * 0.4)(F)), 'w2': _w((lambda *s: torch.randn(*s, dtype=torch.bfloat16) * 0.2)(F, D) * F ** (-0.5)), 'b2': _w((lambda *s: torch.randn(*s, dtype=torch.bfloat16) * 0.2)(D))}
    _B_in = _B_setup()
    return {'A_x': _A_in['x'], 'A_mem0': _A_in['mem0'], 'A_Wq': _A_in['Wq'], 'A_Wk': _A_in['Wk'], 'A_Wv': _A_in['Wv'], 'A_Wo': _A_in['Wo'], 'A_seg_len': _A_in['seg_len'], 'B_x': _B_in['x'], 'B_w1': _B_in['w1'], 'B_b1': _B_in['b1'], 'B_w2': _B_in['w2'], 'B_b2': _B_in['b2']}

def reference(A_x, A_mem0, A_Wq, A_Wk, A_Wv, A_Wo, A_seg_len, B_x, B_w1, B_b1, B_w2, B_b2):

    def _A_ref(x, mem0, Wq, Wk, Wv, Wo, seg_len):
        B, S, Dm = x.shape
        H, Dh = (Wq.shape[1], Wq.shape[2])
        M = mem0.shape[1]
        scale = Dh ** (-0.5)
        n_seg = S // seg_len
        L = M + seg_len
        idx = torch.arange(L)
        mask = (idx[:, None] < M) | (idx[:, None] >= idx[None, :])
        mem = mem0
        outs = []
        for s in range(n_seg):
            xs = x[:, s * seg_len:(s + 1) * seg_len, :].clone()
            h = torch.concatenate([mem, xs], axis=1)
            q = torch.einsum('btd,dhe->bhte', h, Wq)
            k = torch.einsum('btd,dhe->bhte', h, Wk)
            v = torch.einsum('btd,dhe->bhte', h, Wv)
            scores = torch.einsum('bhqe,bhke->bhqk', q, k) * scale
            scores = torch.where(mask[None, None], scores, -1000000000.0)
            p = _softmax(scores, axis=-1)
            o = torch.einsum('bhqk,bhke->bhqe', p, v)
            o = torch.einsum('bhte,hed->btd', o, Wo)
            mem = o[:, :M, :].clone()
            outs.append(o[:, M:, :])
        return torch.concatenate(outs, axis=1)

    def _B_ref(x, w1, b1, w2, b2):
        y = _layernorm(x, axis=-1)
        h = _gelu(torch.einsum('bsd,df->bsf', y, w1) + b1)
        return torch.einsum('bsf,fd->bsd', h, w2) + b2
    x = A_x
    xn = _layernorm(x, axis=-1)
    s = _A_ref(xn, A_mem0, A_Wq, A_Wk, A_Wv, A_Wo, A_seg_len)
    g = _silu(_B_ref(xn, B_w1, B_b1, B_w2, B_b2))
    return x + s * g
```

```cpp
#include <cuda_runtime.h>
#include <cuda_bf16.h>
#include <stdint.h>
#include <cuda.h>

namespace rk {
typedef __nv_bfloat16 bf16;
constexpr int S=2048, D=640, H=32, DH=192, HD=6144, NSEG=64, F=1536;
constexpr uint32_t SENT=0xFFFFFFFFu;
#define GUARDN 400000
constexpr int GUARD=GUARDN;
#define RCOPY 2
constexpr int NCTA=96;

__device__ __align__(128) bf16 g_xn[S*D];
__device__ __align__(128) bf16 g_y[S*D];
__device__ __align__(128) bf16 g_h[S*F];
__device__ __align__(128) bf16 g_gate[S*D];
__device__ __align__(128) bf16 g_k[(size_t)S*HD];
__device__ __align__(128) bf16 g_v[(size_t)S*HD];
__device__ __align__(128) uint2 g_kmf[NSEG*H*12*32];
__device__ __align__(128) uint2 g_vmf[NSEG*H*12*32];
__device__ __align__(128) uint32_t g_flag[NCTA*32];
__device__ __align__(128) bf16 g_ox[(size_t)S*HD];
__device__ __align__(128) float4 g_opp[(size_t)16*8*5*2*2048];
constexpr int C_NEXT=0, C_OP=256, C_M2=288, C_M1=320, C_QA=352, C_NUM=512;
__device__ __align__(128) uint32_t g_cnt[C_NUM];
#define PDL 1
__device__ __align__(128) uint32_t g_mem[(NSEG+1)*RCOPY*80*32];
__device__ __align__(128) uint32_t g_part[80*32*64];
__device__ int g_err;
__device__ unsigned long long g_gt[128*4];
#define GT(i) do{ if(threadIdx.x==0){ unsigned long long g0; asm volatile("mov.u64 %0, %%globaltimer;":"=l"(g0)); g_gt[blockIdx.x*4+(i)]=g0; } }while(0)

__device__ __forceinline__ float rb(float x){ return __bfloat162float(__float2bfloat16(x)); }
__device__ __forceinline__ uint32_t pack_bf16(float lo,float hi){ uint32_t r; asm("cvt.rn.bf16x2.f32 %0, %1, %2;":"=r"(r):"f"(hi),"f"(lo)); return r; }
__device__ __forceinline__ uint32_t movm(uint32_t a){ uint32_t d; asm volatile("movmatrix.sync.aligned.m8n8.trans.b16 %0, %1;":"=r"(d):"r"(a)); return d; }
__device__ __forceinline__ uint4 ldg_rlx4(const uint32_t* p){ uint4 v; asm volatile("ld.relaxed.gpu.global.v4.u32 {%0,%1,%2,%3}, [%4];":"=r"(v.x),"=r"(v.y),"=r"(v.z),"=r"(v.w):"l"(p):"memory"); return v; }
__device__ __forceinline__ void stg_rlx1(uint32_t* p,uint32_t a){ asm volatile("st.relaxed.gpu.global.u32 [%0], %1;"::"l"(p),"r"(a):"memory"); }
__device__ __forceinline__ void stg_rlx2(uint32_t* p,uint32_t a,uint32_t b){ asm volatile("st.relaxed.gpu.global.v2.u32 [%0], {%1,%2};"::"l"(p),"r"(a),"r"(b):"memory"); }
__device__ __forceinline__ void bar_sync(int id,int n){ asm volatile("bar.sync %0, %1;"::"r"(id),"r"(n):"memory"); }
__device__ __forceinline__ void bar_arrive(int id,int n){ asm volatile("bar.arrive %0, %1;"::"r"(id),"r"(n):"memory"); }
__device__ __forceinline__ void mma16816(float* d,const uint32_t* a,uint32_t b0,uint32_t b1){
  asm volatile("mma.sync.aligned.m16n8k16.row.col.f32.bf16.bf16.f32 {%0,%1,%2,%3},{%4,%5,%6,%7},{%8,%9},{%0,%1,%2,%3};"
   :"+f"(d[0]),"+f"(d[1]),"+f"(d[2]),"+f"(d[3]):"r"(a[0]),"r"(a[1]),"r"(a[2]),"r"(a[3]),"r"(b0),"r"(b1));
}
__device__ __forceinline__ void mma1688(float* d,uint32_t a0,uint32_t a1,uint32_t b0){
  asm volatile("mma.sync.aligned.m16n8k8.row.col.f32.bf16.bf16.f32 {%0,%1,%2,%3},{%4,%5},{%6},{%0,%1,%2,%3};"
   :"+f"(d[0]),"+f"(d[1]),"+f"(d[2]),"+f"(d[3]):"r"(a0),"r"(a1),"r"(b0));
}
__device__ __forceinline__ void ldsm4t(uint32_t* r,uint32_t addr){ asm volatile("ldmatrix.sync.aligned.m8n8.x4.trans.shared.b16 {%0,%1,%2,%3}, [%4];":"=r"(r[0]),"=r"(r[1]),"=r"(r[2]),"=r"(r[3]):"r"(addr):"memory"); }
__device__ __forceinline__ void ldsm4(uint32_t* r,uint32_t addr){ asm volatile("ldmatrix.sync.aligned.m8n8.x4.shared.b16 {%0,%1,%2,%3}, [%4];":"=r"(r[0]),"=r"(r[1]),"=r"(r[2]),"=r"(r[3]):"r"(addr):"memory"); }
__device__ __forceinline__ void cp16(uint32_t dst,const void* src){ asm volatile("cp.async.cg.shared.global [%0], [%1], 16;"::"r"(dst),"l"(src):"memory"); }
__device__ __forceinline__ void cp_wait_all(){ asm volatile("cp.async.wait_all;":::"memory"); }
__device__ __forceinline__ void fence_async(){ asm volatile("fence.proxy.async.shared::cta;":::"memory"); }
__device__ __forceinline__ void sts4f(uint32_t a,const float* v){ asm volatile("st.shared.v4.f32 [%0], {%1,%2,%3,%4};"::"r"(a),"f"(v[0]),"f"(v[1]),"f"(v[2]),"f"(v[3]):"memory"); }
__device__ __forceinline__ void sts4(uint32_t a,uint4 v){ asm volatile("st.shared.v4.u32 [%0], {%1,%2,%3,%4};"::"r"(a),"r"(v.x),"r"(v.y),"r"(v.z),"r"(v.w):"memory"); }
__device__ __forceinline__ void sts4r(uint32_t a,const uint32_t* v){ asm volatile("st.shared.v4.u32 [%0], {%1,%2,%3,%4};"::"r"(a),"r"(v[0]),"r"(v[1]),"r"(v[2]),"r"(v[3]):"memory"); }
__device__ __forceinline__ void sts2(uint32_t a,uint32_t x,uint32_t y){ asm volatile("st.shared.v2.u32 [%0], {%1,%2};"::"r"(a),"r"(x),"r"(y):"memory"); }
__device__ __forceinline__ float4 lds4f(uint32_t a){ float4 v; asm volatile("ld.shared.v4.f32 {%0,%1,%2,%3}, [%4];":"=f"(v.x),"=f"(v.y),"=f"(v.z),"=f"(v.w):"r"(a):"memory"); return v; }
__device__ __forceinline__ float2 lds2f(uint32_t a){ float2 v; asm volatile("ld.shared.v2.f32 {%0,%1}, [%2];":"=f"(v.x),"=f"(v.y):"r"(a):"memory"); return v; }
__device__ __forceinline__ uint4 lds4(uint32_t a){ uint4 v; asm volatile("ld.shared.v4.u32 {%0,%1,%2,%3}, [%4];":"=r"(v.x),"=r"(v.y),"=r"(v.z),"=r"(v.w):"r"(a):"memory"); return v; }
__device__ __forceinline__ void lds4r(uint32_t* r,uint32_t a){ asm volatile("ld.shared.v4.u32 {%0,%1,%2,%3}, [%4];":"=r"(r[0]),"=r"(r[1]),"=r"(r[2]),"=r"(r[3]):"r"(a):"memory"); }
__device__ __forceinline__ uint2 lds2(uint32_t a){ uint2 v; asm volatile("ld.shared.v2.u32 {%0,%1}, [%2];":"=r"(v.x),"=r"(v.y):"r"(a):"memory"); return v; }
__device__ __forceinline__ float ex2(float x){ float r; asm("ex2.approx.ftz.f32 %0, %1;":"=f"(r):"f"(x)); return r; }
__device__ __forceinline__ float rcp(float x){ float r; asm("rcp.approx.ftz.f32 %0, %1;":"=f"(r):"f"(x)); return r; }
__device__ __forceinline__ void mbar_init(uint32_t a,int n){ asm volatile("mbarrier.init.shared.b64 [%0], %1;"::"r"(a),"r"(n):"memory"); }
__device__ __forceinline__ void mbar_expect(uint32_t a,int bytes){ asm volatile("mbarrier.arrive.expect_tx.shared.b64 _, [%0], %1;"::"r"(a),"r"(bytes):"memory"); }
__device__ __forceinline__ bool mbar_try(uint32_t a,uint32_t par){ uint32_t ok; asm volatile("{\n.reg .pred p;\nmbarrier.try_wait.parity.shared.b64 p, [%1], %2;\nselp.u32 %0,1,0,p;\n}":"=r"(ok):"r"(a),"r"(par):"memory"); return ok; }
__device__ __forceinline__ bool mbar_try_cl(uint32_t a,uint32_t par){ uint32_t ok; asm volatile("{\n.reg .pred p;\nmbarrier.try_wait.parity.acquire.cluster.shared::cta.b64 p, [%1], %2;\nselp.u32 %0,1,0,p;\n}":"=r"(ok):"r"(a),"r"(par):"memory"); return ok; }
__device__ __forceinline__ void bulk_g2s(uint32_t dst,const void* src,int bytes,uint32_t mb){ asm volatile("cp.async.bulk.shared::cluster.global.mbarrier::complete_tx::bytes [%0], [%1], %2, [%3];"::"r"(dst),"l"(src),"r"(bytes),"r"(mb):"memory"); }
__device__ __forceinline__ uint32_t mapa(uint32_t a,uint32_t r){ uint32_t d; asm("mapa.shared::cluster.u32 %0, %1, %2;":"=r"(d):"r"(a),"r"(r)); return d; }
__device__ __forceinline__ void st_async2(uint32_t ra,uint32_t x,uint32_t y,uint32_t rmb){ asm volatile("st.async.weak.shared::cluster.mbarrier::complete_tx::bytes.v2.b32 [%0], {%1,%2}, [%3];"::"r"(ra),"r"(x),"r"(y),"r"(rmb):"memory"); }
__device__ __forceinline__ void cluster_sync(){ asm volatile("barrier.cluster.arrive.release.aligned;\nbarrier.cluster.wait.acquire.aligned;":::"memory"); }
__device__ __forceinline__ void fence_gpu(){ asm volatile("fence.acq_rel.gpu;":::"memory"); }

template<int NL,class V,class LDF,class OKF>
__device__ __forceinline__ void poll1(V* u,LDF ld,OKF ok,bool& dead,int code){
  #pragma unroll
  for(int i=0;i<NL;i++) u[i]=ld(i);
  int guard=0;
  while(true){
    bool f[NL]; bool a=true;
    #pragma unroll
    for(int i=0;i<NL;i++){ f[i]=ok(u[i]); a=a&&f[i]; }
    if(__all_sync(~0u,a)||dead) break;
    #pragma unroll
    for(int i=0;i<NL;i++) if(!f[i]) u[i]=ld(i);
    if(++guard>GUARD){ dead=true; g_err=code; }
  }
}
template<int N> __device__ __forceinline__ void wgmma(float* d,uint64_t da,uint64_t db,int sc);
template<> __device__ __forceinline__ void wgmma<128>(float* d,uint64_t da,uint64_t db,int sc){
  asm volatile("{\n.reg .pred p;\nsetp.ne.b32 p, %66, 0;\nwgmma.mma_async.sync.aligned.m64n128k16.f32.bf16.bf16 {%0,%1,%2,%3,%4,%5,%6,%7,%8,%9,%10,%11,%12,%13,%14,%15,%16,%17,%18,%19,%20,%21,%22,%23,%24,%25,%26,%27,%28,%29,%30,%31,%32,%33,%34,%35,%36,%37,%38,%39,%40,%41,%42,%43,%44,%45,%46,%47,%48,%49,%50,%51,%52,%53,%54,%55,%56,%57,%58,%59,%60,%61,%62,%63}, %64, %65, p, 1, 1, 0, 1;\n}"
   :"+f"(d[0]),"+f"(d[1]),"+f"(d[2]),"+f"(d[3]),"+f"(d[4]),"+f"(d[5]),"+f"(d[6]),"+f"(d[7]),"+f"(d[8]),"+f"(d[9]),"+f"(d[10]),"+f"(d[11]),"+f"(d[12]),"+f"(d[13]),"+f"(d[14]),"+f"(d[15]),"+f"(d[16]),"+f"(d[17]),"+f"(d[18]),"+f"(d[19]),"+f"(d[20]),"+f"(d[21]),"+f"(d[22]),"+f"(d[23]),"+f"(d[24]),"+f"(d[25]),"+f"(d[26]),"+f"(d[27]),"+f"(d[28]),"+f"(d[29]),"+f"(d[30]),"+f"(d[31]),"+f"(d[32]),"+f"(d[33]),"+f"(d[34]),"+f"(d[35]),"+f"(d[36]),"+f"(d[37]),"+f"(d[38]),"+f"(d[39]),"+f"(d[40]),"+f"(d[41]),"+f"(d[42]),"+f"(d[43]),"+f"(d[44]),"+f"(d[45]),"+f"(d[46]),"+f"(d[47]),"+f"(d[48]),"+f"(d[49]),"+f"(d[50]),"+f"(d[51]),"+f"(d[52]),"+f"(d[53]),"+f"(d[54]),"+f"(d[55]),"+f"(d[56]),"+f"(d[57]),"+f"(d[58]),"+f"(d[59]),"+f"(d[60]),"+f"(d[61]),"+f"(d[62]),"+f"(d[63]):"l"(da),"l"(db),"r"(sc));
}
template<> __device__ __forceinline__ void wgmma<192>(float* d,uint64_t da,uint64_t db,int sc){
  asm volatile("{\n.reg .pred p;\nsetp.ne.b32 p, %98, 0;\nwgmma.mma_async.sync.aligned.m64n192k16.f32.bf16.bf16 {%0,%1,%2,%3,%4,%5,%6,%7,%8,%9,%10,%11,%12,%13,%14,%15,%16,%17,%18,%19,%20,%21,%22,%23,%24,%25,%26,%27,%28,%29,%30,%31,%32,%33,%34,%35,%36,%37,%38,%39,%40,%41,%42,%43,%44,%45,%46,%47,%48,%49,%50,%51,%52,%53,%54,%55,%56,%57,%58,%59,%60,%61,%62,%63,%64,%65,%66,%67,%68,%69,%70,%71,%72,%73,%74,%75,%76,%77,%78,%79,%80,%81,%82,%83,%84,%85,%86,%87,%88,%89,%90,%91,%92,%93,%94,%95}, %96, %97, p, 1, 1, 0, 1;\n}"
   :"+f"(d[0]),"+f"(d[1]),"+f"(d[2]),"+f"(d[3]),"+f"(d[4]),"+f"(d[5]),"+f"(d[6]),"+f"(d[7]),"+f"(d[8]),"+f"(d[9]),"+f"(d[10]),"+f"(d[11]),"+f"(d[12]),"+f"(d[13]),"+f"(d[14]),"+f"(d[15]),"+f"(d[16]),"+f"(d[17]),"+f"(d[18]),"+f"(d[19]),"+f"(d[20]),"+f"(d[21]),"+f"(d[22]),"+f"(d[23]),"+f"(d[24]),"+f"(d[25]),"+f"(d[26]),"+f"(d[27]),"+f"(d[28]),"+f"(d[29]),"+f"(d[30]),"+f"(d[31]),"+f"(d[32]),"+f"(d[33]),"+f"(d[34]),"+f"(d[35]),"+f"(d[36]),"+f"(d[37]),"+f"(d[38]),"+f"(d[39]),"+f"(d[40]),"+f"(d[41]),"+f"(d[42]),"+f"(d[43]),"+f"(d[44]),"+f"(d[45]),"+f"(d[46]),"+f"(d[47]),"+f"(d[48]),"+f"(d[49]),"+f"(d[50]),"+f"(d[51]),"+f"(d[52]),"+f"(d[53]),"+f"(d[54]),"+f"(d[55]),"+f"(d[56]),"+f"(d[57]),"+f"(d[58]),"+f"(d[59]),"+f"(d[60]),"+f"(d[61]),"+f"(d[62]),"+f"(d[63]),"+f"(d[64]),"+f"(d[65]),"+f"(d[66]),"+f"(d[67]),"+f"(d[68]),"+f"(d[69]),"+f"(d[70]),"+f"(d[71]),"+f"(d[72]),"+f"(d[73]),"+f"(d[74]),"+f"(d[75]),"+f"(d[76]),"+f"(d[77]),"+f"(d[78]),"+f"(d[79]),"+f"(d[80]),"+f"(d[81]),"+f"(d[82]),"+f"(d[83]),"+f"(d[84]),"+f"(d[85]),"+f"(d[86]),"+f"(d[87]),"+f"(d[88]),"+f"(d[89]),"+f"(d[90]),"+f"(d[91]),"+f"(d[92]),"+f"(d[93]),"+f"(d[94]),"+f"(d[95]):"l"(da),"l"(db),"r"(sc));
}
template<> __device__ __forceinline__ void wgmma<256>(float* d,uint64_t da,uint64_t db,int sc){
  asm volatile("{\n.reg .pred p;\nsetp.ne.b32 p, %130, 0;\nwgmma.mma_async.sync.aligned.m64n256k16.f32.bf16.bf16 {%0,%1,%2,%3,%4,%5,%6,%7,%8,%9,%10,%11,%12,%13,%14,%15,%16,%17,%18,%19,%20,%21,%22,%23,%24,%25,%26,%27,%28,%29,%30,%31,%32,%33,%34,%35,%36,%37,%38,%39,%40,%41,%42,%43,%44,%45,%46,%47,%48,%49,%50,%51,%52,%53,%54,%55,%56,%57,%58,%59,%60,%61,%62,%63,%64,%65,%66,%67,%68,%69,%70,%71,%72,%73,%74,%75,%76,%77,%78,%79,%80,%81,%82,%83,%84,%85,%86,%87,%88,%89,%90,%91,%92,%93,%94,%95,%96,%97,%98,%99,%100,%101,%102,%103,%104,%105,%106,%107,%108,%109,%110,%111,%112,%113,%114,%115,%116,%117,%118,%119,%120,%121,%122,%123,%124,%125,%126,%127}, %128, %129, p, 1, 1, 0, 1;\n}"
   :"+f"(d[0]),"+f"(d[1]),"+f"(d[2]),"+f"(d[3]),"+f"(d[4]),"+f"(d[5]),"+f"(d[6]),"+f"(d[7]),"+f"(d[8]),"+f"(d[9]),"+f"(d[10]),"+f"(d[11]),"+f"(d[12]),"+f"(d[13]),"+f"(d[14]),"+f"(d[15]),"+f"(d[16]),"+f"(d[17]),"+f"(d[18]),"+f"(d[19]),"+f"(d[20]),"+f"(d[21]),"+f"(d[22]),"+f"(d[23]),"+f"(d[24]),"+f"(d[25]),"+f"(d[26]),"+f"(d[27]),"+f"(d[28]),"+f"(d[29]),"+f"(d[30]),"+f"(d[31]),"+f"(d[32]),"+f"(d[33]),"+f"(d[34]),"+f"(d[35]),"+f"(d[36]),"+f"(d[37]),"+f"(d[38]),"+f"(d[39]),"+f"(d[40]),"+f"(d[41]),"+f"(d[42]),"+f"(d[43]),"+f"(d[44]),"+f"(d[45]),"+f"(d[46]),"+f"(d[47]),"+f"(d[48]),"+f"(d[49]),"+f"(d[50]),"+f"(d[51]),"+f"(d[52]),"+f"(d[53]),"+f"(d[54]),"+f"(d[55]),"+f"(d[56]),"+f"(d[57]),"+f"(d[58]),"+f"(d[59]),"+f"(d[60]),"+f"(d[61]),"+f"(d[62]),"+f"(d[63]),"+f"(d[64]),"+f"(d[65]),"+f"(d[66]),"+f"(d[67]),"+f"(d[68]),"+f"(d[69]),"+f"(d[70]),"+f"(d[71]),"+f"(d[72]),"+f"(d[73]),"+f"(d[74]),"+f"(d[75]),"+f"(d[76]),"+f"(d[77]),"+f"(d[78]),"+f"(d[79]),"+f"(d[80]),"+f"(d[81]),"+f"(d[82]),"+f"(d[83]),"+f"(d[84]),"+f"(d[85]),"+f"(d[86]),"+f"(d[87]),"+f"(d[88]),"+f"(d[89]),"+f"(d[90]),"+f"(d[91]),"+f"(d[92]),"+f"(d[93]),"+f"(d[94]),"+f"(d[95]),"+f"(d[96]),"+f"(d[97]),"+f"(d[98]),"+f"(d[99]),"+f"(d[100]),"+f"(d[101]),"+f"(d[102]),"+f"(d[103]),"+f"(d[104]),"+f"(d[105]),"+f"(d[106]),"+f"(d[107]),"+f"(d[108]),"+f"(d[109]),"+f"(d[110]),"+f"(d[111]),"+f"(d[112]),"+f"(d[113]),"+f"(d[114]),"+f"(d[115]),"+f"(d[116]),"+f"(d[117]),"+f"(d[118]),"+f"(d[119]),"+f"(d[120]),"+f"(d[121]),"+f"(d[122]),"+f"(d[123]),"+f"(d[124]),"+f"(d[125]),"+f"(d[126]),"+f"(d[127]):"l"(da),"l"(db),"r"(sc));
}
__global__ void __launch_bounds__(256) k_pre(const bf16* __restrict__ x,const bf16* __restrict__ mem0){
  const int warp=threadIdx.x>>5, lane=threadIdx.x&31;
  const int row=blockIdx.x*8+warp;
  {
    int i=blockIdx.x*256+threadIdx.x; int n=gridDim.x*256;
    for(int k=i;k<(NSEG+1)*RCOPY*80*32;k+=n){
      uint32_t v=SENT;
      if(k<RCOPY*80*32){ int fb=(k%2560)>>5, r=(k>>2)&7, w=k&3; v=*(const uint32_t*)(mem0+r*D+fb*8+w*2);
        if(v==SENT) v=0x7FFF7FFFu; }
      g_mem[k]=v;
    }
    if(i==0) g_err=0;
    if(i<NCTA*32) g_flag[i]=0;
    if(i<C_NUM) g_cnt[i]=0;
  }
  float v[20];
  {
    const uint32_t* p=(const uint32_t*)(x+(size_t)row*D);
    #pragma unroll
    for(int i=0;i<10;i++){ uint32_t u=p[lane+32*i]; v[2*i]=__uint_as_float(u<<16); v[2*i+1]=__uint_as_float(u&0xffff0000u); }
  }
  #pragma unroll
  for(int pass=0;pass<2;pass++){
    float s=0;
    #pragma unroll
    for(int i=0;i<20;i++) s+=v[i];
    #pragma unroll
    for(int o=16;o;o>>=1) s+=__shfl_xor_sync(~0u,s,o);
    float mean=s*(1.f/D);
    float q=0;
    #pragma unroll
    for(int i=0;i<20;i++){ float d=v[i]-mean; q+=d*d; }
    #pragma unroll
    for(int o=16;o;o>>=1) q+=__shfl_xor_sync(~0u,q,o);
    float var=rb(q*(1.f/D)), mb=rb(mean);
    float den=rb(sqrtf(rb(var+1e-5f)));
    uint32_t* o=(uint32_t*)((pass?g_y:g_xn)+(size_t)row*D);
    #pragma unroll
    for(int i=0;i<10;i++){
      float a=rb(rb(v[2*i]-mb)/den), b=rb(rb(v[2*i+1]-mb)/den);
      v[2*i]=a; v[2*i+1]=b;
      o[lane+32*i]=pack_bf16(a,b);
    }
  }
}

#define WMK 2
#define OMK 3
#define NB 4
constexpr int NSLOT=30+3*WMK+2*OMK;
constexpr int SM_M=0;
constexpr int SM_RED=NSLOT*4096;
constexpr int SM_KX=SM_RED+24576;
constexpr int SM_VX=SM_KX+4096;
constexpr int SM_QKF=SM_VX+12288;
constexpr int SM_SCX=SM_QKF+2048;
constexpr int SM_VMX=SM_SCX+3840;
constexpr int SM_O=SM_VMX+3072;
constexpr int SM_RSUM=SM_O+3072;
constexpr int SM_MB=SM_RSUM+2048;
constexpr int SM_TOTAL=SM_MB+64;
constexpr int SM_STG=SM_RED;
static_assert(SM_MB-SM_STG>=49152,"staging");
static_assert(SM_TOTAL<=232448,"smem");

#define TS(i)
#define TW(i)
#define TF(i)

__device__ __forceinline__ void tma2d(uint32_t dst,const CUtensorMap* tm,int c0,int c1,uint32_t mb){
  asm volatile("cp.async.bulk.tensor.2d.shared::cluster.global.mbarrier::complete_tx::bytes [%0], [%1, {%3, %4}], [%2];"::"r"(dst),"l"(tm),"r"(mb),"r"(c0),"r"(c1):"memory"); }
__device__ __forceinline__ void tma2d_pf(const CUtensorMap* tm,int c0,int c1){
  asm volatile("cp.async.bulk.prefetch.tensor.2d.L2.global [%0, {%1, %2}];"::"l"(tm),"r"(c0),"r"(c1):"memory"); }
__global__ void __launch_bounds__(256,1) k_rec(const __grid_constant__ CUtensorMap tmK,const __grid_constant__ CUtensorMap tmV,const bf16* __restrict__ Wq,const bf16* __restrict__ Wk,const bf16* __restrict__ Wv,const bf16* __restrict__ Wo){
  extern __shared__ __align__(1024) uint8_t sm[];
  const int tid=threadIdx.x, warp=__shfl_sync(~0u,tid>>5,0), lane=tid&31, g=lane>>2, t=lane&3;
  const int b=blockIdx.x, h=b/3, c=b-3*h;
  const uint32_t sb=(uint32_t)__cvta_generic_to_shared(sm);
  const int kq=warp&3, mg=warp>>2;
  const uint32_t s16=sb+lane*16, s8=sb+lane*8;
  const uint32_t mw=s16+SM_M+warp*512;
  const uint32_t XB=sb+SM_MB, KVB=sb+SM_MB+8;
  GT(0);
  asm volatile("griddepcontrol.launch_dependents;");
  if(tid==0){
    mbar_init(XB,1); mbar_init(KVB,1);
    asm volatile("fence.mbarrier_init.release.cluster;":::"memory");
    mbar_expect(XB,6912);
  }
  uint32_t wr[10-WMK][3][4];
  uint32_t wo[12-OMK][2][4];
  #pragma unroll
  for(int p=0;p<5;p++){
    #pragma unroll
    for(int i=0;i<12;i++){
      const int idx=tid+256*i, row=idx>>3, ch=idx&7, m=row>>7, f=160*((row>>5)&3)+32*p+(row&31);
      const bf16* src=(m==0?Wq:(m==1?Wk:Wv))+(size_t)f*HD+h*DH+64*c+ch*8;
      const int sw=(((row>>3)&3)<<1)|(row&1);
      cp16(sb+SM_STG+row*128+((ch^sw)<<4),src);
    }
    cp_wait_all(); __syncthreads();
    #pragma unroll
    for(int e=0;e<2;e++){
      const int k=2*p+e;
      const int fo=8*((lane&7)>>1)+4*e+2*(lane>>4)+(lane&1);
      const int sw=(((fo>>3)&3)<<1)|(fo&1);
      #pragma unroll
      for(int tt=0;tt<6;tt++){
        const int m=tt<4?mg:2, ti=tt<4?tt:(tt-4+2*mg);
        const uint32_t a=sb+SM_STG+((m*4+kq)*32+fo)*128+(((2*ti+((lane>>3)&1))^sw)<<4);
        if(tt<3&&k<10-WMK) ldsm4t(wr[k<10-WMK?k:0][tt<3?tt:0],a);
        else { uint32_t r[4]; ldsm4t(r,a); const int slot=tt>=3? k*3+tt-3 : 30+(k-(10-WMK))*3+tt; sts4r(mw+slot*4096,r); }
      }
    }
    __syncthreads();
  }
  const int ntile=c==0?14:13, tile0=c==0?0:(1+13*c);
  #pragma unroll
  for(int r=0;r<2;r++){
    for(int idx=tid;idx<96*28;idx+=256){
      const int row=idx/28, ch=idx-row*28;
      if(ch<2*ntile) cp16(sb+SM_STG+row*464+ch*16,Wo+(size_t)(h*DH+96*r+row)*D+tile0*16+ch*8);
    }
    cp_wait_all(); __syncthreads();
    #pragma unroll
    for(int kk=0;kk<6;kk++){
      const int ks=6*r+kk;
      #pragma unroll
      for(int i=0;i<2;i++){
        int tl=2*warp+i; if(tl>=ntile) tl=0;
        const uint32_t a=sb+SM_STG+(16*kk+(lane&7)+(lane>>4)*8)*464+(2*tl+((lane>>3)&1))*16;
        if(ks<12-OMK) ldsm4t(wo[ks<12-OMK?ks:0][i],a);
        else { uint32_t rr[4]; ldsm4t(rr,a); sts4r(mw+(30+3*WMK+(ks-(12-OMK))*2+i)*4096,rr); }
      }
    }
    __syncthreads();
  }
  auto kv_issue=[&](int sn){
    fence_async();
    if(lane==0){
      mbar_expect(KVB,32*512);
      tma2d(sb+SM_KX,&tmK,h*DH+64*c,sn*32,KVB);
      #pragma unroll
      for(int i=0;i<3;i++) tma2d(sb+SM_VX+i*4096,&tmV,h*DH+64*i,sn*32,KVB);
    }
    __syncwarp();
  };
  auto kv_pf=[&](int sn){
    if(lane==0){ tma2d_pf(&tmK,h*DH+64*c,sn*32); tma2d_pf(&tmV,h*DH+64*c,sn*32); }
    __syncwarp();
  };
  if(warp==7){ kv_issue(0); kv_pf(1); kv_pf(2); }
  cluster_sync();
  const bool isred=(b%6)<5; const int rline=(b/6)*5+(b%6);
  bool dead=false;
  uint32_t rsc[3];
  #pragma unroll
  for(int r=0;r<3;r++) rsc[r]=mapa(sb,r);
  uint32_t wm[WMK][3][4];
  #pragma unroll
  for(int k=0;k<WMK;k++)
    #pragma unroll
    for(int j=0;j<3;j++) lds4r(wm[k][j],mw+(30+k*3+j)*4096);

  GT(1);
  #define MB0(k) (((k)&1)?mv[(k)>>1].z:mv[(k)>>1].x)
  #define MB1(k) (((k)&1)?mv[(k)>>1].w:mv[(k)>>1].y)
  #pragma unroll 1
  for(int s=0;s<NSEG;s++){
    const uint32_t tg=1+(s&1);
    uint32_t sbuf[NB][4];
    #pragma unroll
    for(int i=0;i<NB;i++) lds4r(sbuf[i],mw+i*4096);
    uint4 mv[5];
    {
      const uint32_t* src=(const uint32_t*)((const char*)g_mem+(uint32_t)((s*RCOPY+(b%RCOPY))*10240+(kq*20+t)*128+g*16));
      auto okf=[&](const uint4& v){ return v.x!=SENT&&v.y!=SENT&&v.z!=SENT&&v.w!=SENT; };
      const uint32_t mx=s16+SM_RED+kq*6144;
      if(mg==0){
        poll1<3>(mv,[&](int i){ return ldg_rlx4(src+i*128); },okf,dead,1);
        TW(0);
        #pragma unroll
        for(int p=0;p<3;p++) sts4(mx+(4+p)*512,mv[p]);
        bar_sync(8+kq,64);
        mv[3]=lds4(mx); mv[4]=lds4(mx+512);
      } else {
        poll1<2>(mv+3,[&](int i){ return ldg_rlx4(src+(3+i)*128); },okf,dead,1);
        TW(0);
        sts4(mx,mv[3]); sts4(mx+512,mv[4]);
        bar_sync(8+kq,64);
        #pragma unroll
        for(int p=0;p<3;p++) mv[p]=lds4(mx+(4+p)*512);
      }
    }
    TS(0); TF(0);
    {
      float acc[6][4];
      #pragma unroll
      for(int i=0;i<6;i++){ acc[i][0]=acc[i][1]=acc[i][2]=acc[i][3]=0.f; }
      #pragma unroll
      for(int k=0;k<10;k++){
        #pragma unroll
        for(int j=0;j<3;j++){
          if(k<10-WMK) mma16816(acc[j],wr[k<10-WMK?k:0][j],MB0(k),MB1(k)); else mma16816(acc[j],wm[k>=10-WMK?k-(10-WMK):0][j],MB0(k),MB1(k));
          const int i=3*k+j;
          mma16816(acc[3+j],sbuf[i%NB],MB0(k),MB1(k));
          if(i+NB<30) lds4r(sbuf[i%NB],mw+(i+NB)*4096);
        }
      }
      TF(1);
      const uint32_t ra=s16+SM_RED+kq*6144;
      #pragma unroll
      for(int i=0;i<4;i++) sts4f(ra+(4*mg+i)*512,acc[i]);
      sts4f(ra+(8+2*mg)*512,acc[4]); sts4f(ra+(9+2*mg)*512,acc[5]);
    }
    bar_sync(1,256);
    TS(1);
    {
      const uint32_t ra=s16+SM_RED+warp*512;
      float4 a=lds4f(ra), c1=lds4f(ra+6144), d2=lds4f(ra+12288), e2=lds4f(ra+18432);
      uint32_t p0=pack_bf16((a.x+c1.x)+(d2.x+e2.x),(a.y+c1.y)+(d2.y+e2.y)), p1=pack_bf16((a.z+c1.z)+(d2.z+e2.z),(a.w+c1.w)+(d2.w+e2.w));
      TF(2);
      uint32_t f0=movm(p0), f1=movm(p1);
      sts2(s8+SM_QKF+warp*256,f0,f1);
    }
    { int gd=0; while(!mbar_try(KVB,s&1)){ if(dead) break; if(++gd>GUARD){ dead=true; g_err=6; } } }
    uint32_t kb[8];
    if(warp>=1&&warp<5){
      const uint32_t ka=sb+SM_KX+(8*(warp-1)+(lane&7))*128+(((lane>>3)^(lane&7))<<4);
      ldsm4(kb,ka); ldsm4(kb+4,ka^64);
    }
    TF(3);
    bar_sync(1,256);
    if(warp<5){
      uint2 q[4];
      #pragma unroll
      for(int k=0;k<4;k++) q[k]=lds2(s8+SM_QKF+k*256);
      if(warp==0){
        #pragma unroll
        for(int k=0;k<4;k++){ uint2 u=lds2(s8+SM_QKF+(4+k)*256); kb[2*k]=u.x; kb[2*k+1]=u.y; }
      }
      TF(4);
      float sc[4]={0.f,0.f,0.f,0.f}, sd[4]={0.f,0.f,0.f,0.f};
      { uint32_t a[4]={q[0].x,0u,q[0].y,0u}; mma16816(sc,a,kb[0],kb[1]); }
      { uint32_t a[4]={q[1].x,0u,q[1].y,0u}; mma16816(sd,a,kb[2],kb[3]); }
      { uint32_t a[4]={q[2].x,0u,q[2].y,0u}; mma16816(sc,a,kb[4],kb[5]); }
      { uint32_t a[4]={q[3].x,0u,q[3].y,0u}; mma16816(sd,a,kb[6],kb[7]); }
      const uint32_t w0=__float_as_uint(sc[0]+sd[0]), w1=__float_as_uint(sc[1]+sd[1]);
      const uint32_t off=SM_SCX+(c*5+warp)*256+lane*8;
      #pragma unroll
      for(int r=0;r<3;r++) st_async2(rsc[r]+off,w0,w1,rsc[r]+SM_MB);
    }
    if(warp>=4){
      const uint32_t ra=s16+SM_RED+(4+warp)*512;
      float4 a=lds4f(ra), c1=lds4f(ra+6144), d2=lds4f(ra+12288), e2=lds4f(ra+18432);
      uint32_t p0=pack_bf16((a.x+c1.x)+(d2.x+e2.x),(a.y+c1.y)+(d2.y+e2.y)), p1=pack_bf16((a.z+c1.z)+(d2.z+e2.z),(a.w+c1.w)+(d2.w+e2.w));
      const uint32_t off=SM_VMX+(4*c+warp-4)*256+lane*8;
      #pragma unroll
      for(int r=0;r<3;r++) st_async2(rsc[r]+off,p0,p1,rsc[r]+SM_MB);
    }
    TS(2); TF(5);
    const int T0=warp<4?2*warp:4+warp;
    uint32_t va[2][2][4];
    {
      const uint32_t vaddr=sb+SM_VX+(T0>>2)*4096+((lane>>4)*8+(lane&7))*128+(((2*(T0&3)+((lane>>3)&1))^(lane&7))<<4);
      ldsm4t(va[0][0],vaddr); ldsm4t(va[0][1],vaddr+2048);
      if(warp<4){ ldsm4t(va[1][0],vaddr^32); ldsm4t(va[1][1],(vaddr^32)+2048); }
    }
    uint32_t om[OMK][2][4];
    #pragma unroll
    for(int k=0;k<OMK;k++)
      #pragma unroll
      for(int i=0;i<2;i++) lds4r(om[k][i],mw+(30+3*WMK+k*2+i)*4096);
    TF(6);
    { int gd=0; while(!mbar_try_cl(XB,s&1)){ if(dead) break; if(++gd>GUARD){ dead=true; g_err=2; } } }
    TS(3); TF(7);
    if(tid==224) mbar_expect(XB,6912);
    {
      float sv[10];
      #pragma unroll
      for(int n=0;n<5;n++){
        float2 u0=lds2f(s8+SM_SCX+n*256), u1=lds2f(s8+SM_SCX+(5+n)*256), u2=lds2f(s8+SM_SCX+(10+n)*256);
        sv[2*n]=rb(rb((u0.x+u1.x)+u2.x)*0.07216878364870322f); sv[2*n+1]=rb(rb((u0.y+u1.y)+u2.y)*0.07216878364870322f);
      }
      uint2 vm0=lds2(s8+SM_VMX+T0*256), vm1=lds2(s8+SM_VMX+(T0+(warp<4?1:0))*256);
      TF(8);
      float mx=fmaxf(fmaxf(fmaxf(sv[0],sv[1]),fmaxf(sv[2],sv[3])),fmaxf(fmaxf(fmaxf(sv[4],sv[5]),fmaxf(sv[6],sv[7])),fmaxf(sv[8],sv[9])));
      mx=fmaxf(mx,__shfl_xor_sync(~0u,mx,1)); mx=fmaxf(mx,__shfl_xor_sync(~0u,mx,2));
      const float mxl=mx*1.4426950408889634f;
      #pragma unroll
      for(int i=0;i<10;i++) sv[i]=ex2(fmaf(sv[i],1.4426950408889634f,-mxl));
      float sum=((sv[0]+sv[1])+(sv[2]+sv[3]))+(((sv[4]+sv[5])+(sv[6]+sv[7]))+(sv[8]+sv[9]));
      sum+=__shfl_xor_sync(~0u,sum,1); sum+=__shfl_xor_sync(~0u,sum,2);
      const float inv=rcp(sum);
      uint32_t pp[5];
      #pragma unroll
      for(int n=0;n<5;n++) pp[n]=pack_bf16(sv[2*n]*inv,sv[2*n+1]*inv);
      TF(9);
      float o[4]={0.f,0.f,0.f,0.f}, o2[4]={0.f,0.f,0.f,0.f};
      mma1688(o,vm0.x,vm0.y,pp[0]); mma16816(o2,va[0][1],pp[3],pp[4]);
      if(warp<4){
        float u[4]={0.f,0.f,0.f,0.f}, u2[4]={0.f,0.f,0.f,0.f};
        mma1688(u,vm1.x,vm1.y,pp[0]); mma16816(u2,va[1][1],pp[3],pp[4]);
        mma16816(o,va[0][0],pp[1],pp[2]); mma16816(u,va[1][0],pp[1],pp[2]);
        uint32_t f0=movm(pack_bf16(o[0]+o2[0],o[1]+o2[1])), f1=movm(pack_bf16(o[2]+o2[2],o[3]+o2[3]));
        uint32_t f2=movm(pack_bf16(u[0]+u2[0],u[1]+u2[1])), f3=movm(pack_bf16(u[2]+u2[2],u[3]+u2[3]));
        sts4(s16+SM_O+warp*512,make_uint4(f0,f1,f2,f3));
      } else {
        mma16816(o,va[0][0],pp[1],pp[2]);
        uint32_t f0=movm(pack_bf16(o[0]+o2[0],o[1]+o2[1])), f1=movm(pack_bf16(o[2]+o2[2],o[3]+o2[3]));
        sts2(s16+SM_O+(T0>>1)*512+(T0&1)*8,f0,f1);
      }
    }
    TF(10);
    bar_sync(1,256);
    if(warp<7){
      uint4 ob[6];
      #pragma unroll
      for(int i=0;i<6;i++) ob[i]=lds4(s16+SM_O+i*512);
      TF(11);
      float ca[2][2][4];
      #pragma unroll
      for(int i=0;i<2;i++)
        #pragma unroll
        for(int j=0;j<2;j++){ ca[i][j][0]=ca[i][j][1]=ca[i][j][2]=ca[i][j][3]=0.f; }
      #pragma unroll
      for(int ks=0;ks<12;ks++){
        const uint32_t b0=(ks&1)?ob[ks>>1].z:ob[ks>>1].x, b1=(ks&1)?ob[ks>>1].w:ob[ks>>1].y;
        #pragma unroll
        for(int i=0;i<2;i++){ if(ks<12-OMK) mma16816(ca[i][ks&1],wo[ks<12-OMK?ks:0][i],b0,b1); else mma16816(ca[i][ks&1],om[ks>=12-OMK?ks-(12-OMK):0][i],b0,b1); }
      }
      TF(12);
      uint32_t* dst=(uint32_t*)((char*)g_part+(uint32_t)(((2*(tile0+2*warp))*32+h)*256+lane*8));
      #pragma unroll
      for(int i=0;i<2;i++){
        if(i==0||2*warp+1<ntile){
          stg_rlx2(dst+(2*i)*2048,(__float_as_uint(ca[i][0][0]+ca[i][1][0])&~3u)|tg,(__float_as_uint(ca[i][0][1]+ca[i][1][1])&~3u)|tg);
          stg_rlx2(dst+(2*i+1)*2048,(__float_as_uint(ca[i][0][2]+ca[i][1][2])&~3u)|tg,(__float_as_uint(ca[i][0][3]+ca[i][1][3])&~3u)|tg);
        }
      }
    } else {
      if(s+1<NSEG) kv_issue(s+1);
      const uint32_t o=(uint32_t)(((s*H+h)*12+4*c)*256+lane*8);
      #pragma unroll
      for(int k=0;k<4;k++){
        uint2 u=lds2(s8+SM_QKF+(4+k)*256); stg_rlx2((uint32_t*)((char*)g_kmf+o+k*256),u.x,u.y);
        uint2 w=lds2(s8+SM_VMX+(4*c+k)*256); stg_rlx2((uint32_t*)((char*)g_vmf+o+k*256),w.x,w.y);
      }
      if(s+3<NSEG) kv_pf(s+3);
      if(isred&&lane<RCOPY&&s+3<=NSEG) asm volatile("prefetch.global.L2 [%0];"::"l"(g_mem+(size_t)((s+3)*RCOPY+lane)*2560+rline*32));
    }
    TW(1);
    TS(4); TF(13);
    #pragma unroll
    for(int k=0;k<WMK;k++)
      #pragma unroll
      for(int j=0;j<3;j++) lds4r(wm[k][j],mw+(30+k*3+j)*4096);
    if(isred){
      const uint32_t* src=(const uint32_t*)((char*)g_part+(uint32_t)((rline*32+4*warp)*256+lane*16));
      uint32_t* mdst=g_mem+(size_t)((s+1)*RCOPY)*2560+rline*32+lane;
      uint4 v[2]; float f[4];
      poll1<2>(v,[&](int i){ return ldg_rlx4(src+i*128); },[&](const uint4& v){ return (v.x&3u)==tg&&(v.y&3u)==tg&&(v.z&3u)==tg&&(v.w&3u)==tg; },dead,4);
      f[0]=__uint_as_float(v[0].x)+__uint_as_float(v[1].x); f[1]=__uint_as_float(v[0].y)+__uint_as_float(v[1].y); f[2]=__uint_as_float(v[0].z)+__uint_as_float(v[1].z); f[3]=__uint_as_float(v[0].w)+__uint_as_float(v[1].w);
      TW(2); TF(14);
      #pragma unroll
      for(int i=0;i<4;i++) f[i]+=__shfl_xor_sync(~0u,f[i],16);
      if(lane<16) sts4f(s16+SM_RSUM+warp*256,f);
      if(warp==0){
        bar_sync(2,256);
        TS(5);
        const float* rp=(const float*)(sm+SM_RSUM)+(lane&3)*16+(lane>>2);
        float a0=((rp[0]+rp[64])+(rp[128]+rp[192]))+((rp[256]+rp[320])+(rp[384]+rp[448]));
        float a1=((rp[8]+rp[72])+(rp[136]+rp[200]))+((rp[264]+rp[328])+(rp[392]+rp[456]));
        uint32_t o=pack_bf16(a0,a1); if(o==SENT) o=0x7FFF7FFFu;
        #pragma unroll
        for(int cc=0;cc<RCOPY;cc++) stg_rlx1(mdst+cc*2560,o);
        TS(6); TW(3);
      } else bar_arrive(2,256);
    }
    TF(15);
    if(warp==7){ fence_gpu(); if(lane==0) stg_rlx1(g_flag+b*32,s+1); }
  }
  GT(2);
  cluster_sync();
}

enum { M_XN=0,M_Y,M_H,M_OX,M_K,M_V,M_GATE,M_WQ,M_WK,M_WV,M_W1,M_W2,M_WO,M_NUM };
struct WParams { CUtensorMap m[M_NUM]; const bf16* x; const bf16* b1; const bf16* b2; bf16* out; };
enum { T_RED=0,T_OP=1,T_QA=2,T_M2=3,T_M1=4,T_KV=5,T_END=6 };
constexpr int NRB=16, NSPL=8, NREDI=20;
constexpr int STG=49152, NST=4;
constexpr int W_STAGING=NST*STG;
constexpr int W_BAR=W_STAGING+32768;
constexpr int W_TOTAL=W_BAR+256;
#define WGUARD 2000000

__device__ __forceinline__ void wg_arrive(){ asm volatile("wgmma.fence.sync.aligned;":::"memory"); }
__device__ __forceinline__ void wg_commit(){ asm volatile("wgmma.commit_group.sync.aligned;":::"memory"); }
template<int N> __device__ __forceinline__ void wg_wait(){ asm volatile("wgmma.wait_group.sync.aligned %0;"::"n"(N):"memory"); }
__device__ __forceinline__ void mbar_arrive(uint32_t a){ asm volatile("mbarrier.arrive.shared.b64 _, [%0];"::"r"(a):"memory"); }
__device__ __forceinline__ void mbar_wait(uint32_t a,uint32_t par){ int gd=0; while(!mbar_try(a,par)){ if(++gd>WGUARD){ g_err=20; break; } } }
__device__ __forceinline__ uint32_t ld_acq(const uint32_t* p){ uint32_t v; asm volatile("ld.acquire.gpu.global.u32 %0, [%1];":"=r"(v):"l"(p):"memory"); return v; }
__device__ __forceinline__ uint32_t ld_rlx(const uint32_t* p){ uint32_t v; asm volatile("ld.relaxed.gpu.global.u32 %0, [%1];":"=r"(v):"l"(p):"memory"); return v; }
__device__ __forceinline__ uint2 ld_rlx2(const uint2* p){ uint2 v; asm volatile("ld.relaxed.gpu.global.v2.u32 {%0,%1}, [%2];":"=r"(v.x),"=r"(v.y):"l"(p):"memory"); return v; }
__device__ __forceinline__ float4 ld_rlx4f(const float4* p){ float4 v; asm volatile("ld.relaxed.gpu.global.v4.f32 {%0,%1,%2,%3}, [%4];":"=f"(v.x),"=f"(v.y),"=f"(v.z),"=f"(v.w):"l"(p):"memory"); return v; }
__device__ __forceinline__ void red_rel(uint32_t* p){ asm volatile("red.release.gpu.global.add.u32 [%0], 1;"::"l"(p):"memory"); }
__device__ __forceinline__ void fence_async_all(){ asm volatile("fence.proxy.async;":::"memory"); }
__device__ __forceinline__ void tma_st(const CUtensorMap* tm,uint32_t src,int c0,int c1){
  asm volatile("cp.async.bulk.tensor.2d.global.shared::cta.bulk_group [%0, {%2, %3}], [%1];"::"l"(tm),"r"(src),"r"(c0),"r"(c1):"memory"); }
__device__ __forceinline__ void bulk_commit(){ asm volatile("cp.async.bulk.commit_group;":::"memory"); }
__device__ __forceinline__ void bulk_wait_rd(){ asm volatile("cp.async.bulk.wait_group.read 0;":::"memory"); }
__device__ __forceinline__ void bulk_wait(){ asm volatile("cp.async.bulk.wait_group 0;":::"memory"); }
__device__ __forceinline__ void stsm4(uint32_t a,uint32_t r0,uint32_t r1,uint32_t r2,uint32_t r3){ asm volatile("stmatrix.sync.aligned.m8n8.x4.shared.b16 [%0], {%1,%2,%3,%4};"::"r"(a),"r"(r0),"r"(r1),"r"(r2),"r"(r3):"memory"); }

template<int N> __device__ __forceinline__ void mainloop(float* acc,int nkb,uint32_t sb,int wg,int lane,uint32_t& st,uint32_t& ph){
  uint32_t pst=0;
  #pragma unroll 1
  for(int kb=0;kb<nkb;kb++){
    mbar_wait(sb+W_BAR+st*8,ph);
    const uint32_t a=sb+st*STG+wg*8192, bq=sb+st*STG+16384;
    const uint64_t da=(uint64_t)((a>>4)&0x3fff)|(1ull<<16)|(64ull<<32)|(1ull<<62);
    const uint64_t db=(uint64_t)((bq>>4)&0x3fff)|(512ull<<16)|(64ull<<32)|(1ull<<62);
    wg_arrive();
    #pragma unroll
    for(int k=0;k<4;k++) wgmma<N>(acc,da+2*k,db+128*k,kb|k);
    wg_commit();
    if(kb>0){ wg_wait<1>(); if(lane==0) mbar_arrive(sb+W_BAR+32+pst*8); }
    pst=st; if(++st==NST){ st=0; ph^=1; }
  }
  wg_wait<0>();
  if(lane==0) mbar_arrive(sb+W_BAR+32+pst*8);
}
template<int N> __device__ __forceinline__ void store_tile(const float* acc,const CUtensorMap* tm,int col0,int row0,uint32_t sb,int wg,int wq,int lane,bool el){
  const uint32_t stg=sb+W_STAGING+wg*16384;
  const int r=16*wq+(lane&7)+((lane>>3)&1)*8;
  const uint32_t ra=stg+r*128; const int sw=lane&7, hi=lane>>4;
  #pragma unroll
  for(int rd=0;rd<(N+127)/128;rd++){
    if(el) bulk_wait_rd();
    bar_sync(2+wg,128);
    #pragma unroll
    for(int j=0;j<8;j++){
      const int J=rd*8+j;
      if(J*16<N) stsm4(ra+(j>>2)*8192+((((2*j+hi)&7)^sw)<<4),pack_bf16(acc[8*J],acc[8*J+1]),pack_bf16(acc[8*J+2],acc[8*J+3]),pack_bf16(acc[8*J+4],acc[8*J+5]),pack_bf16(acc[8*J+6],acc[8*J+7]));
    }
    fence_async();
    bar_sync(2+wg,128);
    if(el){
      tma_st(tm,stg,col0+rd*128,row0);
      if(rd*128+64<N) tma_st(tm,stg+8192,col0+rd*128+64,row0);
      bulk_commit();
    }
  }
}
template<int N,int ACT> __device__ __forceinline__ void bias_act(float* acc,const bf16* bias,int t){
  #pragma unroll
  for(int n=0;n<N/8;n++){
    const uint32_t u=__ldg((const uint32_t*)(bias+8*n+2*t));
    const float b0=__uint_as_float(u<<16), b1=__uint_as_float(u&0xffff0000u);
    #pragma unroll
    for(int i=0;i<4;i++){
      float r=rb(rb(acc[4*n+i])+((i&1)?b1:b0));
      if(ACT==1){ const float uu=0.7978845608028654f*(r+0.044715f*r*r*r); const float e=ex2(uu*2.885390081777927f); const float th=1.f-__fdividef(2.f,1.f+e); r=0.5f*r*(1.f+th); }
      else { r=__fdividef(r,1.f+ex2(-r*1.4426950408889634f)); }
      acc[4*n+i]=r;
    }
  }
}
template<int N> __device__ __forceinline__ void store_part(const float* acc,float4* dst){
  #pragma unroll
  for(int n=0;n<N/8;n++) __stcg(dst+(n>>4)*4096+(n&15)*128,make_float4(acc[4*n],acc[4*n+1],acc[4*n+2],acc[4*n+3]));
}

__device__ __forceinline__ bool item_ready(int c,int idx){
  if(c==T_RED){ const int rbk=idx/NREDI; return ld_acq(g_cnt+C_OP+rbk)>=2*3*NSPL && ld_acq(g_cnt+C_M2+rbk)>=6; }
  if(c==T_OP){ const int rbk=idx/(3*NSPL), sp=(idx-rbk*3*NSPL)/3; return ld_acq(g_cnt+C_QA+rbk*NSPL+sp)>=8; }
  if(c==T_QA){ const uint32_t need=4*(idx>>5)+4; const uint32_t* f=g_flag+(idx&31)*96; return ld_acq(f)>=need && ld_acq(f+32)>=need && ld_acq(f+64)>=need; }
  if(c==T_M2){ return ld_acq(g_cnt+C_M1+idx/3)>=12; }
  return true;
}

template<int MODE>
__global__ void __launch_bounds__(384,1) k_work(const __grid_constant__ WParams P){
  extern __shared__ __align__(1024) uint8_t sm[];
  const uint32_t sb=(uint32_t)__cvta_generic_to_shared(sm);
  const int tid=threadIdx.x, warp=__shfl_sync(~0u,tid>>5,0), lane=tid&31;
  const uint32_t FULL=sb+W_BAR, EMPTY=sb+W_BAR+32, IFULL=sb+W_BAR+64, IEMPTY=sb+W_BAR+80;
  volatile int* idesc=(volatile int*)(sm+W_BAR+128);
  if(tid==0){
    for(int i=0;i<NST;i++){ mbar_init(FULL+i*8,1); mbar_init(EMPTY+i*8,8); }
    for(int i=0;i<2;i++){ mbar_init(IFULL+i*8,1); mbar_init(IEMPTY+i*8,8); }
    asm volatile("fence.mbarrier_init.release.cluster;":::"memory");
  }
  __syncthreads();
  if(warp>=8){
    asm volatile("setmaxnreg.dec.sync.aligned.u32 40;");
    if(warp==8){
      uint32_t st=0, ph=1, it=0;
      int held=-1; int guard=0;
      const int ncls=lane==T_RED?NRB*NREDI:(lane==T_OP?NRB*3*NSPL:(lane==T_QA?NRB*32:(lane==T_M2?NRB*3:(lane==T_M1?NRB*6:0))));
      int sidx=blockIdx.x;
      while(true){
        int type, idx;
        if(MODE==0){ if(sidx<NRB*48){ type=T_KV; idx=sidx; sidx+=gridDim.x; } else { type=T_END; idx=0; } }
        else {
          while(true){
            int cand=held; bool rdy=false;
            if(lane<5){
              if(cand<0){ cand=(int)ld_rlx(g_cnt+C_NEXT+lane*32); if(cand>=ncls) cand=-1; }
              if(cand>=0) rdy=item_ready(lane,cand);
            }
            const uint32_t br=__ballot_sync(~0u,rdy), ba=__ballot_sync(~0u,cand>=0);
            if(!ba){ type=T_END; idx=0; break; }
            if(br){
              const int w=__ffs(br)-1; int got=-1;
              if(lane==w){
                if(held>=0){ got=held; held=-1; }
                else { int tk=(int)atomicAdd(g_cnt+C_NEXT+lane*32,1u); if(tk<ncls){ if(tk==cand||item_ready(lane,tk)) got=tk; else held=tk; } }
              }
              got=__shfl_sync(~0u,got,w);
              if(got>=0){ type=w; idx=got; break; }
            } else {
              __nanosleep(100);
              if(++guard>WGUARD){ g_err=21; type=T_END; idx=0; break; }
            }
          }
        }
        __syncwarp();
        if(lane==0){
          const uint32_t sl=it&1;
          mbar_wait(IEMPTY+sl*8,((it>>1)&1)^1);
          idesc[sl*2]=type; idesc[sl*2+1]=idx;
          mbar_arrive(IFULL+sl*8);
          if(type!=T_END&&type!=T_RED){
            int ma,mb,row0,col0,k0=0,nkb,nbox;
            if(type==T_KV){ const int rbk=idx/48, nt=idx-rbk*48; ma=M_XN; mb=nt<24?M_WK:M_WV; row0=rbk*128; col0=(nt<24?nt:nt-24)*256; nkb=10; nbox=4; }
            else if(type==T_M1){ const int rbk=idx/6, nt=idx-rbk*6; ma=M_Y; mb=M_W1; row0=rbk*128; col0=nt*256; nkb=10; nbox=4; }
            else if(type==T_M2){ const int rbk=idx/3, nt=idx-rbk*3; ma=M_H; mb=M_W2; row0=rbk*128; col0=nt*256; nkb=24; nbox=nt<2?4:2; }
            else if(type==T_QA){ ma=M_XN; mb=M_WQ; row0=(idx>>5)*128; col0=(idx&31)*192; nkb=10; nbox=3; }
            else { const int rbk=idx/(3*NSPL), r=idx-rbk*3*NSPL, sp=r/3, nt=r-sp*3; ma=M_OX; mb=M_WO; row0=rbk*128; col0=nt*256; k0=sp*(HD/NSPL); nkb=HD/NSPL/64; nbox=nt<2?4:2; }
            if(MODE) fence_async_all();
            const CUtensorMap* A=&P.m[ma]; const CUtensorMap* B=&P.m[mb];
            for(int kb=0;kb<nkb;kb++){
              mbar_wait(EMPTY+st*8,ph);
              const uint32_t d=sb+st*STG, fb=FULL+st*8;
              mbar_expect(fb,16384+nbox*8192);
              const int kk=k0+kb*64;
              tma2d(d,A,kk,row0,fb); tma2d(d+8192,A,kk,row0+64,fb);
              for(int j=0;j<nbox;j++) tma2d(d+16384+j*8192,B,col0+j*64,kk,fb);
              if(++st==NST){ st=0; ph^=1; }
            }
            if(type==T_QA){
              for(int q=0;q<2;q++){
                mbar_wait(EMPTY+st*8,ph);
                const uint32_t d=sb+st*STG, fb=FULL+st*8;
                mbar_expect(fb,49152);
                for(int j=0;j<6;j++) tma2d(d+j*8192,&P.m[M_K+q],col0+(j%3)*64,row0+(j/3)*64,fb);
                if(++st==NST){ st=0; ph^=1; }
              }
            }
          }
        }
        __syncwarp();
        it++;
        if(type==T_END) break;
      }
    }
  } else {
    asm volatile("setmaxnreg.inc.sync.aligned.u32 232;");
    const int wg=warp>>2, wq=warp&3, g=lane>>2, t=lane&3;
    const bool el=(tid&127)==0;
    uint32_t st=0, ph=0;
    float acc[128];
    #pragma unroll 1
    for(uint32_t it=0;;it++){
      const uint32_t sl=it&1;
      mbar_wait(IFULL+sl*8,(it>>1)&1);
      const int type=idesc[sl*2], idx=idesc[sl*2+1];
      __syncwarp();
      if(lane==0) mbar_arrive(IEMPTY+sl*8);
      if(type==T_END) break;
      uint32_t* cnt=nullptr;
      if(MODE==0||type==T_KV){
        const int rbk=idx/48, nt=idx-rbk*48;
        mainloop<256>(acc,10,sb,wg,lane,st,ph);
        store_tile<256>(acc,&P.m[nt<24?M_K:M_V],(nt<24?nt:nt-24)*256,rbk*128+wg*64,sb,wg,wq,lane,el);
      } else if(type==T_M1){
        const int rbk=idx/6, nt=idx-rbk*6;
        mainloop<256>(acc,10,sb,wg,lane,st,ph);
        bias_act<256,1>(acc,P.b1+nt*256,t);
        store_tile<256>(acc,&P.m[M_H],nt*256,rbk*128+wg*64,sb,wg,wq,lane,el);
        cnt=g_cnt+C_M1+rbk;
      } else if(type==T_M2){
        const int rbk=idx/3, nt=idx-rbk*3;
        if(nt<2){
          mainloop<256>(acc,24,sb,wg,lane,st,ph);
          bias_act<256,2>(acc,P.b2+nt*256,t);
          store_tile<256>(acc,&P.m[M_GATE],nt*256,rbk*128+wg*64,sb,wg,wq,lane,el);
        } else {
          mainloop<128>(acc,24,sb,wg,lane,st,ph);
          bias_act<128,2>(acc,P.b2+nt*256,t);
          store_tile<128>(acc,&P.m[M_GATE],nt*256,rbk*128+wg*64,sb,wg,wq,lane,el);
        }
        cnt=g_cnt+C_M2+rbk;
      } else if(type==T_OP){
        const int rbk=idx/(3*NSPL), r=idx-rbk*3*NSPL, sp=r/3, nt=r-sp*3;
        float4* dst=g_opp+(size_t)(((rbk*NSPL+sp)*5+2*nt)*2+wg)*2048+(tid&127);
        if(nt<2){ mainloop<256>(acc,HD/NSPL/64,sb,wg,lane,st,ph); store_part<256>(acc,dst); }
        else { mainloop<128>(acc,HD/NSPL/64,sb,wg,lane,st,ph); store_part<128>(acc,dst); }
        __threadfence();
        bar_sync(2+wg,128);
        if(el) red_rel(g_cnt+C_OP+rbk);
      } else if(type==T_RED){
        const int rbk=idx/NREDI, r=idx-rbk*NREDI, cb=r>>2, jq=r&3;
        const float4* src=g_opp+(size_t)((rbk*NSPL*5+cb)*2+wg)*2048+jq*512+(tid&127);
        float4 v[4][NSPL];
        #pragma unroll
        for(int j=0;j<4;j++)
          #pragma unroll
          for(int s=0;s<NSPL;s++) v[j][s]=ld_rlx4f(src+(size_t)s*5*4096+j*128);
        const int row=rbk*128+wg*64+wq*16+g;
        #pragma unroll
        for(int j=0;j<4;j++){
          const int col=cb*128+(4*jq+j)*8+2*t;
          float4 a=v[j][0];
          #pragma unroll
          for(int s=1;s<NSPL;s++){ a.x+=v[j][s].x; a.y+=v[j][s].y; a.z+=v[j][s].z; a.w+=v[j][s].w; }
          #pragma unroll
          for(int hh=0;hh<2;hh++){
            const size_t o=(size_t)(row+8*hh)*D+col;
            const uint32_t gx=ld_rlx((const uint32_t*)(g_gate+o)), xx=__ldg((const uint32_t*)(P.x+o));
            const float s0=rb(hh?a.z:a.x), s1=rb(hh?a.w:a.y);
            const float o0=__uint_as_float(xx<<16)+rb(s0*__uint_as_float(gx<<16)), o1=__uint_as_float(xx&0xffff0000u)+rb(s1*__uint_as_float(gx&0xffff0000u));
            *(uint32_t*)(P.out+o)=pack_bf16(o0,o1);
          }
        }
      } else {
        const int rbk=idx>>5, h=idx&31;
        const int sgl=wq>>1, rh=wq&1, sg=rbk*4+wg*2+sgl;
        uint2 km[12], vm[12];
        {
          const uint2* kp=g_kmf+(size_t)((sg*H+h)*12)*32+lane; const uint2* vp=g_vmf+(size_t)((sg*H+h)*12)*32+lane;
          #pragma unroll
          for(int i=0;i<12;i++){ km[i]=ld_rlx2(kp+i*32); vm[i]=ld_rlx2(vp+i*32); }
        }
        mainloop<192>(acc,10,sb,wg,lane,st,ph);
        uint32_t pa[2][4], pm[2];
        {
          float sc[5][4];
          #pragma unroll
          for(int n=0;n<5;n++){ sc[n][0]=sc[n][1]=sc[n][2]=sc[n][3]=0.f; }
          mbar_wait(FULL+st*8,ph);
          const int kr=sgl*32+(lane&7)+((lane>>4)<<3);
          const uint32_t ka=sb+st*STG+wg*24576+kr*128; const int cs=(lane>>3)&1, sw=lane&7;
          #pragma unroll
          for(int T=0;T<12;T++){
            uint32_t qf[4]={pack_bf16(acc[8*T],acc[8*T+1]),pack_bf16(acc[8*T+2],acc[8*T+3]),pack_bf16(acc[8*T+4],acc[8*T+5]),pack_bf16(acc[8*T+6],acc[8*T+7])};
            mma16816(sc[0],qf,km[T].x,km[T].y);
            const uint32_t a=ka+(T>>2)*8192+((((T&3)*2+cs)^sw)<<4);
            uint32_t kb[4]; ldsm4(kb,a);
            mma16816(sc[1],qf,kb[0],kb[1]); mma16816(sc[2],qf,kb[2],kb[3]);
            if(rh){ ldsm4(kb,a+2048); mma16816(sc[3],qf,kb[0],kb[1]); mma16816(sc[4],qf,kb[2],kb[3]); }
          }
          __syncwarp();
          if(lane==0) mbar_arrive(EMPTY+st*8);
          if(++st==NST){ st=0; ph^=1; }
          const float NEG=rb(-1e9f);
          float mx[2]={-3.4e38f,-3.4e38f};
          #pragma unroll
          for(int n=0;n<5;n++)
            #pragma unroll
            for(int i=0;i<4;i++){
              float v=rb(rb(sc[n][i])*0.07216878364870322f);
              if(n>0){ const int key=8*(n-1)+2*t+(i&1), row=16*rh+g+8*(i>>1); if(key>row) v=NEG; }
              sc[n][i]=v; mx[i>>1]=fmaxf(mx[i>>1],v);
            }
          float sum[2]={0.f,0.f};
          #pragma unroll
          for(int r=0;r<2;r++){ mx[r]=fmaxf(mx[r],__shfl_xor_sync(~0u,mx[r],1)); mx[r]=fmaxf(mx[r],__shfl_xor_sync(~0u,mx[r],2)); }
          #pragma unroll
          for(int n=0;n<5;n++)
            #pragma unroll
            for(int i=0;i<4;i++){ const float e=ex2((sc[n][i]-mx[i>>1])*1.4426950408889634f); sc[n][i]=e; sum[i>>1]+=e; }
          #pragma unroll
          for(int r=0;r<2;r++){ sum[r]+=__shfl_xor_sync(~0u,sum[r],1); sum[r]+=__shfl_xor_sync(~0u,sum[r],2); sum[r]=rcp(sum[r]); }
          pm[0]=pack_bf16(sc[0][0]*sum[0],sc[0][1]*sum[0]); pm[1]=pack_bf16(sc[0][2]*sum[1],sc[0][3]*sum[1]);
          #pragma unroll
          for(int ks=0;ks<2;ks++){
            pa[ks][0]=pack_bf16(sc[1+2*ks][0]*sum[0],sc[1+2*ks][1]*sum[0]); pa[ks][1]=pack_bf16(sc[1+2*ks][2]*sum[1],sc[1+2*ks][3]*sum[1]);
            pa[ks][2]=pack_bf16(sc[2+2*ks][0]*sum[0],sc[2+2*ks][1]*sum[0]); pa[ks][3]=pack_bf16(sc[2+2*ks][2]*sum[1],sc[2+2*ks][3]*sum[1]);
          }
        }
        {
          mbar_wait(FULL+st*8,ph);
          const int vr=sgl*32+(lane&7)+(((lane>>3)&1)<<3);
          const uint32_t va=sb+st*STG+wg*24576+vr*128; const int cs=lane>>4, sw=lane&7;
          #pragma unroll
          for(int T=0;T<12;T++){
            float* o0=acc+8*T; float* o1=acc+8*T+4;
            #pragma unroll
            for(int i=0;i<8;i++) o0[i]=0.f;
            mma1688(o0,pm[0],pm[1],vm[T].x); mma1688(o1,pm[0],pm[1],vm[T].y);
            const uint32_t a=va+(T>>2)*8192+((((T&3)*2+cs)^sw)<<4);
            uint32_t vb[4]; ldsm4t(vb,a);
            mma16816(o0,pa[0],vb[0],vb[1]); mma16816(o1,pa[0],vb[2],vb[3]);
            ldsm4t(vb,a+2048);
            mma16816(o0,pa[1],vb[0],vb[1]); mma16816(o1,pa[1],vb[2],vb[3]);
          }
          __syncwarp();
          if(lane==0) mbar_arrive(EMPTY+st*8);
          if(++st==NST){ st=0; ph^=1; }
        }
        store_tile<192>(acc,&P.m[M_OX],h*192,rbk*128+wg*64,sb,wg,wq,lane,el);
        cnt=g_cnt+C_QA+rbk*NSPL+(h>>2);
      }
      if(MODE&&cnt&&el){ bulk_wait(); fence_async_all(); red_rel(cnt); }
    }
    if(el) bulk_wait();
  }
}
typedef CUresult (*EncFn)(CUtensorMap*,CUtensorMapDataType,cuuint32_t,void*,const cuuint64_t*,const cuuint64_t*,const cuuint32_t*,const cuuint32_t*,CUtensorMapInterleave,CUtensorMapSwizzle,CUtensorMapL2promotion,CUtensorMapFloatOOBfill);
static CUtensorMap mk2d(const void* base,uint64_t cols,uint64_t rows,uint32_t bc,uint32_t br){
  static EncFn fn=nullptr;
  if(!fn){ void* p=nullptr; cudaDriverEntryPointQueryResult qr; cudaGetDriverEntryPoint("cuTensorMapEncodeTiled",&p,cudaEnableDefault,&qr); fn=(EncFn)p; }
  CUtensorMap m; cuuint64_t gd[2]={cols,rows}; cuuint64_t gs[1]={cols*2}; cuuint32_t bd[2]={bc,br}; cuuint32_t es[2]={1,1};
  fn(&m,CU_TENSOR_MAP_DATA_TYPE_BFLOAT16,2,(void*)base,gd,gs,bd,es,CU_TENSOR_MAP_INTERLEAVE_NONE,CU_TENSOR_MAP_SWIZZLE_128B,CU_TENSOR_MAP_L2_PROMOTION_L2_128B,CU_TENSOR_MAP_FLOAT_OOB_FILL_NONE);
  return m;
}
template<class T> static T* sym(T& s){ void* p; cudaGetSymbolAddress(&p,s); return (T*)p; }
}

int g_reconly=0;
extern "C" void kernel_launch(void* const* d_in, const int* in_sizes, int n_in, void* d_out, int out_size) {
  using namespace rk;
  const bf16* x=(const bf16*)d_in[0]; const bf16* mem0=(const bf16*)d_in[1];
  const bf16* Wq=(const bf16*)d_in[2]; const bf16* Wk=(const bf16*)d_in[3]; const bf16* Wv=(const bf16*)d_in[4]; const bf16* Wo=(const bf16*)d_in[5];
  const bf16* w1=(const bf16*)d_in[8]; const bf16* b1=(const bf16*)d_in[9]; const bf16* w2=(const bf16*)d_in[10]; const bf16* b2=(const bf16*)d_in[11];
  cudaStream_t st=cudaStreamPerThread;
  cudaFuncSetAttribute(k_rec,cudaFuncAttributeMaxDynamicSharedMemorySize,SM_TOTAL);
  cudaFuncSetAttribute(k_work<0>,cudaFuncAttributeMaxDynamicSharedMemorySize,W_TOTAL);
  cudaFuncSetAttribute(k_work<1>,cudaFuncAttributeMaxDynamicSharedMemorySize,W_TOTAL);
  bf16* k=(bf16*)sym(g_k); bf16* v=(bf16*)sym(g_v);
  WParams P;
  P.m[M_XN]=mk2d(sym(g_xn),D,S,64,64); P.m[M_Y]=mk2d(sym(g_y),D,S,64,64); P.m[M_H]=mk2d(sym(g_h),F,S,64,64); P.m[M_OX]=mk2d(sym(g_ox),HD,S,64,64);
  P.m[M_K]=mk2d(k,HD,S,64,64); P.m[M_V]=mk2d(v,HD,S,64,64); P.m[M_GATE]=mk2d(sym(g_gate),D,S,64,64);
  P.m[M_WQ]=mk2d(Wq,HD,D,64,64); P.m[M_WK]=mk2d(Wk,HD,D,64,64); P.m[M_WV]=mk2d(Wv,HD,D,64,64);
  P.m[M_W1]=mk2d(w1,F,D,64,64); P.m[M_W2]=mk2d(w2,D,F,64,64); P.m[M_WO]=mk2d(Wo,D,HD,64,64);
  P.x=x; P.b1=b1; P.b2=b2; P.out=(bf16*)d_out;
  k_pre<<<S/8,256,0,st>>>(x,mem0);
  if(!(g_reconly&1)) k_work<0><<<132,384,W_TOTAL,st>>>(P);
  if(!(g_reconly&4)){
    cudaLaunchConfig_t cfg={}; cfg.gridDim=dim3(NCTA); cfg.blockDim=dim3(256); cfg.dynamicSmemBytes=SM_TOTAL; cfg.stream=st;
    cudaLaunchAttribute at[1]; at[0].id=cudaLaunchAttributeClusterDimension; at[0].val.clusterDim.x=3; at[0].val.clusterDim.y=1; at[0].val.clusterDim.z=1; cfg.attrs=at; cfg.numAttrs=1;
    CUtensorMap tk=mk2d(k,HD,S,64,32), tv=mk2d(v,HD,S,64,32);
    cudaLaunchKernelEx(&cfg,k_rec,tk,tv,Wq,Wk,Wv,Wo);
  }
  if(!(g_reconly&2)){
    cudaLaunchConfig_t cfg={}; cfg.gridDim=dim3(132); cfg.blockDim=dim3(384); cfg.dynamicSmemBytes=W_TOTAL; cfg.stream=st;
    cudaLaunchAttribute at[1]; at[0].id=cudaLaunchAttributeProgrammaticStreamSerialization; at[0].val.programmaticStreamSerializationAllowed=1; cfg.attrs=at; cfg.numAttrs=PDL;
    cudaLaunchKernelEx(&cfg,k_work<1>,P);
  }
}
```

```cpp
#include <cuda_runtime.h>
#include <cuda_bf16.h>
#include <stdint.h>
#include <cuda.h>

namespace rk {
typedef __nv_bfloat16 bf16;
constexpr int S=2048, D=640, H=32, DH=192, HD=6144, NSEG=64, F=1536;
constexpr uint32_t SENT=0xFFFFFFFFu;
#define GUARDN 400000
constexpr int GUARD=GUARDN;
#define RCOPY 2
constexpr int NCTA=96;

__device__ __align__(128) bf16 g_xn[S*D];
__device__ __align__(128) bf16 g_y[S*D];
__device__ __align__(128) bf16 g_h[S*F];
__device__ __align__(128) bf16 g_gate[S*D];
__device__ __align__(128) bf16 g_k[(size_t)S*HD];
__device__ __align__(128) bf16 g_v[(size_t)S*HD];
__device__ __align__(128) uint2 g_kmf[NSEG*H*12*32];
__device__ __align__(128) uint2 g_vmf[NSEG*H*12*32];
__device__ __align__(128) uint32_t g_flag[NCTA*32];
__device__ __align__(128) bf16 g_ox[(size_t)S*HD];
__device__ __align__(128) float4 g_opp[(size_t)16*8*5*2*2048];
constexpr int C_NEXT=0, C_OP=256, C_M2=288, C_M1=320, C_QA=352, C_NUM=512;
__device__ __align__(128) uint32_t g_cnt[C_NUM];
#define PDL 1
__device__ __align__(128) uint32_t g_mem[(NSEG+1)*RCOPY*80*32];
__device__ __align__(128) uint32_t g_part[80*32*64];
__device__ int g_err;
__device__ unsigned long long g_gt[128*4];
#define GT(i) do{ if(threadIdx.x==0){ unsigned long long g0; asm volatile("mov.u64 %0, %%globaltimer;":"=l"(g0)); g_gt[blockIdx.x*4+(i)]=g0; } }while(0)

__device__ __forceinline__ float rb(float x){ return __bfloat162float(__float2bfloat16(x)); }
__device__ __forceinline__ uint32_t pack_bf16(float lo,float hi){ uint32_t r; asm("cvt.rn.bf16x2.f32 %0, %1, %2;":"=r"(r):"f"(hi),"f"(lo)); return r; }
__device__ __forceinline__ uint32_t movm(uint32_t a){ uint32_t d; asm volatile("movmatrix.sync.aligned.m8n8.trans.b16 %0, %1;":"=r"(d):"r"(a)); return d; }
__device__ __forceinline__ uint4 ldg_rlx4(const uint32_t* p){ uint4 v; asm volatile("ld.relaxed.gpu.global.v4.u32 {%0,%1,%2,%3}, [%4];":"=r"(v.x),"=r"(v.y),"=r"(v.z),"=r"(v.w):"l"(p):"memory"); return v; }
__device__ __forceinline__ void stg_rlx1(uint32_t* p,uint32_t a){ asm volatile("st.relaxed.gpu.global.u32 [%0], %1;"::"l"(p),"r"(a):"memory"); }
__device__ __forceinline__ void stg_rlx2(uint32_t* p,uint32_t a,uint32_t b){ asm volatile("st.relaxed.gpu.global.v2.u32 [%0], {%1,%2};"::"l"(p),"r"(a),"r"(b):"memory"); }
__device__ __forceinline__ void bar_sync(int id,int n){ asm volatile("bar.sync %0, %1;"::"r"(id),"r"(n):"memory"); }
__device__ __forceinline__ void bar_arrive(int id,int n){ asm volatile("bar.arrive %0, %1;"::"r"(id),"r"(n):"memory"); }
__device__ __forceinline__ void mma16816(float* d,const uint32_t* a,uint32_t b0,uint32_t b1){
  asm volatile("mma.sync.aligned.m16n8k16.row.col.f32.bf16.bf16.f32 {%0,%1,%2,%3},{%4,%5,%6,%7},{%8,%9},{%0,%1,%2,%3};"
   :"+f"(d[0]),"+f"(d[1]),"+f"(d[2]),"+f"(d[3]):"r"(a[0]),"r"(a[1]),"r"(a[2]),"r"(a[3]),"r"(b0),"r"(b1));
}
__device__ __forceinline__ void mma1688(float* d,uint32_t a0,uint32_t a1,uint32_t b0){
  asm volatile("mma.sync.aligned.m16n8k8.row.col.f32.bf16.bf16.f32 {%0,%1,%2,%3},{%4,%5},{%6},{%0,%1,%2,%3};"
   :"+f"(d[0]),"+f"(d[1]),"+f"(d[2]),"+f"(d[3]):"r"(a0),"r"(a1),"r"(b0));
}
__device__ __forceinline__ void ldsm4t(uint32_t* r,uint32_t addr){ asm volatile("ldmatrix.sync.aligned.m8n8.x4.trans.shared.b16 {%0,%1,%2,%3}, [%4];":"=r"(r[0]),"=r"(r[1]),"=r"(r[2]),"=r"(r[3]):"r"(addr):"memory"); }
__device__ __forceinline__ void ldsm4(uint32_t* r,uint32_t addr){ asm volatile("ldmatrix.sync.aligned.m8n8.x4.shared.b16 {%0,%1,%2,%3}, [%4];":"=r"(r[0]),"=r"(r[1]),"=r"(r[2]),"=r"(r[3]):"r"(addr):"memory"); }
__device__ __forceinline__ void cp16(uint32_t dst,const void* src){ asm volatile("cp.async.cg.shared.global [%0], [%1], 16;"::"r"(dst),"l"(src):"memory"); }
__device__ __forceinline__ void cp_wait_all(){ asm volatile("cp.async.wait_all;":::"memory"); }
__device__ __forceinline__ void fence_async(){ asm volatile("fence.proxy.async.shared::cta;":::"memory"); }
__device__ __forceinline__ void sts4f(uint32_t a,const float* v){ asm volatile("st.shared.v4.f32 [%0], {%1,%2,%3,%4};"::"r"(a),"f"(v[0]),"f"(v[1]),"f"(v[2]),"f"(v[3]):"memory"); }
__device__ __forceinline__ void sts4(uint32_t a,uint4 v){ asm volatile("st.shared.v4.u32 [%0], {%1,%2,%3,%4};"::"r"(a),"r"(v.x),"r"(v.y),"r"(v.z),"r"(v.w):"memory"); }
__device__ __forceinline__ void sts4r(uint32_t a,const uint32_t* v){ asm volatile("st.shared.v4.u32 [%0], {%1,%2,%3,%4};"::"r"(a),"r"(v[0]),"r"(v[1]),"r"(v[2]),"r"(v[3]):"memory"); }
__device__ __forceinline__ void sts2(uint32_t a,uint32_t x,uint32_t y){ asm volatile("st.shared.v2.u32 [%0], {%1,%2};"::"r"(a),"r"(x),"r"(y):"memory"); }
__device__ __forceinline__ float4 lds4f(uint32_t a){ float4 v; asm volatile("ld.shared.v4.f32 {%0,%1,%2,%3}, [%4];":"=f"(v.x),"=f"(v.y),"=f"(v.z),"=f"(v.w):"r"(a):"memory"); return v; }
__device__ __forceinline__ float2 lds2f(uint32_t a){ float2 v; asm volatile("ld.shared.v2.f32 {%0,%1}, [%2];":"=f"(v.x),"=f"(v.y):"r"(a):"memory"); return v; }
__device__ __forceinline__ uint4 lds4(uint32_t a){ uint4 v; asm volatile("ld.shared.v4.u32 {%0,%1,%2,%3}, [%4];":"=r"(v.x),"=r"(v.y),"=r"(v.z),"=r"(v.w):"r"(a):"memory"); return v; }
__device__ __forceinline__ void lds4r(uint32_t* r,uint32_t a){ asm volatile("ld.shared.v4.u32 {%0,%1,%2,%3}, [%4];":"=r"(r[0]),"=r"(r[1]),"=r"(r[2]),"=r"(r[3]):"r"(a):"memory"); }
__device__ __forceinline__ uint2 lds2(uint32_t a){ uint2 v; asm volatile("ld.shared.v2.u32 {%0,%1}, [%2];":"=r"(v.x),"=r"(v.y):"r"(a):"memory"); return v; }
__device__ __forceinline__ float ex2(float x){ float r; asm("ex2.approx.ftz.f32 %0, %1;":"=f"(r):"f"(x)); return r; }
__device__ __forceinline__ float rcp(float x){ float r; asm("rcp.approx.ftz.f32 %0, %1;":"=f"(r):"f"(x)); return r; }
__device__ __forceinline__ void mbar_init(uint32_t a,int n){ asm volatile("mbarrier.init.shared.b64 [%0], %1;"::"r"(a),"r"(n):"memory"); }
__device__ __forceinline__ void mbar_expect(uint32_t a,int bytes){ asm volatile("mbarrier.arrive.expect_tx.shared.b64 _, [%0], %1;"::"r"(a),"r"(bytes):"memory"); }
__device__ __forceinline__ bool mbar_try(uint32_t a,uint32_t par){ uint32_t ok; asm volatile("{\n.reg .pred p;\nmbarrier.try_wait.parity.shared.b64 p, [%1], %2;\nselp.u32 %0,1,0,p;\n}":"=r"(ok):"r"(a),"r"(par):"memory"); return ok; }
__device__ __forceinline__ bool mbar_try_cl(uint32_t a,uint32_t par){ uint32_t ok; asm volatile("{\n.reg .pred p;\nmbarrier.try_wait.parity.acquire.cluster.shared::cta.b64 p, [%1], %2;\nselp.u32 %0,1,0,p;\n}":"=r"(ok):"r"(a),"r"(par):"memory"); return ok; }
__device__ __forceinline__ void bulk_g2s(uint32_t dst,const void* src,int bytes,uint32_t mb){ asm volatile("cp.async.bulk.shared::cluster.global.mbarrier::complete_tx::bytes [%0], [%1], %2, [%3];"::"r"(dst),"l"(src),"r"(bytes),"r"(mb):"memory"); }
__device__ __forceinline__ uint32_t mapa(uint32_t a,uint32_t r){ uint32_t d; asm("mapa.shared::cluster.u32 %0, %1, %2;":"=r"(d):"r"(a),"r"(r)); return d; }
__device__ __forceinline__ void st_async2(uint32_t ra,uint32_t x,uint32_t y,uint32_t rmb){ asm volatile("st.async.weak.shared::cluster.mbarrier::complete_tx::bytes.v2.b32 [%0], {%1,%2}, [%3];"::"r"(ra),"r"(x),"r"(y),"r"(rmb):"memory"); }
__device__ __forceinline__ void cluster_sync(){ asm volatile("barrier.cluster.arrive.release.aligned;\nbarrier.cluster.wait.acquire.aligned;":::"memory"); }
__device__ __forceinline__ void fence_gpu(){ asm volatile("fence.acq_rel.gpu;":::"memory"); }

template<int NL,class V,class LDF,class OKF>
__device__ __forceinline__ void poll1(V* u,LDF ld,OKF ok,bool& dead,int code){
  #pragma unroll
  for(int i=0;i<NL;i++) u[i]=ld(i);
  int guard=0;
  while(true){
    bool f[NL]; bool a=true;
    #pragma unroll
    for(int i=0;i<NL;i++){ f[i]=ok(u[i]); a=a&&f[i]; }
    if(__all_sync(~0u,a)||dead) break;
    #pragma unroll
    for(int i=0;i<NL;i++) if(!f[i]) u[i]=ld(i);
    if(++guard>GUARD){ dead=true; g_err=code; }
  }
}
template<int N> __device__ __forceinline__ void wgmma(float* d,uint64_t da,uint64_t db,int sc);
template<> __device__ __forceinline__ void wgmma<128>(float* d,uint64_t da,uint64_t db,int sc){
  asm volatile("{\n.reg .pred p;\nsetp.ne.b32 p, %66, 0;\nwgmma.mma_async.sync.aligned.m64n128k16.f32.bf16.bf16 {%0,%1,%2,%3,%4,%5,%6,%7,%8,%9,%10,%11,%12,%13,%14,%15,%16,%17,%18,%19,%20,%21,%22,%23,%24,%25,%26,%27,%28,%29,%30,%31,%32,%33,%34,%35,%36,%37,%38,%39,%40,%41,%42,%43,%44,%45,%46,%47,%48,%49,%50,%51,%52,%53,%54,%55,%56,%57,%58,%59,%60,%61,%62,%63}, %64, %65, p, 1, 1, 0, 1;\n}"
   :"+f"(d[0]),"+f"(d[1]),"+f"(d[2]),"+f"(d[3]),"+f"(d[4]),"+f"(d[5]),"+f"(d[6]),"+f"(d[7]),"+f"(d[8]),"+f"(d[9]),"+f"(d[10]),"+f"(d[11]),"+f"(d[12]),"+f"(d[13]),"+f"(d[14]),"+f"(d[15]),"+f"(d[16]),"+f"(d[17]),"+f"(d[18]),"+f"(d[19]),"+f"(d[20]),"+f"(d[21]),"+f"(d[22]),"+f"(d[23]),"+f"(d[24]),"+f"(d[25]),"+f"(d[26]),"+f"(d[27]),"+f"(d[28]),"+f"(d[29]),"+f"(d[30]),"+f"(d[31]),"+f"(d[32]),"+f"(d[33]),"+f"(d[34]),"+f"(d[35]),"+f"(d[36]),"+f"(d[37]),"+f"(d[38]),"+f"(d[39]),"+f"(d[40]),"+f"(d[41]),"+f"(d[42]),"+f"(d[43]),"+f"(d[44]),"+f"(d[45]),"+f"(d[46]),"+f"(d[47]),"+f"(d[48]),"+f"(d[49]),"+f"(d[50]),"+f"(d[51]),"+f"(d[52]),"+f"(d[53]),"+f"(d[54]),"+f"(d[55]),"+f"(d[56]),"+f"(d[57]),"+f"(d[58]),"+f"(d[59]),"+f"(d[60]),"+f"(d[61]),"+f"(d[62]),"+f"(d[63]):"l"(da),"l"(db),"r"(sc));
}
template<> __device__ __forceinline__ void wgmma<192>(float* d,uint64_t da,uint64_t db,int sc){
  asm volatile("{\n.reg .pred p;\nsetp.ne.b32 p, %98, 0;\nwgmma.mma_async.sync.aligned.m64n192k16.f32.bf16.bf16 {%0,%1,%2,%3,%4,%5,%6,%7,%8,%9,%10,%11,%12,%13,%14,%15,%16,%17,%18,%19,%20,%21,%22,%23,%24,%25,%26,%27,%28,%29,%30,%31,%32,%33,%34,%35,%36,%37,%38,%39,%40,%41,%42,%43,%44,%45,%46,%47,%48,%49,%50,%51,%52,%53,%54,%55,%56,%57,%58,%59,%60,%61,%62,%63,%64,%65,%66,%67,%68,%69,%70,%71,%72,%73,%74,%75,%76,%77,%78,%79,%80,%81,%82,%83,%84,%85,%86,%87,%88,%89,%90,%91,%92,%93,%94,%95}, %96, %97, p, 1, 1, 0, 1;\n}"
   :"+f"(d[0]),"+f"(d[1]),"+f"(d[2]),"+f"(d[3]),"+f"(d[4]),"+f"(d[5]),"+f"(d[6]),"+f"(d[7]),"+f"(d[8]),"+f"(d[9]),"+f"(d[10]),"+f"(d[11]),"+f"(d[12]),"+f"(d[13]),"+f"(d[14]),"+f"(d[15]),"+f"(d[16]),"+f"(d[17]),"+f"(d[18]),"+f"(d[19]),"+f"(d[20]),"+f"(d[21]),"+f"(d[22]),"+f"(d[23]),"+f"(d[24]),"+f"(d[25]),"+f"(d[26]),"+f"(d[27]),"+f"(d[28]),"+f"(d[29]),"+f"(d[30]),"+f"(d[31]),"+f"(d[32]),"+f"(d[33]),"+f"(d[34]),"+f"(d[35]),"+f"(d[36]),"+f"(d[37]),"+f"(d[38]),"+f"(d[39]),"+f"(d[40]),"+f"(d[41]),"+f"(d[42]),"+f"(d[43]),"+f"(d[44]),"+f"(d[45]),"+f"(d[46]),"+f"(d[47]),"+f"(d[48]),"+f"(d[49]),"+f"(d[50]),"+f"(d[51]),"+f"(d[52]),"+f"(d[53]),"+f"(d[54]),"+f"(d[55]),"+f"(d[56]),"+f"(d[57]),"+f"(d[58]),"+f"(d[59]),"+f"(d[60]),"+f"(d[61]),"+f"(d[62]),"+f"(d[63]),"+f"(d[64]),"+f"(d[65]),"+f"(d[66]),"+f"(d[67]),"+f"(d[68]),"+f"(d[69]),"+f"(d[70]),"+f"(d[71]),"+f"(d[72]),"+f"(d[73]),"+f"(d[74]),"+f"(d[75]),"+f"(d[76]),"+f"(d[77]),"+f"(d[78]),"+f"(d[79]),"+f"(d[80]),"+f"(d[81]),"+f"(d[82]),"+f"(d[83]),"+f"(d[84]),"+f"(d[85]),"+f"(d[86]),"+f"(d[87]),"+f"(d[88]),"+f"(d[89]),"+f"(d[90]),"+f"(d[91]),"+f"(d[92]),"+f"(d[93]),"+f"(d[94]),"+f"(d[95]):"l"(da),"l"(db),"r"(sc));
}
template<> __device__ __forceinline__ void wgmma<256>(float* d,uint64_t da,uint64_t db,int sc){
  asm volatile("{\n.reg .pred p;\nsetp.ne.b32 p, %130, 0;\nwgmma.mma_async.sync.aligned.m64n256k16.f32.bf16.bf16 {%0,%1,%2,%3,%4,%5,%6,%7,%8,%9,%10,%11,%12,%13,%14,%15,%16,%17,%18,%19,%20,%21,%22,%23,%24,%25,%26,%27,%28,%29,%30,%31,%32,%33,%34,%35,%36,%37,%38,%39,%40,%41,%42,%43,%44,%45,%46,%47,%48,%49,%50,%51,%52,%53,%54,%55,%56,%57,%58,%59,%60,%61,%62,%63,%64,%65,%66,%67,%68,%69,%70,%71,%72,%73,%74,%75,%76,%77,%78,%79,%80,%81,%82,%83,%84,%85,%86,%87,%88,%89,%90,%91,%92,%93,%94,%95,%96,%97,%98,%99,%100,%101,%102,%103,%104,%105,%106,%107,%108,%109,%110,%111,%112,%113,%114,%115,%116,%117,%118,%119,%120,%121,%122,%123,%124,%125,%126,%127}, %128, %129, p, 1, 1, 0, 1;\n}"
   :"+f"(d[0]),"+f"(d[1]),"+f"(d[2]),"+f"(d[3]),"+f"(d[4]),"+f"(d[5]),"+f"(d[6]),"+f"(d[7]),"+f"(d[8]),"+f"(d[9]),"+f"(d[10]),"+f"(d[11]),"+f"(d[12]),"+f"(d[13]),"+f"(d[14]),"+f"(d[15]),"+f"(d[16]),"+f"(d[17]),"+f"(d[18]),"+f"(d[19]),"+f"(d[20]),"+f"(d[21]),"+f"(d[22]),"+f"(d[23]),"+f"(d[24]),"+f"(d[25]),"+f"(d[26]),"+f"(d[27]),"+f"(d[28]),"+f"(d[29]),"+f"(d[30]),"+f"(d[31]),"+f"(d[32]),"+f"(d[33]),"+f"(d[34]),"+f"(d[35]),"+f"(d[36]),"+f"(d[37]),"+f"(d[38]),"+f"(d[39]),"+f"(d[40]),"+f"(d[41]),"+f"(d[42]),"+f"(d[43]),"+f"(d[44]),"+f"(d[45]),"+f"(d[46]),"+f"(d[47]),"+f"(d[48]),"+f"(d[49]),"+f"(d[50]),"+f"(d[51]),"+f"(d[52]),"+f"(d[53]),"+f"(d[54]),"+f"(d[55]),"+f"(d[56]),"+f"(d[57]),"+f"(d[58]),"+f"(d[59]),"+f"(d[60]),"+f"(d[61]),"+f"(d[62]),"+f"(d[63]),"+f"(d[64]),"+f"(d[65]),"+f"(d[66]),"+f"(d[67]),"+f"(d[68]),"+f"(d[69]),"+f"(d[70]),"+f"(d[71]),"+f"(d[72]),"+f"(d[73]),"+f"(d[74]),"+f"(d[75]),"+f"(d[76]),"+f"(d[77]),"+f"(d[78]),"+f"(d[79]),"+f"(d[80]),"+f"(d[81]),"+f"(d[82]),"+f"(d[83]),"+f"(d[84]),"+f"(d[85]),"+f"(d[86]),"+f"(d[87]),"+f"(d[88]),"+f"(d[89]),"+f"(d[90]),"+f"(d[91]),"+f"(d[92]),"+f"(d[93]),"+f"(d[94]),"+f"(d[95]),"+f"(d[96]),"+f"(d[97]),"+f"(d[98]),"+f"(d[99]),"+f"(d[100]),"+f"(d[101]),"+f"(d[102]),"+f"(d[103]),"+f"(d[104]),"+f"(d[105]),"+f"(d[106]),"+f"(d[107]),"+f"(d[108]),"+f"(d[109]),"+f"(d[110]),"+f"(d[111]),"+f"(d[112]),"+f"(d[113]),"+f"(d[114]),"+f"(d[115]),"+f"(d[116]),"+f"(d[117]),"+f"(d[118]),"+f"(d[119]),"+f"(d[120]),"+f"(d[121]),"+f"(d[122]),"+f"(d[123]),"+f"(d[124]),"+f"(d[125]),"+f"(d[126]),"+f"(d[127]):"l"(da),"l"(db),"r"(sc));
}
__global__ void __launch_bounds__(256) k_pre(const bf16* __restrict__ x,const bf16* __restrict__ mem0){
  const int warp=threadIdx.x>>5, lane=threadIdx.x&31;
  const int row=blockIdx.x*8+warp;
  {
    int i=blockIdx.x*256+threadIdx.x; int n=gridDim.x*256;
    for(int k=i;k<(NSEG+1)*RCOPY*80*32;k+=n){
      uint32_t v=SENT;
      if(k<RCOPY*80*32){ int fb=(k%2560)>>5, r=(k>>2)&7, w=k&3; v=*(const uint32_t*)(mem0+r*D+fb*8+w*2);
        if(v==SENT) v=0x7FFF7FFFu; }
      g_mem[k]=v;
    }
    if(i==0) g_err=0;
    if(i<NCTA*32) g_flag[i]=0;
    if(i<C_NUM) g_cnt[i]=0;
  }
  float v[20];
  {
    const uint32_t* p=(const uint32_t*)(x+(size_t)row*D);
    #pragma unroll
    for(int i=0;i<10;i++){ uint32_t u=p[lane+32*i]; v[2*i]=__uint_as_float(u<<16); v[2*i+1]=__uint_as_float(u&0xffff0000u); }
  }
  #pragma unroll
  for(int pass=0;pass<2;pass++){
    float s=0;
    #pragma unroll
    for(int i=0;i<20;i++) s+=v[i];
    #pragma unroll
    for(int o=16;o;o>>=1) s+=__shfl_xor_sync(~0u,s,o);
    float mean=s*(1.f/D);
    float q=0;
    #pragma unroll
    for(int i=0;i<20;i++){ float d=v[i]-mean; q+=d*d; }
    #pragma unroll
    for(int o=16;o;o>>=1) q+=__shfl_xor_sync(~0u,q,o);
    float var=rb(q*(1.f/D)), mb=rb(mean);
    float den=rb(sqrtf(rb(var+1e-5f)));
    uint32_t* o=(uint32_t*)((pass?g_y:g_xn)+(size_t)row*D);
    #pragma unroll
    for(int i=0;i<10;i++){
      float a=rb(rb(v[2*i]-mb)/den), b=rb(rb(v[2*i+1]-mb)/den);
      v[2*i]=a; v[2*i+1]=b;
      o[lane+32*i]=pack_bf16(a,b);
    }
  }
}

#define BDELAY 0
constexpr int SM_QS=0;
constexpr int SM_VS=49152;
constexpr int SM_OS=131072;
constexpr int SM_O=SM_OS+43008;
constexpr int SM_RSUM=SM_O+3072;
constexpr int SM_RED=180224;
constexpr int SM_KX=SM_RED+24576;
constexpr int SM_VX=SM_KX+4096;
constexpr int SM_QKF=SM_VX+12288;
constexpr int SM_SCX=SM_QKF+2048;
constexpr int SM_VMX=SM_SCX+3840;
constexpr int SM_MB=SM_VMX+3072;
constexpr int SM_TOTAL=SM_MB+64;
static_assert(SM_MB-SM_RED>=49152,"staging");
static_assert(SM_TOTAL<=232448,"smem");

#define TS(i)
#define TW(i)
#define TF(i)

__device__ __forceinline__ void cp_commit(){ asm volatile("cp.async.commit_group;":::"memory"); }
template<int N> __device__ __forceinline__ void cp_wait(){ asm volatile("cp.async.wait_group %0;"::"n"(N):"memory"); }
__device__ __forceinline__ void tma2d(uint32_t dst,const CUtensorMap* tm,int c0,int c1,uint32_t mb){
  asm volatile("cp.async.bulk.tensor.2d.shared::cluster.global.mbarrier::complete_tx::bytes [%0], [%1, {%3, %4}], [%2];"::"r"(dst),"l"(tm),"r"(mb),"r"(c0),"r"(c1):"memory"); }
__device__ __forceinline__ void tma2d_pf(const CUtensorMap* tm,int c0,int c1){
  asm volatile("cp.async.bulk.prefetch.tensor.2d.L2.global [%0, {%1, %2}];"::"l"(tm),"r"(c0),"r"(c1):"memory"); }
__global__ void __launch_bounds__(256,1) k_rec(const __grid_constant__ CUtensorMap tmK,const __grid_constant__ CUtensorMap tmV,const bf16* __restrict__ Wq,const bf16* __restrict__ Wk,const bf16* __restrict__ Wv,const bf16* __restrict__ Wo){
  extern __shared__ __align__(1024) uint8_t sm[];
  const int tid=threadIdx.x, warp=__shfl_sync(~0u,tid>>5,0), lane=tid&31, g=lane>>2, t=lane&3;
  const int b=blockIdx.x, h=b/3, c=b-3*h;
  const uint32_t sb=(uint32_t)__cvta_generic_to_shared(sm);
  const int kq=warp&3, mg=warp>>2;
  const uint32_t s16=sb+lane*16, s8=sb+lane*8;
  const uint32_t qs=s16+SM_QS+warp*6144, vs=s16+SM_VS+kq*20480, os=s16+SM_OS+warp*6144;
  const uint32_t XS=sb+SM_MB, KVB=sb+SM_MB+8, XV=sb+SM_MB+16;
  GT(0);
  asm volatile("griddepcontrol.launch_dependents;");
  if(tid==0){
    mbar_init(XS,1); mbar_init(KVB,1); mbar_init(XV,1);
    asm volatile("fence.mbarrier_init.release.cluster;":::"memory");
    mbar_expect(XS,3840); mbar_expect(XV,3072);
  }
  const int ntile=c==0?14:13, tile0=c==0?0:(1+13*c);
  uint32_t wr[7][4][4];
  uint32_t wo[6][2][4];
  auto ldW=[&](int p,uint32_t stg){
    #pragma unroll
    for(int i=0;i<12;i++){
      const int idx=tid+256*i, row=idx>>3, ch=idx&7, m=row>>7, f=160*((row>>5)&3)+32*p+(row&31);
      const bf16* src=(m==0?Wq:(m==1?Wk:Wv))+(size_t)f*HD+h*DH+64*c+ch*8;
      const int sw=(((row>>3)&3)<<1)|(row&1);
      cp16(stg+row*128+((ch^sw)<<4),src);
    }
    cp_commit();
  };
  auto ldO=[&](int r,uint32_t stg){
    for(int idx=tid;idx<96*28;idx+=256){
      const int row=idx/28, ch=idx-row*28;
      if(ch<2*ntile) cp16(stg+row*464+ch*16,Wo+(size_t)(h*DH+96*r+row)*D+tile0*16+ch*8);
    }
    cp_commit();
  };
  ldW(0,sb+SM_RED);
  #pragma unroll
  for(int p=0;p<5;p++){
    const uint32_t stg=sb+((p&1)?SM_OS:SM_RED), nstg=sb+((p&1)?SM_RED:SM_OS);
    if(p<4) ldW(p+1,nstg); else ldO(0,nstg);
    cp_wait<1>(); __syncthreads();
    #pragma unroll
    for(int e=0;e<2;e++){
      const int k=2*p+e;
      const int fo=8*((lane&7)>>1)+4*e+2*(lane>>4)+(lane&1);
      const int sw=(((fo>>3)&3)<<1)|(fo&1);
      #pragma unroll
      for(int j=0;j<4;j++){
        const uint32_t a=stg+((mg*4+kq)*32+fo)*128+(((2*j+((lane>>3)&1))^sw)<<4);
        if(k>=2&&k<9) ldsm4t(wr[(k>=2&&k<9)?k-2:0][j],a);
        else { uint32_t r[4]; ldsm4t(r,a); sts4r(qs+((k<2?k*4:8)+j)*512,r); }
        if(mg){ uint32_t r[4]; ldsm4t(r,a+16384); sts4r(vs+(k*4+j)*512,r); }
      }
    }
    __syncthreads();
  }
  #pragma unroll
  for(int r=0;r<2;r++){
    const uint32_t stg=sb+(r?SM_RED:SM_OS);
    if(r==0){ ldO(1,sb+SM_RED); cp_wait<1>(); } else cp_wait<0>();
    __syncthreads();
    #pragma unroll
    for(int kk=0;kk<6;kk++){
      #pragma unroll
      for(int i=0;i<2;i++){
        int tl=2*warp+i; if(tl>=ntile) tl=0;
        const uint32_t a=stg+(16*kk+(lane&7)+(lane>>4)*8)*464+(2*tl+((lane>>3)&1))*16;
        if(r==0) ldsm4t(wo[kk][i],a);
        else { uint32_t rr[4]; ldsm4t(rr,a); if(warp<7) sts4r(os+(kk*2+i)*512,rr); }
      }
    }
    __syncthreads();
  }
  auto kv_issue=[&](int sn){
    fence_async();
    if(lane==0){
      mbar_expect(KVB,32*512);
      tma2d(sb+SM_KX,&tmK,h*DH+64*c,sn*32,KVB);
      #pragma unroll
      for(int i=0;i<3;i++) tma2d(sb+SM_VX+i*4096,&tmV,h*DH+64*i,sn*32,KVB);
    }
    __syncwarp();
  };
  auto kv_pf=[&](int sn){
    if(lane==0){ tma2d_pf(&tmK,h*DH+64*c,sn*32); tma2d_pf(&tmV,h*DH+64*c,sn*32); }
    __syncwarp();
  };
  if(warp==7){ kv_issue(0); kv_pf(1); kv_pf(2); }
  cluster_sync();
  const bool isred=(b%6)<5; const int rline=(b/6)*5+(b%6);
  bool dead=false;
  uint32_t rsc[3];
  #pragma unroll
  for(int r=0;r<3;r++) rsc[r]=mapa(sb,r);
  uint32_t buf[8][4];
  #pragma unroll
  for(int i=0;i<8;i++) lds4r(buf[i],qs+i*512);

  GT(1);
  #define MB0(k) (((k)&1)?mv[(k)>>1].z:mv[(k)>>1].x)
  #define MB1(k) (((k)&1)?mv[(k)>>1].w:mv[(k)>>1].y)
  #pragma unroll 1
  for(int s=0;s<NSEG;s++){
    const uint32_t tg=1+(s&1);
    uint4 mv[5];
    {
      const uint32_t* src=(const uint32_t*)((const char*)g_mem+(uint32_t)((s*RCOPY+(b%RCOPY))*10240+(kq*20+t)*128+g*16));
      auto okf=[&](const uint4& v){ return v.x!=SENT&&v.y!=SENT&&v.z!=SENT&&v.w!=SENT; };
      const uint32_t mx=s16+SM_RED+kq*4096;
      if(mg==0){
        poll1<3>(mv,[&](int i){ return ldg_rlx4(src+i*128); },okf,dead,1);
        TW(0);
        #pragma unroll
        for(int p=0;p<3;p++) sts4(mx+(4+p)*512,mv[p]);
        bar_sync(8+kq,64);
        mv[3]=lds4(mx); mv[4]=lds4(mx+512);
      } else {
        poll1<2>(mv+3,[&](int i){ return ldg_rlx4(src+(3+i)*128); },okf,dead,1);
        TW(0);
        sts4(mx,mv[3]); sts4(mx+512,mv[4]);
        bar_sync(8+kq,64);
        #pragma unroll
        for(int p=0;p<3;p++) mv[p]=lds4(mx+(4+p)*512);
      }
    }
    TS(0); TF(0);
    float acc[4][4];
    #pragma unroll
    for(int i=0;i<4;i++){ acc[i][0]=acc[i][1]=acc[i][2]=acc[i][3]=0.f; }
    #pragma unroll
    for(int k=0;k<10;k++){
      #pragma unroll
      for(int j=0;j<4;j++){
        if(k<2) mma16816(acc[j],buf[(k&1)*4+j],MB0(k),MB1(k));
        else if(k<9) mma16816(acc[j],wr[(k>=2&&k<9)?k-2:0][j],MB0(k),MB1(k));
        else mma16816(acc[j],buf[j],MB0(k),MB1(k));
        if(k==2) lds4r(buf[j],qs+(8+j)*512);
        if(k==4&&mg) lds4r(buf[4+j],vs+j*512);
      }
    }
    TF(1);
    {
      const uint32_t ra=s16+SM_RED+kq*4096+mg*2048;
      #pragma unroll
      for(int i=0;i<4;i++) sts4f(ra+i*512,acc[i]);
    }
    const uint32_t exo=(uint32_t)(((s*H+h)*12+4*c+kq)*256+lane*8);
    if(mg){
      bar_arrive(1,256);
      #pragma unroll
      for(int j=0;j<4;j++) lds4r(buf[j],vs+(4+j)*512);
      #pragma unroll
      for(int i=0;i<4;i++){ acc[i][0]=acc[i][1]=acc[i][2]=acc[i][3]=0.f; }
      #pragma unroll
      for(int u=0;u<40;u++){
        mma16816(acc[u&3],buf[(u+4)&7],MB0(u>>2),MB1(u>>2));
        if(u+8<40) lds4r(buf[(u+4)&7],vs+(u+8)*512);
      }
      TF(2);
      const uint32_t ra=s16+SM_RED+16384;
      #pragma unroll
      for(int i=0;i<4;i++) sts4f(ra+kq*2048+i*512,acc[i]);
      bar_sync(3,128);
      float4 a=lds4f(ra+kq*512), c1=lds4f(ra+kq*512+2048), d2=lds4f(ra+kq*512+4096), e2=lds4f(ra+kq*512+6144);
      const uint32_t p0=pack_bf16((a.x+c1.x)+(d2.x+e2.x),(a.y+c1.y)+(d2.y+e2.y)), p1=pack_bf16((a.z+c1.z)+(d2.z+e2.z),(a.w+c1.w)+(d2.w+e2.w));
      const uint32_t off=SM_VMX+(4*c+kq)*256+lane*8;
      #pragma unroll
      for(int r=0;r<3;r++) st_async2(rsc[r]+off,p0,p1,rsc[r]+SM_MB+16);
      TF(5);
      stg_rlx2((uint32_t*)((char*)g_vmf+exo),p0,p1);
      if(warp<7){
        #pragma unroll
        for(int i=0;i<8;i++) lds4r(buf[i],os+i*512);
      }
    } else {
      { int gd=0; while(!mbar_try(KVB,s&1)){ if(dead) break; if(++gd>GUARD){ dead=true; g_err=6; } } }
      uint32_t kb[8];
      {
        const uint32_t ka=sb+SM_KX+(8*kq+(lane&7))*128+(((lane>>3)^(lane&7))<<4);
        ldsm4(kb,ka); ldsm4(kb+4,ka^64);
      }
      bar_sync(1,256);
      TS(1);
      {
        const uint32_t ra=s16+SM_RED+kq*512;
        float4 a=lds4f(ra), c1=lds4f(ra+4096), d2=lds4f(ra+8192), e2=lds4f(ra+12288);
        float4 a3=lds4f(ra+2048), c3=lds4f(ra+6144), d3=lds4f(ra+10240), e3=lds4f(ra+14336);
        const uint32_t p0=pack_bf16((a.x+c1.x)+(d2.x+e2.x),(a.y+c1.y)+(d2.y+e2.y)), p1=pack_bf16((a.z+c1.z)+(d2.z+e2.z),(a.w+c1.w)+(d2.w+e2.w));
        const uint32_t p2=pack_bf16((a3.x+c3.x)+(d3.x+e3.x),(a3.y+c3.y)+(d3.y+e3.y)), p3=pack_bf16((a3.z+c3.z)+(d3.z+e3.z),(a3.w+c3.w)+(d3.w+e3.w));
        TF(2);
        const uint32_t f0=movm(p0), f1=movm(p1), f2=movm(p2), f3=movm(p3);
        sts4(s16+SM_QKF+kq*512,make_uint4(f0,f1,f2,f3));
        TF(3);
        bar_sync(2,128);
        stg_rlx2((uint32_t*)((char*)g_kmf+exo),f2,f3);
      }
      {
        uint4 q[4];
        if(warp==0){
          #pragma unroll
          for(int k=0;k<4;k++) q[k]=lds4(s16+SM_QKF+k*512);
        } else {
          #pragma unroll
          for(int k=0;k<4;k++){ uint2 u=lds2(s16+SM_QKF+k*512); q[k].x=u.x; q[k].y=u.y; }
        }
        TF(4);
        float sc[4]={0.f,0.f,0.f,0.f}, sd[4]={0.f,0.f,0.f,0.f};
        { uint32_t a[4]={q[0].x,0u,q[0].y,0u}; mma16816(sc,a,kb[0],kb[1]); }
        { uint32_t a[4]={q[1].x,0u,q[1].y,0u}; mma16816(sd,a,kb[2],kb[3]); }
        { uint32_t a[4]={q[2].x,0u,q[2].y,0u}; mma16816(sc,a,kb[4],kb[5]); }
        { uint32_t a[4]={q[3].x,0u,q[3].y,0u}; mma16816(sd,a,kb[6],kb[7]); }
        const uint32_t off=SM_SCX+(c*5)*256+lane*8;
        if(warp==0){
          float se[4]={0.f,0.f,0.f,0.f}, sf[4]={0.f,0.f,0.f,0.f};
          { uint32_t a[4]={q[0].x,0u,q[0].y,0u}; mma16816(se,a,q[0].z,q[0].w); }
          { uint32_t a[4]={q[1].x,0u,q[1].y,0u}; mma16816(sf,a,q[1].z,q[1].w); }
          { uint32_t a[4]={q[2].x,0u,q[2].y,0u}; mma16816(se,a,q[2].z,q[2].w); }
          { uint32_t a[4]={q[3].x,0u,q[3].y,0u}; mma16816(sf,a,q[3].z,q[3].w); }
          const uint32_t w0=__float_as_uint(se[0]+sf[0]), w1=__float_as_uint(se[1]+sf[1]);
          #pragma unroll
          for(int r=0;r<3;r++) st_async2(rsc[r]+off,w0,w1,rsc[r]+SM_MB);
        }
        const uint32_t w0=__float_as_uint(sc[0]+sd[0]), w1=__float_as_uint(sc[1]+sd[1]);
        #pragma unroll
        for(int r=0;r<3;r++) st_async2(rsc[r]+off+(1+kq)*256,w0,w1,rsc[r]+SM_MB);
      }
      TS(2); TF(5);
      uint32_t va[3][2][4];
      #pragma unroll
      for(int i=0;i<3;i++){
        const int T=3*kq+i;
        const uint32_t vaddr=sb+SM_VX+(T>>2)*4096+((lane>>4)*8+(lane&7))*128+(((2*(T&3)+((lane>>3)&1))^(lane&7))<<4);
        ldsm4t(va[i][0],vaddr); ldsm4t(va[i][1],vaddr+2048);
      }
      #pragma unroll
      for(int i=0;i<4;i++) lds4r(buf[i],os+i*512);
      TF(6);
      { int gd=0; while(!mbar_try_cl(XS,s&1)){ if(dead) break; if(++gd>GUARD){ dead=true; g_err=2; } } }
      TS(3); TF(7);
      float sv[10];
      #pragma unroll
      for(int n=0;n<5;n++){
        float2 u0=lds2f(s8+SM_SCX+n*256), u1=lds2f(s8+SM_SCX+(5+n)*256), u2=lds2f(s8+SM_SCX+(10+n)*256);
        sv[2*n]=rb(rb((u0.x+u1.x)+u2.x)*0.07216878364870322f); sv[2*n+1]=rb(rb((u0.y+u1.y)+u2.y)*0.07216878364870322f);
      }
      TF(8);
      float mx=fmaxf(fmaxf(fmaxf(sv[0],sv[1]),fmaxf(sv[2],sv[3])),fmaxf(fmaxf(fmaxf(sv[4],sv[5]),fmaxf(sv[6],sv[7])),fmaxf(sv[8],sv[9])));
      mx=fmaxf(mx,__shfl_xor_sync(~0u,mx,1)); mx=fmaxf(mx,__shfl_xor_sync(~0u,mx,2));
      #pragma unroll
      for(int i=0;i<10;i++) sv[i]=ex2((sv[i]-mx)*1.4426950408889634f);
      float sum=((sv[0]+sv[1])+(sv[2]+sv[3]))+(((sv[4]+sv[5])+(sv[6]+sv[7]))+(sv[8]+sv[9]));
      sum+=__shfl_xor_sync(~0u,sum,1); sum+=__shfl_xor_sync(~0u,sum,2);
      const float inv=rcp(sum);
      uint32_t pp[5];
      #pragma unroll
      for(int n=0;n<5;n++) pp[n]=pack_bf16(sv[2*n]*inv,sv[2*n+1]*inv);
      TF(9);
      float o[3][4];
      #pragma unroll
      for(int i=0;i<3;i++){ o[i][0]=o[i][1]=o[i][2]=o[i][3]=0.f; mma16816(o[i],va[i][0],pp[1],pp[2]); }
      #pragma unroll
      for(int i=0;i<3;i++) mma16816(o[i],va[i][1],pp[3],pp[4]);
      { int gd=0; while(!mbar_try_cl(XV,s&1)){ if(dead) break; if(++gd>GUARD){ dead=true; g_err=3; } } }
      #pragma unroll
      for(int i=0;i<3;i++){ uint2 vm=lds2(s8+SM_VMX+(3*kq+i)*256); mma1688(o[i],vm.x,vm.y,pp[0]); }
      #pragma unroll
      for(int i=0;i<3;i++){
        const int T=3*kq+i;
        const uint32_t f0=movm(pack_bf16(o[i][0],o[i][1])), f1=movm(pack_bf16(o[i][2],o[i][3]));
        sts2(s16+SM_O+(T>>1)*512+(T&1)*8,f0,f1);
      }
      #pragma unroll
      for(int i=4;i<8;i++) lds4r(buf[i],os+i*512);
    }
    TF(10);
    bar_sync(4,256);
    if(warp<7){
      uint4 ob[6];
      ob[3]=lds4(s16+SM_O+3*512);
      #pragma unroll
      for(int i=0;i<6;i++) if(i!=3) ob[i]=lds4(s16+SM_O+i*512);
      TF(11);
      float ca[2][2][4];
      #pragma unroll
      for(int i=0;i<2;i++)
        #pragma unroll
        for(int j=0;j<2;j++){ ca[i][j][0]=ca[i][j][1]=ca[i][j][2]=ca[i][j][3]=0.f; }
      #pragma unroll
      for(int x=0;x<12;x++){
        const int ks=x<2?6+x:(x<8?x-2:x);
        const uint32_t b0=(ks&1)?ob[ks>>1].z:ob[ks>>1].x, b1=(ks&1)?ob[ks>>1].w:ob[ks>>1].y;
        #pragma unroll
        for(int i=0;i<2;i++){
          if(ks<6) mma16816(ca[i][ks&1],wo[ks<6?ks:0][i],b0,b1);
          else mma16816(ca[i][ks&1],buf[((ks-6)*2+i)&7],b0,b1);
          if(x==3||x==4) lds4r(buf[(x-3)*2+i],os+(8+(x-3)*2+i)*512);
        }
      }
      TF(12);
      uint32_t* dst=(uint32_t*)((char*)g_part+(uint32_t)(((2*(tile0+2*warp))*32+h)*256+lane*8));
      #pragma unroll
      for(int i=0;i<2;i++){
        if(i==0||2*warp+1<ntile){
          stg_rlx2(dst+(2*i)*2048,(__float_as_uint(ca[i][0][0]+ca[i][1][0])&~3u)|tg,(__float_as_uint(ca[i][0][1]+ca[i][1][1])&~3u)|tg);
          stg_rlx2(dst+(2*i+1)*2048,(__float_as_uint(ca[i][0][2]+ca[i][1][2])&~3u)|tg,(__float_as_uint(ca[i][0][3]+ca[i][1][3])&~3u)|tg);
        }
      }
    } else {
      if(lane==0){ mbar_expect(XS,3840); mbar_expect(XV,3072); }
      if(s+1<NSEG) kv_issue(s+1);
      if(s+3<NSEG) kv_pf(s+3);
      if(isred&&lane<RCOPY&&s+3<=NSEG) asm volatile("prefetch.global.L2 [%0];"::"l"(g_mem+(size_t)((s+3)*RCOPY+lane)*2560+rline*32));
    }
    TW(1);
    TS(4); TF(13);
    #pragma unroll
    for(int i=0;i<8;i++) lds4r(buf[i],qs+i*512);
    if(isred){
      const uint32_t* src=(const uint32_t*)((char*)g_part+(uint32_t)((rline*32+4*warp)*256+lane*16));
      uint32_t* mdst=g_mem+(size_t)((s+1)*RCOPY)*2560+rline*32+lane;
      uint4 v[2]; float f[4];
      auto okr=[&](const uint4& v){ return (v.x&3u)==tg&&(v.y&3u)==tg&&(v.z&3u)==tg&&(v.w&3u)==tg; };
      poll1<2>(v,[&](int i){ return ldg_rlx4(src+i*128); },okr,dead,4);
      f[0]=__uint_as_float(v[0].x)+__uint_as_float(v[1].x); f[1]=__uint_as_float(v[0].y)+__uint_as_float(v[1].y); f[2]=__uint_as_float(v[0].z)+__uint_as_float(v[1].z); f[3]=__uint_as_float(v[0].w)+__uint_as_float(v[1].w);
      TW(2); TF(14);
      #pragma unroll
      for(int i=0;i<4;i++) f[i]+=__shfl_xor_sync(~0u,f[i],16);
      if(lane<16) sts4f(s16+SM_RSUM+warp*256,f);
      if(warp==0){
        bar_sync(5,256);
        TS(5);
        const float* rp=(const float*)(sm+SM_RSUM)+(lane&3)*16+(lane>>2);
        float a0=((rp[0]+rp[64])+(rp[128]+rp[192]))+((rp[256]+rp[320])+(rp[384]+rp[448]));
        float a1=((rp[8]+rp[72])+(rp[136]+rp[200]))+((rp[264]+rp[328])+(rp[392]+rp[456]));
        uint32_t o=pack_bf16(a0,a1); if(o==SENT) o=0x7FFF7FFFu;
        #pragma unroll
        for(int cc=0;cc<RCOPY;cc++) stg_rlx1(mdst+cc*2560,o);
        TS(6); TW(3);
      } else bar_arrive(5,256);
    }
    TF(15);
    if(warp==7){ fence_gpu(); if(lane==0) stg_rlx1(g_flag+b*32,s+1); }
  }
  GT(2);
  cluster_sync();
}

enum { M_XN=0,M_Y,M_H,M_OX,M_K,M_V,M_GATE,M_WQ,M_WK,M_WV,M_W1,M_W2,M_WO,M_NUM };
struct WParams { CUtensorMap m[M_NUM]; const bf16* x; const bf16* b1; const bf16* b2; bf16* out; };
enum { T_RED=0,T_OP=1,T_QA=2,T_M2=3,T_M1=4,T_KV=5,T_END=6 };
constexpr int NRB=16, NSPL=8, NREDI=20;
constexpr int STG=49152, NST=4;
constexpr int W_STAGING=NST*STG;
constexpr int W_BAR=W_STAGING+32768;
constexpr int W_TOTAL=W_BAR+256;
#define WGUARD 2000000

__device__ __forceinline__ void wg_arrive(){ asm volatile("wgmma.fence.sync.aligned;":::"memory"); }
__device__ __forceinline__ void wg_commit(){ asm volatile("wgmma.commit_group.sync.aligned;":::"memory"); }
template<int N> __device__ __forceinline__ void wg_wait(){ asm volatile("wgmma.wait_group.sync.aligned %0;"::"n"(N):"memory"); }
__device__ __forceinline__ void mbar_arrive(uint32_t a){ asm volatile("mbarrier.arrive.shared.b64 _, [%0];"::"r"(a):"memory"); }
__device__ __forceinline__ void mbar_wait(uint32_t a,uint32_t par){ int gd=0; while(!mbar_try(a,par)){ if(++gd>WGUARD){ g_err=20; break; } } }
__device__ __forceinline__ uint32_t ld_acq(const uint32_t* p){ uint32_t v; asm volatile("ld.acquire.gpu.global.u32 %0, [%1];":"=r"(v):"l"(p):"memory"); return v; }
__device__ __forceinline__ uint32_t ld_rlx(const uint32_t* p){ uint32_t v; asm volatile("ld.relaxed.gpu.global.u32 %0, [%1];":"=r"(v):"l"(p):"memory"); return v; }
__device__ __forceinline__ uint2 ld_rlx2(const uint2* p){ uint2 v; asm volatile("ld.relaxed.gpu.global.v2.u32 {%0,%1}, [%2];":"=r"(v.x),"=r"(v.y):"l"(p):"memory"); return v; }
__device__ __forceinline__ float4 ld_rlx4f(const float4* p){ float4 v; asm volatile("ld.relaxed.gpu.global.v4.f32 {%0,%1,%2,%3}, [%4];":"=f"(v.x),"=f"(v.y),"=f"(v.z),"=f"(v.w):"l"(p):"memory"); return v; }
__device__ __forceinline__ void red_rel(uint32_t* p){ asm volatile("red.release.gpu.global.add.u32 [%0], 1;"::"l"(p):"memory"); }
__device__ __forceinline__ void fence_async_all(){ asm volatile("fence.proxy.async;":::"memory"); }
__device__ __forceinline__ void tma_st(const CUtensorMap* tm,uint32_t src,int c0,int c1){
  asm volatile("cp.async.bulk.tensor.2d.global.shared::cta.bulk_group [%0, {%2, %3}], [%1];"::"l"(tm),"r"(src),"r"(c0),"r"(c1):"memory"); }
__device__ __forceinline__ void bulk_commit(){ asm volatile("cp.async.bulk.commit_group;":::"memory"); }
__device__ __forceinline__ void bulk_wait_rd(){ asm volatile("cp.async.bulk.wait_group.read 0;":::"memory"); }
__device__ __forceinline__ void bulk_wait(){ asm volatile("cp.async.bulk.wait_group 0;":::"memory"); }
__device__ __forceinline__ void stsm4(uint32_t a,uint32_t r0,uint32_t r1,uint32_t r2,uint32_t r3){ asm volatile("stmatrix.sync.aligned.m8n8.x4.shared.b16 [%0], {%1,%2,%3,%4};"::"r"(a),"r"(r0),"r"(r1),"r"(r2),"r"(r3):"memory"); }

template<int N> __device__ __forceinline__ void mainloop(float* acc,int nkb,uint32_t sb,int wg,int lane,uint32_t& st,uint32_t& ph){
  uint32_t pst=0;
  #pragma unroll 1
  for(int kb=0;kb<nkb;kb++){
    mbar_wait(sb+W_BAR+st*8,ph);
    const uint32_t a=sb+st*STG+wg*8192, bq=sb+st*STG+16384;
    const uint64_t da=(uint64_t)((a>>4)&0x3fff)|(1ull<<16)|(64ull<<32)|(1ull<<62);
    const uint64_t db=(uint64_t)((bq>>4)&0x3fff)|(512ull<<16)|(64ull<<32)|(1ull<<62);
    wg_arrive();
    #pragma unroll
    for(int k=0;k<4;k++) wgmma<N>(acc,da+2*k,db+128*k,kb|k);
    wg_commit();
    if(kb>0){ wg_wait<1>(); if(lane==0) mbar_arrive(sb+W_BAR+32+pst*8); }
    pst=st; if(++st==NST){ st=0; ph^=1; }
  }
  wg_wait<0>();
  if(lane==0) mbar_arrive(sb+W_BAR+32+pst*8);
}
struct Epi { uint32_t sb; int wg,wq,lane; bool el; uint32_t sph; volatile int* cmd; };
__device__ __forceinline__ void epi_cmd(Epi& e,int map,int col,int row,int nbox,int cnt){
  if(e.el){ e.cmd[0]=map; e.cmd[1]=col; e.cmd[2]=row; e.cmd[3]=nbox; e.cmd[4]=cnt; }
  bar_arrive(4+e.wg,160);
}
__device__ __forceinline__ void epi_acquire(Epi& e){ mbar_wait(e.sb+W_BAR+96+e.wg*8,e.sph); e.sph^=1; }
__device__ __forceinline__ uint32_t act2(uint32_t u,uint32_t bb,float c1,float c3){
  uint32_t s; asm("add.rn.bf16x2 %0, %1, %2;":"=r"(s):"r"(u),"r"(bb));
  float r[2]={__uint_as_float(s<<16), __uint_as_float(s&0xffff0000u)};
  #pragma unroll
  for(int i=0;i<2;i++){
    const float z=r[i]*fmaf(r[i]*r[i],c3,c1);
    r[i]=r[i]*rcp(1.f+ex2(z));
  }
  return pack_bf16(r[0],r[1]);
}
template<int NB2> __device__ __forceinline__ void store_round(Epi& e,const float* acc,int map,int col0,int row0,int cnt,int act,const uint4* bb){
  const uint32_t stg=e.sb+W_STAGING+e.wg*16384;
  const int r=16*e.wq+(e.lane&7)+((e.lane>>3)&1)*8;
  const uint32_t ra=stg+r*128; const int sw=e.lane&7, hi=e.lane>>4;
  uint32_t pk[NB2*16];
  #pragma unroll
  for(int j=0;j<NB2*16;j++) pk[j]=pack_bf16(acc[2*j],acc[2*j+1]);
  epi_acquire(e);
  #pragma unroll
  for(int j=0;j<NB2*4;j++) stsm4(ra+(j>>2)*8192+((((2*j+hi)&7)^sw)<<4),pk[4*j],pk[4*j+1],pk[4*j+2],pk[4*j+3]);
  if(act){
    __syncwarp();
    const float c1=act==1?-2.302208198144325f:-1.4426950408889634f, c3=act==1?-0.10294323958f:0.f;
    #pragma unroll 1
    for(int i=0;i<2;i++){
      uint4 u[2][2]; uint32_t a[2];
      #pragma unroll
      for(int q=0;q<2;q++){
        const int rr=16*e.wq+8*i+4*q+(e.lane>>3);
        a[q]=stg+rr*128+(((e.lane&7)^(rr&7))<<4);
        u[q][0]=lds4(a[q]); u[q][1]=lds4(a[q]+8192);
      }
      #pragma unroll
      for(int q=0;q<2;q++)
        #pragma unroll
        for(int bx=0;bx<2;bx++){
          uint4& v=u[q][bx];
          v.x=act2(v.x,bb[bx].x,c1,c3); v.y=act2(v.y,bb[bx].y,c1,c3); v.z=act2(v.z,bb[bx].z,c1,c3); v.w=act2(v.w,bb[bx].w,c1,c3);
          sts4(a[q]+bx*8192,v);
        }
    }
  }
  fence_async();
  epi_cmd(e,map,col0,row0,NB2,cnt);
}
template<int N> __device__ __forceinline__ void store_part(const float* acc,float4* dst){
  #pragma unroll
  for(int n=0;n<N/8;n++) __stcg(dst+(n>>4)*4096+(n&15)*128,make_float4(acc[4*n],acc[4*n+1],acc[4*n+2],acc[4*n+3]));
}

__device__ __forceinline__ bool item_ready(int c,int idx){
  if(c==T_RED){ const int rbk=idx/NREDI; return ld_acq(g_cnt+C_OP+rbk)>=2*3*NSPL && ld_acq(g_cnt+C_M2+rbk)>=6; }
  if(c==T_OP){ const int rbk=idx/(3*NSPL), sp=(idx-rbk*3*NSPL)/3; return ld_acq(g_cnt+C_QA+rbk*NSPL+sp)>=8; }
  if(c==T_QA){ const uint32_t need=4*(idx>>5)+4; const uint32_t* f=g_flag+(idx&31)*96; return ld_acq(f)>=need && ld_acq(f+32)>=need && ld_acq(f+64)>=need; }
  if(c==T_M2){ return ld_acq(g_cnt+C_M1+idx/3)>=12; }
  return true;
}

template<int MODE>
__global__ void __launch_bounds__(384,1) k_work(const __grid_constant__ WParams P){
  extern __shared__ __align__(1024) uint8_t sm[];
  const uint32_t sb=(uint32_t)__cvta_generic_to_shared(sm);
  const int tid=threadIdx.x, warp=__shfl_sync(~0u,tid>>5,0), lane=tid&31;
  const uint32_t FULL=sb+W_BAR, EMPTY=sb+W_BAR+32, IFULL=sb+W_BAR+64, IEMPTY=sb+W_BAR+80;
  volatile int* idesc=(volatile int*)(sm+W_BAR+128);
  if(tid==0){
    for(int i=0;i<NST;i++){ mbar_init(FULL+i*8,1); mbar_init(EMPTY+i*8,8); }
    for(int i=0;i<2;i++){ mbar_init(IFULL+i*8,1); mbar_init(IEMPTY+i*8,8); mbar_init(sb+W_BAR+96+i*8,1); }
    asm volatile("fence.mbarrier_init.release.cluster;":::"memory");
  }
  __syncthreads();
  if(warp>=8){
    asm volatile("setmaxnreg.dec.sync.aligned.u32 40;");
    if(warp==8){
      uint32_t st=0, ph=1, it=0;
      int held=-1; int guard=0;
      const int ncls=lane==T_RED?NRB*NREDI:(lane==T_OP?NRB*3*NSPL:(lane==T_QA?NRB*32:(lane==T_M2?NRB*3:(lane==T_M1?NRB*6:0))));
      int sidx=blockIdx.x;
      while(true){
        int type, idx;
        if(MODE==0){ if(sidx<NRB*48){ type=T_KV; idx=sidx; sidx+=gridDim.x; } else { type=T_END; idx=0; } }
        else {
          while(true){
            int cand=held; bool rdy=false;
            if(lane<5){
              if(cand<0){ cand=(int)ld_rlx(g_cnt+C_NEXT+lane*32); if(cand>=ncls) cand=-1; }
              if(cand>=0) rdy=item_ready(lane,cand);
            }
            const uint32_t br=__ballot_sync(~0u,rdy), ba=__ballot_sync(~0u,cand>=0);
            if(!ba){ type=T_END; idx=0; break; }
            if(br){
              const int w=(br>>T_M2)? T_M2+__ffs(br>>T_M2)-1 : __ffs(br)-1; int got=-1;
              if(lane==w){
                if(held>=0){ got=held; held=-1; }
                else { int tk=(int)atomicAdd(g_cnt+C_NEXT+lane*32,1u); if(tk<ncls){ if(tk==cand||item_ready(lane,tk)) got=tk; else held=tk; } }
              }
              got=__shfl_sync(~0u,got,w);
              if(got>=0){ type=w; idx=got; break; }
            } else {
              __nanosleep(100);
              if(++guard>WGUARD){ g_err=21; type=T_END; idx=0; break; }
            }
          }
        }
        __syncwarp();
        if(lane==0){
          const uint32_t sl=it&1;
          mbar_wait(IEMPTY+sl*8,((it>>1)&1)^1);
          idesc[sl*2]=type; idesc[sl*2+1]=idx;
          mbar_arrive(IFULL+sl*8);
          if(type!=T_END&&type!=T_RED){
            int ma,mb,row0,col0,k0=0,nkb,nbox;
            if(type==T_KV){ const int rbk=idx/48, nt=idx-rbk*48; ma=M_XN; mb=nt<24?M_WK:M_WV; row0=rbk*128; col0=(nt<24?nt:nt-24)*256; nkb=10; nbox=4; }
            else if(type==T_M1){ const int rbk=idx/6, nt=idx-rbk*6; ma=M_Y; mb=M_W1; row0=rbk*128; col0=nt*256; nkb=10; nbox=4; }
            else if(type==T_M2){ const int rbk=idx/3, nt=idx-rbk*3; ma=M_H; mb=M_W2; row0=rbk*128; col0=nt*256; nkb=24; nbox=nt<2?4:2; }
            else if(type==T_QA){ ma=M_XN; mb=M_WQ; row0=(idx>>5)*128; col0=(idx&31)*192; nkb=10; nbox=3; }
            else { const int rbk=idx/(3*NSPL), r=idx-rbk*3*NSPL, sp=r/3, nt=r-sp*3; ma=M_OX; mb=M_WO; row0=rbk*128; col0=nt*256; k0=sp*(HD/NSPL); nkb=HD/NSPL/64; nbox=nt<2?4:2; }
            if(MODE) fence_async_all();
            const CUtensorMap* A=&P.m[ma]; const CUtensorMap* B=&P.m[mb];
            for(int kb=0;kb<nkb;kb++){
              mbar_wait(EMPTY+st*8,ph);
              const uint32_t d=sb+st*STG, fb=FULL+st*8;
              mbar_expect(fb,16384+nbox*8192);
              const int kk=k0+kb*64;
              tma2d(d,A,kk,row0,fb); tma2d(d+8192,A,kk,row0+64,fb);
              for(int j=0;j<nbox;j++) tma2d(d+16384+j*8192,B,col0+j*64,kk,fb);
              if(++st==NST){ st=0; ph^=1; }
            }
            if(type==T_QA){
              for(int q=0;q<2;q++){
                mbar_wait(EMPTY+st*8,ph);
                const uint32_t d=sb+st*STG, fb=FULL+st*8;
                mbar_expect(fb,49152);
                for(int j=0;j<6;j++) tma2d(d+j*8192,&P.m[M_K+q],col0+(j%3)*64,row0+(j/3)*64,fb);
                if(++st==NST){ st=0; ph^=1; }
              }
            }
          }
        }
        __syncwarp();
        it++;
        if(type==T_END) break;
      }
    } else if(warp<11){
      const int wg=warp-9; volatile int* cmd=(volatile int*)(sm+W_BAR+160+wg*32);
      const uint32_t stg=sb+W_STAGING+wg*16384;
      while(true){
        bar_sync(4+wg,160);
        const int map=cmd[0], col=cmd[1], row=cmd[2], nbox=cmd[3], cnt=cmd[4];
        __syncwarp();
        if(map==-2) break;
        if(lane==0){
          if(map>=0){
            tma_st(&P.m[map],stg,col,row);
            if(nbox>1) tma_st(&P.m[map],stg+8192,col+64,row);
            bulk_commit();
            bulk_wait_rd();
          }
          mbar_arrive(sb+W_BAR+96+wg*8);
          if(cnt>=0){ if(map>=0){ bulk_wait(); fence_async_all(); } else fence_gpu(); red_rel(g_cnt+cnt); }
        }
        __syncwarp();
      }
      if(lane==0) bulk_wait();
    }
  } else {
    asm volatile("setmaxnreg.inc.sync.aligned.u32 232;");
    const int wg=warp>>2, wq=warp&3, g=lane>>2, t=lane&3;
    const bool el=(tid&127)==0;
    uint32_t st=0, ph=0;
    Epi E{sb,wg,wq,lane,el,1u,(volatile int*)(sm+W_BAR+160+wg*32)};
    float acc[128];
    #pragma unroll 1
    for(uint32_t it=0;;it++){
      const uint32_t sl=it&1;
      mbar_wait(IFULL+sl*8,(it>>1)&1);
      const int type=idesc[sl*2], idx=idesc[sl*2+1];
      __syncwarp();
      if(lane==0) mbar_arrive(IEMPTY+sl*8);
      if(type==T_END) break;
      if(MODE==0||type>=T_M2||type==T_OP){
        int rbk,nt,nkb=10,map,cnt=-1,act=0,sp=0; const bf16* bias=P.b1;
        if(MODE==0||type==T_KV){ rbk=idx/48; nt=idx-rbk*48; map=M_K; if(nt>=24){ nt-=24; map=M_V; } }
        else if(type==T_M1){ rbk=idx/6; nt=idx-rbk*6; map=M_H; cnt=C_M1+rbk; act=1; }
        else if(type==T_M2){ rbk=idx/3; nt=idx-rbk*3; map=M_GATE; cnt=C_M2+rbk; act=2; bias=P.b2; nkb=24; }
        else { rbk=idx/(3*NSPL); const int r=idx-rbk*3*NSPL; sp=r/3; nt=r-sp*3; map=-1; cnt=C_OP+rbk; nkb=HD/NSPL/64; }
        const bool wide=MODE==0||type>=T_M1||nt<2;
        uint4 bb[4];
        if(MODE&&act){
          #pragma unroll
          for(int i=0;i<4;i++) if(i<2||wide) bb[i]=__ldg((const uint4*)(bias+nt*256+i*64+(lane&7)*8));
        }
        if(wide) mainloop<256>(acc,nkb,sb,wg,lane,st,ph); else mainloop<128>(acc,nkb,sb,wg,lane,st,ph);
        if(MODE&&map<0){
          float4* dst=g_opp+(size_t)(((rbk*NSPL+sp)*5+2*nt)*2+wg)*2048+(tid&127);
          store_part<128>(acc,dst);
          if(wide) store_part<128>(acc+64,dst+4096);
          epi_acquire(E);
          epi_cmd(E,-1,0,0,0,cnt);
        } else {
          store_round<2>(E,acc,map,nt*256,rbk*128+wg*64,wide?-1:cnt,act,bb);
          if(wide) store_round<2>(E,acc+64,map,nt*256+128,rbk*128+wg*64,cnt,act,bb+2);
        }
      } else if(type==T_RED){
        const int rbk=idx/NREDI, r=idx-rbk*NREDI, cb=r>>2, jq=r&3;
        const float4* src=g_opp+(size_t)((rbk*NSPL*5+cb)*2+wg)*2048+jq*512+(tid&127);
        float4 v[4][NSPL];
        #pragma unroll
        for(int j=0;j<4;j++)
          #pragma unroll
          for(int s=0;s<NSPL;s++) v[j][s]=ld_rlx4f(src+(size_t)s*5*4096+j*128);
        const int row=rbk*128+wg*64+wq*16+g;
        uint32_t gx[4][2], xx[4][2];
        #pragma unroll
        for(int j=0;j<4;j++)
          #pragma unroll
          for(int hh=0;hh<2;hh++){ const size_t o=(size_t)(row+8*hh)*D+cb*128+(4*jq+j)*8+2*t; gx[j][hh]=ld_rlx((const uint32_t*)(g_gate+o)); xx[j][hh]=ld_rlx((const uint32_t*)(P.x+o)); }
        #pragma unroll
        for(int j=0;j<4;j++){
          const int col=cb*128+(4*jq+j)*8+2*t;
          float4 a=v[j][0];
          #pragma unroll
          for(int s=1;s<NSPL;s++){ a.x+=v[j][s].x; a.y+=v[j][s].y; a.z+=v[j][s].z; a.w+=v[j][s].w; }
          #pragma unroll
          for(int hh=0;hh<2;hh++){
            const size_t o=(size_t)(row+8*hh)*D+col;
            const float s0=rb(hh?a.z:a.x), s1=rb(hh?a.w:a.y);
            const float o0=__uint_as_float(xx[j][hh]<<16)+rb(s0*__uint_as_float(gx[j][hh]<<16)), o1=__uint_as_float(xx[j][hh]&0xffff0000u)+rb(s1*__uint_as_float(gx[j][hh]&0xffff0000u));
            *(uint32_t*)(P.out+o)=pack_bf16(o0,o1);
          }
        }
      } else {
        const int rbk=idx>>5, h=idx&31;
        const int sgl=wq>>1, rh=wq&1, sg=rbk*4+wg*2+sgl;
        uint2 km[12], vm[12];
        {
          const uint2* kp=g_kmf+(size_t)((sg*H+h)*12)*32+lane; const uint2* vp=g_vmf+(size_t)((sg*H+h)*12)*32+lane;
          #pragma unroll
          for(int i=0;i<12;i++){ km[i]=ld_rlx2(kp+i*32); vm[i]=ld_rlx2(vp+i*32); }
        }
        mainloop<192>(acc,10,sb,wg,lane,st,ph);
        uint32_t pa[2][4], pm[2];
        {
          float sc[5][4];
          #pragma unroll
          for(int n=0;n<5;n++){ sc[n][0]=sc[n][1]=sc[n][2]=sc[n][3]=0.f; }
          mbar_wait(FULL+st*8,ph);
          const int kr=sgl*32+(lane&7)+((lane>>4)<<3);
          const uint32_t ka=sb+st*STG+wg*24576+kr*128; const int cs=(lane>>3)&1, sw=lane&7;
          #pragma unroll
          for(int T=0;T<12;T++){
            uint32_t qf[4]={pack_bf16(acc[8*T],acc[8*T+1]),pack_bf16(acc[8*T+2],acc[8*T+3]),pack_bf16(acc[8*T+4],acc[8*T+5]),pack_bf16(acc[8*T+6],acc[8*T+7])};
            mma16816(sc[0],qf,km[T].x,km[T].y);
            const uint32_t a=ka+(T>>2)*8192+((((T&3)*2+cs)^sw)<<4);
            uint32_t kb[4]; ldsm4(kb,a);
            mma16816(sc[1],qf,kb[0],kb[1]); mma16816(sc[2],qf,kb[2],kb[3]);
            if(rh){ ldsm4(kb,a+2048); mma16816(sc[3],qf,kb[0],kb[1]); mma16816(sc[4],qf,kb[2],kb[3]); }
          }
          __syncwarp();
          if(lane==0) mbar_arrive(EMPTY+st*8);
          if(++st==NST){ st=0; ph^=1; }
          const float NEG=rb(-1e9f);
          float mx[2]={-3.4e38f,-3.4e38f};
          #pragma unroll
          for(int n=0;n<5;n++)
            #pragma unroll
            for(int i=0;i<4;i++){
              float v=rb(rb(sc[n][i])*0.07216878364870322f);
              if(n>0){ const int key=8*(n-1)+2*t+(i&1), row=16*rh+g+8*(i>>1); if(key>row) v=NEG; }
              sc[n][i]=v; mx[i>>1]=fmaxf(mx[i>>1],v);
            }
          float sum[2]={0.f,0.f};
          #pragma unroll
          for(int r=0;r<2;r++){ mx[r]=fmaxf(mx[r],__shfl_xor_sync(~0u,mx[r],1)); mx[r]=fmaxf(mx[r],__shfl_xor_sync(~0u,mx[r],2)); }
          #pragma unroll
          for(int n=0;n<5;n++)
            #pragma unroll
            for(int i=0;i<4;i++){ const float e=ex2((sc[n][i]-mx[i>>1])*1.4426950408889634f); sc[n][i]=e; sum[i>>1]+=e; }
          #pragma unroll
          for(int r=0;r<2;r++){ sum[r]+=__shfl_xor_sync(~0u,sum[r],1); sum[r]+=__shfl_xor_sync(~0u,sum[r],2); sum[r]=rcp(sum[r]); }
          pm[0]=pack_bf16(sc[0][0]*sum[0],sc[0][1]*sum[0]); pm[1]=pack_bf16(sc[0][2]*sum[1],sc[0][3]*sum[1]);
          #pragma unroll
          for(int ks=0;ks<2;ks++){
            pa[ks][0]=pack_bf16(sc[1+2*ks][0]*sum[0],sc[1+2*ks][1]*sum[0]); pa[ks][1]=pack_bf16(sc[1+2*ks][2]*sum[1],sc[1+2*ks][3]*sum[1]);
            pa[ks][2]=pack_bf16(sc[2+2*ks][0]*sum[0],sc[2+2*ks][1]*sum[0]); pa[ks][3]=pack_bf16(sc[2+2*ks][2]*sum[1],sc[2+2*ks][3]*sum[1]);
          }
        }
        {
          mbar_wait(FULL+st*8,ph);
          const int vr=sgl*32+(lane&7)+(((lane>>3)&1)<<3);
          const uint32_t va=sb+st*STG+wg*24576+vr*128; const int cs=lane>>4, sw=lane&7;
          #pragma unroll
          for(int T=0;T<12;T++){
            float* o0=acc+8*T; float* o1=acc+8*T+4;
            #pragma unroll
            for(int i=0;i<8;i++) o0[i]=0.f;
            mma1688(o0,pm[0],pm[1],vm[T].x); mma1688(o1,pm[0],pm[1],vm[T].y);
            const uint32_t a=va+(T>>2)*8192+((((T&3)*2+cs)^sw)<<4);
            uint32_t vb[4]; ldsm4t(vb,a);
            mma16816(o0,pa[0],vb[0],vb[1]); mma16816(o1,pa[0],vb[2],vb[3]);
            ldsm4t(vb,a+2048);
            mma16816(o0,pa[1],vb[0],vb[1]); mma16816(o1,pa[1],vb[2],vb[3]);
          }
          __syncwarp();
          if(lane==0) mbar_arrive(EMPTY+st*8);
          if(++st==NST){ st=0; ph^=1; }
        }
        store_round<2>(E,acc,M_OX,h*192,rbk*128+wg*64,-1,0,nullptr);
        store_round<1>(E,acc+64,M_OX,h*192+128,rbk*128+wg*64,C_QA+rbk*NSPL+(h>>2),0,nullptr);
      }
    }
    epi_acquire(E);
    epi_cmd(E,-2,0,0,0,-1);
  }
}
typedef CUresult (*EncFn)(CUtensorMap*,CUtensorMapDataType,cuuint32_t,void*,const cuuint64_t*,const cuuint64_t*,const cuuint32_t*,const cuuint32_t*,CUtensorMapInterleave,CUtensorMapSwizzle,CUtensorMapL2promotion,CUtensorMapFloatOOBfill);
static CUtensorMap mk2d(const void* base,uint64_t cols,uint64_t rows,uint32_t bc,uint32_t br){
  static EncFn fn=nullptr;
  if(!fn){ void* p=nullptr; cudaDriverEntryPointQueryResult qr; cudaGetDriverEntryPoint("cuTensorMapEncodeTiled",&p,cudaEnableDefault,&qr); fn=(EncFn)p; }
  CUtensorMap m; cuuint64_t gd[2]={cols,rows}; cuuint64_t gs[1]={cols*2}; cuuint32_t bd[2]={bc,br}; cuuint32_t es[2]={1,1};
  fn(&m,CU_TENSOR_MAP_DATA_TYPE_BFLOAT16,2,(void*)base,gd,gs,bd,es,CU_TENSOR_MAP_INTERLEAVE_NONE,CU_TENSOR_MAP_SWIZZLE_128B,CU_TENSOR_MAP_L2_PROMOTION_L2_128B,CU_TENSOR_MAP_FLOAT_OOB_FILL_NONE);
  return m;
}
template<class T> static T* sym(T& s){ void* p; cudaGetSymbolAddress(&p,s); return (T*)p; }
}

int g_reconly=0;
extern "C" void kernel_launch(void* const* d_in, const int* in_sizes, int n_in, void* d_out, int out_size) {
  using namespace rk;
  const bf16* x=(const bf16*)d_in[0]; const bf16* mem0=(const bf16*)d_in[1];
  const bf16* Wq=(const bf16*)d_in[2]; const bf16* Wk=(const bf16*)d_in[3]; const bf16* Wv=(const bf16*)d_in[4]; const bf16* Wo=(const bf16*)d_in[5];
  const bf16* w1=(const bf16*)d_in[8]; const bf16* b1=(const bf16*)d_in[9]; const bf16* w2=(const bf16*)d_in[10]; const bf16* b2=(const bf16*)d_in[11];
  cudaStream_t st=cudaStreamPerThread;
  cudaFuncSetAttribute(k_rec,cudaFuncAttributeMaxDynamicSharedMemorySize,SM_TOTAL);
  cudaFuncSetAttribute(k_work<0>,cudaFuncAttributeMaxDynamicSharedMemorySize,W_TOTAL);
  cudaFuncSetAttribute(k_work<1>,cudaFuncAttributeMaxDynamicSharedMemorySize,W_TOTAL);
  bf16* k=(bf16*)sym(g_k); bf16* v=(bf16*)sym(g_v);
  WParams P;
  P.m[M_XN]=mk2d(sym(g_xn),D,S,64,64); P.m[M_Y]=mk2d(sym(g_y),D,S,64,64); P.m[M_H]=mk2d(sym(g_h),F,S,64,64); P.m[M_OX]=mk2d(sym(g_ox),HD,S,64,64);
  P.m[M_K]=mk2d(k,HD,S,64,64); P.m[M_V]=mk2d(v,HD,S,64,64); P.m[M_GATE]=mk2d(sym(g_gate),D,S,64,64);
  P.m[M_WQ]=mk2d(Wq,HD,D,64,64); P.m[M_WK]=mk2d(Wk,HD,D,64,64); P.m[M_WV]=mk2d(Wv,HD,D,64,64);
  P.m[M_W1]=mk2d(w1,F,D,64,64); P.m[M_W2]=mk2d(w2,D,F,64,64); P.m[M_WO]=mk2d(Wo,D,HD,64,64);
  P.x=x; P.b1=b1; P.b2=b2; P.out=(bf16*)d_out;
  k_pre<<<S/8,256,0,st>>>(x,mem0);
  if(!(g_reconly&1)) k_work<0><<<132,384,W_TOTAL,st>>>(P);
  if(!(g_reconly&4)){
    cudaLaunchConfig_t cfg={}; cfg.gridDim=dim3(NCTA); cfg.blockDim=dim3(256); cfg.dynamicSmemBytes=SM_TOTAL; cfg.stream=st;
    cudaLaunchAttribute at[1]; at[0].id=cudaLaunchAttributeClusterDimension; at[0].val.clusterDim.x=3; at[0].val.clusterDim.y=1; at[0].val.clusterDim.z=1; cfg.attrs=at; cfg.numAttrs=1;
    CUtensorMap tk=mk2d(k,HD,S,64,32), tv=mk2d(v,HD,S,64,32);
    cudaLaunchKernelEx(&cfg,k_rec,tk,tv,Wq,Wk,Wv,Wo);
  }
  if(!(g_reconly&2)){
    cudaLaunchConfig_t cfg={}; cfg.gridDim=dim3(132); cfg.blockDim=dim3(384); cfg.dynamicSmemBytes=W_TOTAL; cfg.stream=st;
    cudaLaunchAttribute at[1]; at[0].id=cudaLaunchAttributeProgrammaticStreamSerialization; at[0].val.programmaticStreamSerializationAllowed=1; cfg.attrs=at; cfg.numAttrs=PDL;
    cudaLaunchKernelEx(&cfg,k_work<1>,P);
  }
}
```

```cpp
#include <cuda_runtime.h>
#include <cuda_bf16.h>
#include <stdint.h>
#include <cuda.h>

namespace rk {
typedef __nv_bfloat16 bf16;
constexpr int S=2048, D=640, H=32, DH=192, HD=6144, NSEG=64, F=1536;
constexpr uint32_t SENT=0xFFFFFFFFu;
#define GUARDN 400000
constexpr int GUARD=GUARDN;
#define RCOPY 2
constexpr int NCTA=96;

__device__ __align__(128) bf16 g_xn[S*D];
__device__ __align__(128) bf16 g_y[S*D];
__device__ __align__(128) bf16 g_h[S*F];
__device__ __align__(128) bf16 g_gate[S*D];
__device__ __align__(128) bf16 g_k[(size_t)S*HD];
__device__ __align__(128) bf16 g_v[(size_t)S*HD];
__device__ __align__(128) uint2 g_kmf[NSEG*H*12*32];
__device__ __align__(128) uint2 g_vmf[NSEG*H*12*32];
__device__ __align__(128) uint32_t g_flag[NCTA*32];
__device__ __align__(128) bf16 g_ox[(size_t)S*HD];
__device__ __align__(128) float4 g_opp[(size_t)16*8*5*2*2048];
constexpr int C_NEXT=0, C_OP=256, C_M2=288, C_M1=320, C_QA=352, C_KV=480, C_NUM=512;
__device__ __align__(128) uint32_t g_cnt[C_NUM];
#define PDL 1
__device__ __align__(128) uint32_t g_mem[(NSEG+1)*RCOPY*80*32];
__device__ __align__(128) uint32_t g_part[80*32*64];
__device__ int g_err;
__device__ unsigned long long g_gt[128*4];
#define GT(i) do{ if(threadIdx.x==0){ unsigned long long g0; asm volatile("mov.u64 %0, %%globaltimer;":"=l"(g0)); g_gt[blockIdx.x*4+(i)]=g0; } }while(0)

__device__ __forceinline__ float rb(float x){ return __bfloat162float(__float2bfloat16(x)); }
__device__ __forceinline__ uint32_t pack_bf16(float lo,float hi){ uint32_t r; asm("cvt.rn.bf16x2.f32 %0, %1, %2;":"=r"(r):"f"(hi),"f"(lo)); return r; }
__device__ __forceinline__ uint32_t movm(uint32_t a){ uint32_t d; asm volatile("movmatrix.sync.aligned.m8n8.trans.b16 %0, %1;":"=r"(d):"r"(a)); return d; }
__device__ __forceinline__ uint4 ldg_rlx4(const uint32_t* p){ uint4 v; asm volatile("ld.relaxed.gpu.global.v4.u32 {%0,%1,%2,%3}, [%4];":"=r"(v.x),"=r"(v.y),"=r"(v.z),"=r"(v.w):"l"(p):"memory"); return v; }
__device__ __forceinline__ void stg_rlx1(uint32_t* p,uint32_t a){ asm volatile("st.relaxed.gpu.global.u32 [%0], %1;"::"l"(p),"r"(a):"memory"); }
__device__ __forceinline__ void stg_rlx2(uint32_t* p,uint32_t a,uint32_t b){ asm volatile("st.relaxed.gpu.global.v2.u32 [%0], {%1,%2};"::"l"(p),"r"(a),"r"(b):"memory"); }
__device__ __forceinline__ void bar_sync(int id,int n){ asm volatile("bar.sync %0, %1;"::"r"(id),"r"(n):"memory"); }
__device__ __forceinline__ void bar_arrive(int id,int n){ asm volatile("bar.arrive %0, %1;"::"r"(id),"r"(n):"memory"); }
__device__ __forceinline__ void mma16816(float* d,const uint32_t* a,uint32_t b0,uint32_t b1){
  asm volatile("mma.sync.aligned.m16n8k16.row.col.f32.bf16.bf16.f32 {%0,%1,%2,%3},{%4,%5,%6,%7},{%8,%9},{%0,%1,%2,%3};"
   :"+f"(d[0]),"+f"(d[1]),"+f"(d[2]),"+f"(d[3]):"r"(a[0]),"r"(a[1]),"r"(a[2]),"r"(a[3]),"r"(b0),"r"(b1));
}
__device__ __forceinline__ void mma1688(float* d,uint32_t a0,uint32_t a1,uint32_t b0){
  asm volatile("mma.sync.aligned.m16n8k8.row.col.f32.bf16.bf16.f32 {%0,%1,%2,%3},{%4,%5},{%6},{%0,%1,%2,%3};"
   :"+f"(d[0]),"+f"(d[1]),"+f"(d[2]),"+f"(d[3]):"r"(a0),"r"(a1),"r"(b0));
}
__device__ __forceinline__ void ldsm4t(uint32_t* r,uint32_t addr){ asm volatile("ldmatrix.sync.aligned.m8n8.x4.trans.shared.b16 {%0,%1,%2,%3}, [%4];":"=r"(r[0]),"=r"(r[1]),"=r"(r[2]),"=r"(r[3]):"r"(addr):"memory"); }
__device__ __forceinline__ void ldsm4(uint32_t* r,uint32_t addr){ asm volatile("ldmatrix.sync.aligned.m8n8.x4.shared.b16 {%0,%1,%2,%3}, [%4];":"=r"(r[0]),"=r"(r[1]),"=r"(r[2]),"=r"(r[3]):"r"(addr):"memory"); }
__device__ __forceinline__ void stsm4(uint32_t a,uint32_t r0,uint32_t r1,uint32_t r2,uint32_t r3){ asm volatile("stmatrix.sync.aligned.m8n8.x4.shared.b16 [%0], {%1,%2,%3,%4};"::"r"(a),"r"(r0),"r"(r1),"r"(r2),"r"(r3):"memory"); }
__device__ __forceinline__ void stsm2(uint32_t a,uint32_t r0,uint32_t r1){ asm volatile("stmatrix.sync.aligned.m8n8.x2.shared.b16 [%0], {%1,%2};"::"r"(a),"r"(r0),"r"(r1):"memory"); }
__device__ __forceinline__ void cp16(uint32_t dst,const void* src){ asm volatile("cp.async.cg.shared.global [%0], [%1], 16;"::"r"(dst),"l"(src):"memory"); }
__device__ __forceinline__ void cp_wait_all(){ asm volatile("cp.async.wait_all;":::"memory"); }
__device__ __forceinline__ void fence_async(){ asm volatile("fence.proxy.async.shared::cta;":::"memory"); }
__device__ __forceinline__ void sts4f(uint32_t a,const float* v){ asm volatile("st.shared.v4.f32 [%0], {%1,%2,%3,%4};"::"r"(a),"f"(v[0]),"f"(v[1]),"f"(v[2]),"f"(v[3]):"memory"); }
__device__ __forceinline__ void sts4(uint32_t a,uint4 v){ asm volatile("st.shared.v4.u32 [%0], {%1,%2,%3,%4};"::"r"(a),"r"(v.x),"r"(v.y),"r"(v.z),"r"(v.w):"memory"); }
__device__ __forceinline__ void sts4r(uint32_t a,const uint32_t* v){ asm volatile("st.shared.v4.u32 [%0], {%1,%2,%3,%4};"::"r"(a),"r"(v[0]),"r"(v[1]),"r"(v[2]),"r"(v[3]):"memory"); }
__device__ __forceinline__ void sts2(uint32_t a,uint32_t x,uint32_t y){ asm volatile("st.shared.v2.u32 [%0], {%1,%2};"::"r"(a),"r"(x),"r"(y):"memory"); }
__device__ __forceinline__ float4 lds4f(uint32_t a){ float4 v; asm volatile("ld.shared.v4.f32 {%0,%1,%2,%3}, [%4];":"=f"(v.x),"=f"(v.y),"=f"(v.z),"=f"(v.w):"r"(a):"memory"); return v; }
__device__ __forceinline__ float2 lds2f(uint32_t a){ float2 v; asm volatile("ld.shared.v2.f32 {%0,%1}, [%2];":"=f"(v.x),"=f"(v.y):"r"(a):"memory"); return v; }
__device__ __forceinline__ uint4 lds4(uint32_t a){ uint4 v; asm volatile("ld.shared.v4.u32 {%0,%1,%2,%3}, [%4];":"=r"(v.x),"=r"(v.y),"=r"(v.z),"=r"(v.w):"r"(a):"memory"); return v; }
__device__ __forceinline__ void lds4r(uint32_t* r,uint32_t a){ asm volatile("ld.shared.v4.u32 {%0,%1,%2,%3}, [%4];":"=r"(r[0]),"=r"(r[1]),"=r"(r[2]),"=r"(r[3]):"r"(a):"memory"); }
__device__ __forceinline__ uint2 lds2(uint32_t a){ uint2 v; asm volatile("ld.shared.v2.u32 {%0,%1}, [%2];":"=r"(v.x),"=r"(v.y):"r"(a):"memory"); return v; }
__device__ __forceinline__ float ex2(float x){ float r; asm("ex2.approx.ftz.f32 %0, %1;":"=f"(r):"f"(x)); return r; }
__device__ __forceinline__ float rcp(float x){ float r; asm("rcp.approx.ftz.f32 %0, %1;":"=f"(r):"f"(x)); return r; }
__device__ __forceinline__ void mbar_init(uint32_t a,int n){ asm volatile("mbarrier.init.shared.b64 [%0], %1;"::"r"(a),"r"(n):"memory"); }
__device__ __forceinline__ void mbar_expect(uint32_t a,int bytes){ asm volatile("mbarrier.arrive.expect_tx.shared.b64 _, [%0], %1;"::"r"(a),"r"(bytes):"memory"); }
__device__ __forceinline__ void mbar_arrive(uint32_t a){ asm volatile("mbarrier.arrive.shared.b64 _, [%0];"::"r"(a):"memory"); }
__device__ __forceinline__ bool mbar_try(uint32_t a,uint32_t par){ uint32_t ok; asm volatile("{\n.reg .pred p;\nmbarrier.try_wait.parity.shared.b64 p, [%1], %2;\nselp.u32 %0,1,0,p;\n}":"=r"(ok):"r"(a),"r"(par):"memory"); return ok; }
__device__ __forceinline__ bool mbar_try_cl(uint32_t a,uint32_t par){ uint32_t ok; asm volatile("{\n.reg .pred p;\nmbarrier.try_wait.parity.acquire.cluster.shared::cta.b64 p, [%1], %2;\nselp.u32 %0,1,0,p;\n}":"=r"(ok):"r"(a),"r"(par):"memory"); return ok; }
__device__ __forceinline__ void bulk_g2s(uint32_t dst,const void* src,int bytes,uint32_t mb){ asm volatile("cp.async.bulk.shared::cluster.global.mbarrier::complete_tx::bytes [%0], [%1], %2, [%3];"::"r"(dst),"l"(src),"r"(bytes),"r"(mb):"memory"); }
__device__ __forceinline__ uint32_t mapa(uint32_t a,uint32_t r){ uint32_t d; asm("mapa.shared::cluster.u32 %0, %1, %2;":"=r"(d):"r"(a),"r"(r)); return d; }
__device__ __forceinline__ void st_async2(uint32_t ra,uint32_t x,uint32_t y,uint32_t rmb){ asm volatile("st.async.weak.shared::cluster.mbarrier::complete_tx::bytes.v2.b32 [%0], {%1,%2}, [%3];"::"r"(ra),"r"(x),"r"(y),"r"(rmb):"memory"); }
__device__ __forceinline__ void st_async4(uint32_t ra,uint32_t x,uint32_t y,uint32_t z,uint32_t w,uint32_t rmb){ asm volatile("st.async.weak.shared::cluster.mbarrier::complete_tx::bytes.v4.b32 [%0], {%1,%2,%3,%4}, [%5];"::"r"(ra),"r"(x),"r"(y),"r"(z),"r"(w),"r"(rmb):"memory"); }
__device__ __forceinline__ void stg_rlx4(uint32_t* p,uint32_t a,uint32_t b,uint32_t c,uint32_t d){ asm volatile("st.relaxed.gpu.global.v4.u32 [%0], {%1,%2,%3,%4};"::"l"(p),"r"(a),"r"(b),"r"(c),"r"(d):"memory"); }
__device__ __forceinline__ void cluster_sync(){ asm volatile("barrier.cluster.arrive.release.aligned;\nbarrier.cluster.wait.acquire.aligned;":::"memory"); }
__device__ __forceinline__ uint32_t ld_acq(const uint32_t* p){ uint32_t v; asm volatile("ld.acquire.gpu.global.u32 %0, [%1];":"=r"(v):"l"(p):"memory"); return v; }
__device__ __forceinline__ void fence_async_all(){ asm volatile("fence.proxy.async;":::"memory"); }
__device__ __forceinline__ void fence_gpu(){ asm volatile("fence.acq_rel.gpu;":::"memory"); }

template<int NL,class V,class LDF,class OKF>
__device__ __forceinline__ int poll1(V* u,LDF ld,OKF ok,bool& dead,int code){
  #pragma unroll
  for(int i=0;i<NL;i++) u[i]=ld(i);
  int guard=0;
  while(true){
    bool f[NL]; bool a=true;
    #pragma unroll
    for(int i=0;i<NL;i++){ f[i]=ok(u[i]); a=a&&f[i]; }
    if(__all_sync(~0u,a)||dead) break;
    #pragma unroll
    for(int i=0;i<NL;i++) if(!f[i]) u[i]=ld(i);
    if(++guard>GUARD){ dead=true; g_err=code; }
  }
  return guard;
}
template<int NL,class V,class LDF,class OKF>
__device__ __forceinline__ void poll2(V* u,LDF ld,OKF ok,bool& dead,int code){
  int guard=0;
  while(true){
    bool f[NL]; bool a=true;
    #pragma unroll
    for(int i=0;i<NL;i++){ f[i]=ok(u[i]); a=a&&f[i]; }
    if(__all_sync(~0u,a)||dead) break;
    #pragma unroll
    for(int i=0;i<NL;i++) if(!f[i]) u[i]=ld(i);
    if(++guard>GUARD){ dead=true; g_err=code; }
  }
}
__device__ __forceinline__ void spin(uint32_t n){ uint32_t t0,t1; asm volatile("mov.u32 %0, %%clock;":"=r"(t0)); do{ asm volatile("mov.u32 %0, %%clock;":"=r"(t1)); }while(t1-t0<n); }
__device__ __forceinline__ void keep(const uint4& v){ asm volatile(""::"r"(v.x),"r"(v.y),"r"(v.z),"r"(v.w)); }
template<int NL,int D,class LDF,class OKF>
__device__ __forceinline__ int pollS(uint4* out,uint4 (*u)[NL],LDF ld,OKF ok,bool& dead,int code,uint32_t stag){
  #pragma unroll
  for(int j=0;j<D;j++){
    if(j) spin(stag);
    #pragma unroll
    for(int i=0;i<NL;i++) u[j][i]=ld(i);
  }
  int guard=0;
  while(true){
    bool fin=false;
    #pragma unroll
    for(int j=0;j<D;j++){
      if(!fin){
        bool f[NL]; bool a=true;
        #pragma unroll
        for(int i=0;i<NL;i++){ f[i]=ok(u[j][i]); a=a&&f[i]; }
        if(__all_sync(~0u,a)||dead){
          fin=true;
          #pragma unroll
          for(int i=0;i<NL;i++) out[i]=u[j][i];
        } else {
          #pragma unroll
          for(int i=0;i<NL;i++) if(!f[i]) u[j][i]=ld(i);
          guard++;
        }
      }
    }
    if(fin) break;
    if(guard>GUARD){ dead=true; g_err=code; }
  }
  return guard;
}
template<int N> __device__ __forceinline__ void wgmma(float* d,uint64_t da,uint64_t db,int sc);
template<> __device__ __forceinline__ void wgmma<128>(float* d,uint64_t da,uint64_t db,int sc){
  asm volatile("{\n.reg .pred p;\nsetp.ne.b32 p, %66, 0;\nwgmma.mma_async.sync.aligned.m64n128k16.f32.bf16.bf16 {%0,%1,%2,%3,%4,%5,%6,%7,%8,%9,%10,%11,%12,%13,%14,%15,%16,%17,%18,%19,%20,%21,%22,%23,%24,%25,%26,%27,%28,%29,%30,%31,%32,%33,%34,%35,%36,%37,%38,%39,%40,%41,%42,%43,%44,%45,%46,%47,%48,%49,%50,%51,%52,%53,%54,%55,%56,%57,%58,%59,%60,%61,%62,%63}, %64, %65, p, 1, 1, 0, 1;\n}"
   :"+f"(d[0]),"+f"(d[1]),"+f"(d[2]),"+f"(d[3]),"+f"(d[4]),"+f"(d[5]),"+f"(d[6]),"+f"(d[7]),"+f"(d[8]),"+f"(d[9]),"+f"(d[10]),"+f"(d[11]),"+f"(d[12]),"+f"(d[13]),"+f"(d[14]),"+f"(d[15]),"+f"(d[16]),"+f"(d[17]),"+f"(d[18]),"+f"(d[19]),"+f"(d[20]),"+f"(d[21]),"+f"(d[22]),"+f"(d[23]),"+f"(d[24]),"+f"(d[25]),"+f"(d[26]),"+f"(d[27]),"+f"(d[28]),"+f"(d[29]),"+f"(d[30]),"+f"(d[31]),"+f"(d[32]),"+f"(d[33]),"+f"(d[34]),"+f"(d[35]),"+f"(d[36]),"+f"(d[37]),"+f"(d[38]),"+f"(d[39]),"+f"(d[40]),"+f"(d[41]),"+f"(d[42]),"+f"(d[43]),"+f"(d[44]),"+f"(d[45]),"+f"(d[46]),"+f"(d[47]),"+f"(d[48]),"+f"(d[49]),"+f"(d[50]),"+f"(d[51]),"+f"(d[52]),"+f"(d[53]),"+f"(d[54]),"+f"(d[55]),"+f"(d[56]),"+f"(d[57]),"+f"(d[58]),"+f"(d[59]),"+f"(d[60]),"+f"(d[61]),"+f"(d[62]),"+f"(d[63]):"l"(da),"l"(db),"r"(sc));
}
template<> __device__ __forceinline__ void wgmma<192>(float* d,uint64_t da,uint64_t db,int sc){
  asm volatile("{\n.reg .pred p;\nsetp.ne.b32 p, %98, 0;\nwgmma.mma_async.sync.aligned.m64n192k16.f32.bf16.bf16 {%0,%1,%2,%3,%4,%5,%6,%7,%8,%9,%10,%11,%12,%13,%14,%15,%16,%17,%18,%19,%20,%21,%22,%23,%24,%25,%26,%27,%28,%29,%30,%31,%32,%33,%34,%35,%36,%37,%38,%39,%40,%41,%42,%43,%44,%45,%46,%47,%48,%49,%50,%51,%52,%53,%54,%55,%56,%57,%58,%59,%60,%61,%62,%63,%64,%65,%66,%67,%68,%69,%70,%71,%72,%73,%74,%75,%76,%77,%78,%79,%80,%81,%82,%83,%84,%85,%86,%87,%88,%89,%90,%91,%92,%93,%94,%95}, %96, %97, p, 1, 1, 0, 1;\n}"
   :"+f"(d[0]),"+f"(d[1]),"+f"(d[2]),"+f"(d[3]),"+f"(d[4]),"+f"(d[5]),"+f"(d[6]),"+f"(d[7]),"+f"(d[8]),"+f"(d[9]),"+f"(d[10]),"+f"(d[11]),"+f"(d[12]),"+f"(d[13]),"+f"(d[14]),"+f"(d[15]),"+f"(d[16]),"+f"(d[17]),"+f"(d[18]),"+f"(d[19]),"+f"(d[20]),"+f"(d[21]),"+f"(d[22]),"+f"(d[23]),"+f"(d[24]),"+f"(d[25]),"+f"(d[26]),"+f"(d[27]),"+f"(d[28]),"+f"(d[29]),"+f"(d[30]),"+f"(d[31]),"+f"(d[32]),"+f"(d[33]),"+f"(d[34]),"+f"(d[35]),"+f"(d[36]),"+f"(d[37]),"+f"(d[38]),"+f"(d[39]),"+f"(d[40]),"+f"(d[41]),"+f"(d[42]),"+f"(d[43]),"+f"(d[44]),"+f"(d[45]),"+f"(d[46]),"+f"(d[47]),"+f"(d[48]),"+f"(d[49]),"+f"(d[50]),"+f"(d[51]),"+f"(d[52]),"+f"(d[53]),"+f"(d[54]),"+f"(d[55]),"+f"(d[56]),"+f"(d[57]),"+f"(d[58]),"+f"(d[59]),"+f"(d[60]),"+f"(d[61]),"+f"(d[62]),"+f"(d[63]),"+f"(d[64]),"+f"(d[65]),"+f"(d[66]),"+f"(d[67]),"+f"(d[68]),"+f"(d[69]),"+f"(d[70]),"+f"(d[71]),"+f"(d[72]),"+f"(d[73]),"+f"(d[74]),"+f"(d[75]),"+f"(d[76]),"+f"(d[77]),"+f"(d[78]),"+f"(d[79]),"+f"(d[80]),"+f"(d[81]),"+f"(d[82]),"+f"(d[83]),"+f"(d[84]),"+f"(d[85]),"+f"(d[86]),"+f"(d[87]),"+f"(d[88]),"+f"(d[89]),"+f"(d[90]),"+f"(d[91]),"+f"(d[92]),"+f"(d[93]),"+f"(d[94]),"+f"(d[95]):"l"(da),"l"(db),"r"(sc));
}
template<> __device__ __forceinline__ void wgmma<256>(float* d,uint64_t da,uint64_t db,int sc){
  asm volatile("{\n.reg .pred p;\nsetp.ne.b32 p, %130, 0;\nwgmma.mma_async.sync.aligned.m64n256k16.f32.bf16.bf16 {%0,%1,%2,%3,%4,%5,%6,%7,%8,%9,%10,%11,%12,%13,%14,%15,%16,%17,%18,%19,%20,%21,%22,%23,%24,%25,%26,%27,%28,%29,%30,%31,%32,%33,%34,%35,%36,%37,%38,%39,%40,%41,%42,%43,%44,%45,%46,%47,%48,%49,%50,%51,%52,%53,%54,%55,%56,%57,%58,%59,%60,%61,%62,%63,%64,%65,%66,%67,%68,%69,%70,%71,%72,%73,%74,%75,%76,%77,%78,%79,%80,%81,%82,%83,%84,%85,%86,%87,%88,%89,%90,%91,%92,%93,%94,%95,%96,%97,%98,%99,%100,%101,%102,%103,%104,%105,%106,%107,%108,%109,%110,%111,%112,%113,%114,%115,%116,%117,%118,%119,%120,%121,%122,%123,%124,%125,%126,%127}, %128, %129, p, 1, 1, 0, 1;\n}"
   :"+f"(d[0]),"+f"(d[1]),"+f"(d[2]),"+f"(d[3]),"+f"(d[4]),"+f"(d[5]),"+f"(d[6]),"+f"(d[7]),"+f"(d[8]),"+f"(d[9]),"+f"(d[10]),"+f"(d[11]),"+f"(d[12]),"+f"(d[13]),"+f"(d[14]),"+f"(d[15]),"+f"(d[16]),"+f"(d[17]),"+f"(d[18]),"+f"(d[19]),"+f"(d[20]),"+f"(d[21]),"+f"(d[22]),"+f"(d[23]),"+f"(d[24]),"+f"(d[25]),"+f"(d[26]),"+f"(d[27]),"+f"(d[28]),"+f"(d[29]),"+f"(d[30]),"+f"(d[31]),"+f"(d[32]),"+f"(d[33]),"+f"(d[34]),"+f"(d[35]),"+f"(d[36]),"+f"(d[37]),"+f"(d[38]),"+f"(d[39]),"+f"(d[40]),"+f"(d[41]),"+f"(d[42]),"+f"(d[43]),"+f"(d[44]),"+f"(d[45]),"+f"(d[46]),"+f"(d[47]),"+f"(d[48]),"+f"(d[49]),"+f"(d[50]),"+f"(d[51]),"+f"(d[52]),"+f"(d[53]),"+f"(d[54]),"+f"(d[55]),"+f"(d[56]),"+f"(d[57]),"+f"(d[58]),"+f"(d[59]),"+f"(d[60]),"+f"(d[61]),"+f"(d[62]),"+f"(d[63]),"+f"(d[64]),"+f"(d[65]),"+f"(d[66]),"+f"(d[67]),"+f"(d[68]),"+f"(d[69]),"+f"(d[70]),"+f"(d[71]),"+f"(d[72]),"+f"(d[73]),"+f"(d[74]),"+f"(d[75]),"+f"(d[76]),"+f"(d[77]),"+f"(d[78]),"+f"(d[79]),"+f"(d[80]),"+f"(d[81]),"+f"(d[82]),"+f"(d[83]),"+f"(d[84]),"+f"(d[85]),"+f"(d[86]),"+f"(d[87]),"+f"(d[88]),"+f"(d[89]),"+f"(d[90]),"+f"(d[91]),"+f"(d[92]),"+f"(d[93]),"+f"(d[94]),"+f"(d[95]),"+f"(d[96]),"+f"(d[97]),"+f"(d[98]),"+f"(d[99]),"+f"(d[100]),"+f"(d[101]),"+f"(d[102]),"+f"(d[103]),"+f"(d[104]),"+f"(d[105]),"+f"(d[106]),"+f"(d[107]),"+f"(d[108]),"+f"(d[109]),"+f"(d[110]),"+f"(d[111]),"+f"(d[112]),"+f"(d[113]),"+f"(d[114]),"+f"(d[115]),"+f"(d[116]),"+f"(d[117]),"+f"(d[118]),"+f"(d[119]),"+f"(d[120]),"+f"(d[121]),"+f"(d[122]),"+f"(d[123]),"+f"(d[124]),"+f"(d[125]),"+f"(d[126]),"+f"(d[127]):"l"(da),"l"(db),"r"(sc));
}
__global__ void __launch_bounds__(256) k_pre(const bf16* __restrict__ x,const bf16* __restrict__ mem0){
  const int warp=threadIdx.x>>5, lane=threadIdx.x&31;
  const int row=blockIdx.x*8+warp;
  asm volatile("griddepcontrol.launch_dependents;");
  {
    int i=blockIdx.x*256+threadIdx.x; int n=gridDim.x*256;
    for(int k=i;k<(NSEG+1)*RCOPY*80*32;k+=n){
      uint32_t v=SENT;
      if(k<RCOPY*80*32){ int fb=(k%2560)>>5, r=(k>>2)&7, w=k&3; const uint16_t* mp=(const uint16_t*)mem0+r*D+(fb>>1)*16+(fb&1)*4+w; v=mp[0]|((uint32_t)mp[8]<<16);
        if(v==SENT) v=0x7FFF7FFFu; }
      g_mem[k]=v;
    }
    if(i==0) g_err=0;
    if(i<NCTA*32) g_flag[i]=0;
    if(i<C_NUM) g_cnt[i]=0;
  }
  float v[20];
  {
    const uint32_t* p=(const uint32_t*)(x+(size_t)row*D);
    #pragma unroll
    for(int i=0;i<10;i++){ uint32_t u=p[lane+32*i]; v[2*i]=__uint_as_float(u<<16); v[2*i+1]=__uint_as_float(u&0xffff0000u); }
  }
  #pragma unroll
  for(int pass=0;pass<2;pass++){
    float s=0;
    #pragma unroll
    for(int i=0;i<20;i++) s+=v[i];
    #pragma unroll
    for(int o=16;o;o>>=1) s+=__shfl_xor_sync(~0u,s,o);
    float mean=s*(1.f/D);
    float q=0;
    #pragma unroll
    for(int i=0;i<20;i++){ float d=v[i]-mean; q+=d*d; }
    #pragma unroll
    for(int o=16;o;o>>=1) q+=__shfl_xor_sync(~0u,q,o);
    float var=rb(q*(1.f/D)), mb=rb(mean);
    float den=rb(sqrtf(rb(var+1e-5f)));
    uint32_t* o=(uint32_t*)((pass?g_y:g_xn)+(size_t)row*D);
    #pragma unroll
    for(int i=0;i<10;i++){
      float a=rb(rb(v[2*i]-mb)/den), b=rb(rb(v[2*i+1]-mb)/den);
      v[2*i]=a; v[2*i+1]=b;
      o[lane+32*i]=pack_bf16(a,b);
    }
  }
}

#define RDELAY 400
#define BDELAY 0
constexpr int SM_QS=0;
constexpr int SM_VS=49152;
constexpr int SM_OS=131072;
constexpr int SM_O=SM_OS+43008;
constexpr int SM_RSUM=SM_O+3072;
constexpr int SM_RED=180224;
constexpr int SM_KX=SM_RED+16384;
constexpr int SM_VX=SM_KX+4096;
constexpr int SM_SCX=SM_VX+12288;
constexpr int SM_VMX=SM_SCX+6144;
constexpr int SM_VRED=SM_VMX+3072;
constexpr int SM_MB=SM_VRED+8192+1024;
constexpr int SM_TOTAL=SM_MB+64;
static_assert(SM_MB-SM_RED>=49152,"staging");
static_assert(SM_TOTAL<=232448,"smem");

#define TS(i)
#define PC(i) (void)np
#define TW(i)
#define TF(i)

__device__ __forceinline__ void cp_commit(){ asm volatile("cp.async.commit_group;":::"memory"); }
template<int N> __device__ __forceinline__ void cp_wait(){ asm volatile("cp.async.wait_group %0;"::"n"(N):"memory"); }
__device__ __forceinline__ void tma2d(uint32_t dst,const CUtensorMap* tm,int c0,int c1,uint32_t mb){
  asm volatile("cp.async.bulk.tensor.2d.shared::cluster.global.mbarrier::complete_tx::bytes [%0], [%1, {%3, %4}], [%2];"::"r"(dst),"l"(tm),"r"(mb),"r"(c0),"r"(c1):"memory"); }
__device__ __forceinline__ void tma2d_pf(const CUtensorMap* tm,int c0,int c1){
  asm volatile("cp.async.bulk.prefetch.tensor.2d.L2.global [%0, {%1, %2}];"::"l"(tm),"r"(c0),"r"(c1):"memory"); }
__global__ void __launch_bounds__(256,1) k_rec(const __grid_constant__ CUtensorMap tmK,const __grid_constant__ CUtensorMap tmV,const bf16* __restrict__ Wq,const bf16* __restrict__ Wk,const bf16* __restrict__ Wv,const bf16* __restrict__ Wo){
  extern __shared__ __align__(1024) uint8_t sm[];
  const int tid=threadIdx.x, warp=__shfl_sync(~0u,tid>>5,0), lane=tid&31, g=lane>>2, t=lane&3;
  const int b=blockIdx.x, h=b/3, c=b-3*h;
  const uint32_t sb=(uint32_t)__cvta_generic_to_shared(sm);
  const int kq=warp&3, mg=warp>>2;
  const uint32_t s16=sb+lane*16, s8=sb+lane*8;
  const uint32_t qs=s16+SM_QS+warp*6144, vs=s16+SM_VS+kq*20480, os=s16+SM_OS+warp*6144;
  const uint32_t XS=sb+SM_MB, KVB=sb+SM_MB+8, XV=sb+SM_MB+16;
  GT(0);
  asm volatile("griddepcontrol.launch_dependents;");
  if(tid==0){
    mbar_init(XS,5); mbar_init(KVB,1); mbar_init(XV,5);
    asm volatile("fence.mbarrier_init.release.cluster;":::"memory");
    mbar_expect(XS,4096); mbar_expect(XV,2048);
  }
  const int ntile=c==0?14:13, tile0=c==0?0:(1+13*c);
  uint32_t wr[7][4][4];
  uint32_t wo[6][2][4];
  auto ldW=[&](int p,uint32_t stg){
    #pragma unroll
    for(int i=0;i<12;i++){
      const int idx=tid+256*i, row=idx>>3, ch=idx&7, m=row>>7, f=160*((row>>5)&3)+32*p+(row&31);
      const bf16* src=(m==0?Wq:(m==1?Wk:Wv))+(size_t)f*HD+h*DH+64*c+ch*8;
      const int sw=(row>>2)&7;
      cp16(stg+row*128+((ch^sw)<<4),src);
    }
    cp_commit();
  };
  auto ldO=[&](int r,uint32_t stg){
    for(int idx=tid;idx<96*28;idx+=256){
      const int row=idx/28, ch=idx-row*28;
      if(ch<2*ntile) cp16(stg+row*464+ch*16,Wo+(size_t)(h*DH+96*r+row)*D+tile0*16+ch*8);
    }
    cp_commit();
  };
  ldW(0,sb+SM_RED);
  #pragma unroll
  for(int p=0;p<5;p++){
    const uint32_t stg=sb+((p&1)?SM_OS:SM_RED), nstg=sb+((p&1)?SM_RED:SM_OS);
    if(p<4) ldW(p+1,nstg); else ldO(0,nstg);
    cp_wait<1>(); __syncthreads();
    #pragma unroll
    for(int e=0;e<2;e++){
      const int k=2*p+e;
      const int fo=16*((lane>>2)&1)+4*((lane>>1)&1)+2*e+(lane>>4)+8*(lane&1);
      const int sw=(fo>>2)&7;
      #pragma unroll
      for(int j=0;j<4;j++){
        const uint32_t a=stg+((mg*4+kq)*32+fo)*128+(((2*j+((lane>>3)&1))^sw)<<4);
        if(k>=2&&k<9) ldsm4t(wr[(k>=2&&k<9)?k-2:0][j],a);
        else { uint32_t r[4]; ldsm4t(r,a); sts4r(qs+((k<2?k*4:8)+j)*512,r); }
        if(mg){ uint32_t r[4]; ldsm4t(r,a+16384); sts4r(vs+(k*4+j)*512,r); }
      }
    }
    __syncthreads();
  }
  #pragma unroll
  for(int r=0;r<2;r++){
    const uint32_t stg=sb+(r?SM_RED:SM_OS);
    if(r==0){ ldO(1,sb+SM_RED); cp_wait<1>(); } else cp_wait<0>();
    __syncthreads();
    #pragma unroll
    for(int kk=0;kk<6;kk++){
      #pragma unroll
      for(int i=0;i<2;i++){
        int tl=2*warp+i; if(tl>=ntile) tl=0;
        const uint32_t a=stg+(16*kk+(lane&7)+(lane>>4)*8)*464+(2*tl+((lane>>3)&1))*16;
        if(r==0) ldsm4t(wo[kk][i],a);
        else { uint32_t rr[4]; ldsm4t(rr,a); if(warp<7) sts4r(os+(kk*2+i)*512,rr); }
      }
    }
    __syncthreads();
  }
  auto kv_issue=[&](int sn){
    if(lane==0){
      mbar_expect(KVB,32*512);
      tma2d(sb+SM_KX,&tmK,h*DH+64*c,sn*32,KVB);
      #pragma unroll
      for(int i=0;i<3;i++) tma2d(sb+SM_VX+i*4096,&tmV,h*DH+64*i,sn*32,KVB);
    }
    __syncwarp();
  };
  auto kv_chk=[&](int rbk){
    if(lane==0){ int gd=0; while(ld_acq(g_cnt+C_KV+rbk)<96){ if(++gd>GUARD){ g_err=7; break; } } fence_async_all(); }
    __syncwarp();
  };
  auto kv_pf=[&](int sn){
    if(lane==0){ tma2d_pf(&tmK,h*DH+64*c,sn*32); tma2d_pf(&tmV,h*DH+64*c,sn*32); }
    __syncwarp();
  };
  if(warp==7){ fence_async(); kv_chk(0); kv_issue(0); kv_pf(1); kv_pf(2); }
  cluster_sync();
  const bool isred=(b%6)<5; const int rline=(b/6)*5+(b%6);
  bool dead=false;
  const uint32_t qrd=sb+SM_RED+1024+((lane>>3)&1)*4096+(lane>>4)*128+(lane&7)*16+kq*256;
  uint32_t rsc[2];
  rsc[0]=mapa(sb,c==2?0:c+1); rsc[1]=mapa(sb,c==0?2:c-1);
  uint32_t buf[8][4];
  #pragma unroll
  for(int i=0;i<8;i++) lds4r(buf[i],qs+i*512);

  GT(1);
  #define MB0(k) (((k)&1)?mv[(k)>>1].z:mv[(k)>>1].x)
  #define MB1(k) (((k)&1)?mv[(k)>>1].w:mv[(k)>>1].y)
  #pragma unroll 1
  for(int s=0;s<NSEG;s++){
    const uint32_t tg=1+(s&1);
    uint4 mv[5];
    {
      const uint32_t* src=(const uint32_t*)((const char*)g_mem+(uint32_t)((s*RCOPY+(b%RCOPY))*10240+(kq*20+t)*128+g*16));
      auto okf=[&](const uint4& v){ return v.x!=SENT&&v.y!=SENT&&v.z!=SENT&&v.w!=SENT; };
      const uint32_t mx=s16+SM_RED+kq*4096;
      if(mg==0){
        int np=poll1<3>(mv,[&](int i){ return ldg_rlx4(src+i*128); },okf,dead,1);
        TW(0); PC(0);
        #pragma unroll
        for(int p=0;p<3;p++) sts4(mx+(4+p)*512,mv[p]);
        bar_sync(8+kq,64);
        mv[3]=lds4(mx); mv[4]=lds4(mx+512);
      } else {
        int np=poll1<2>(mv+3,[&](int i){ return ldg_rlx4(src+(3+i)*128); },okf,dead,1);
        TW(0); PC(0);
        sts4(mx,mv[3]); sts4(mx+512,mv[4]);
        bar_sync(8+kq,64);
        #pragma unroll
        for(int p=0;p<3;p++) mv[p]=lds4(mx+(4+p)*512);
      }
    }
    TS(0); TF(0);
    float acc[4][4]; uint32_t kb[8];
    #pragma unroll
    for(int i=0;i<4;i++){ acc[i][0]=acc[i][1]=acc[i][2]=acc[i][3]=0.f; }
    #pragma unroll
    for(int k=0;k<10;k++){
      #pragma unroll
      for(int j=0;j<4;j++){
        if(k<2) mma16816(acc[j],buf[(k&1)*4+j],MB0(k),MB1(k));
        else if(k<9) mma16816(acc[j],wr[(k>=2&&k<9)?k-2:0][j],MB0(k),MB1(k));
        else mma16816(acc[j],buf[j],MB0(k),MB1(k));
        if(k==2) lds4r(buf[j],qs+(8+j)*512);
        if(k==4&&mg) lds4r(buf[4+j],vs+j*512);
      }
      if(k==5&&!mg){
        { int gd=0; while(!mbar_try(KVB,s&1)){ if(dead) break; if(++gd>GUARD){ dead=true; g_err=6; } } }
        const uint32_t ka=sb+SM_KX+(8*kq+(lane&7))*128+((((lane>>3)^(2*kq))^(lane&7))<<4);
        ldsm4(kb,ka); ldsm4(kb+4,ka^64);
      }
    }
    TF(1);
    const uint32_t exo=(uint32_t)(((s*H+h)*12+4*c+kq)*256+lane*8);
    if(mg){
      {
        const uint32_t ra=s16+SM_RED+kq*4096+2048;
        #pragma unroll
        for(int i=0;i<4;i++) sts4f(ra+i*512,acc[i]);
      }
      bar_arrive(1,256);
      #pragma unroll
      for(int j=0;j<4;j++) lds4r(buf[j],vs+(4+j)*512);
      #pragma unroll
      for(int i=0;i<4;i++){ acc[i][0]=acc[i][1]=acc[i][2]=acc[i][3]=0.f; }
      #pragma unroll
      for(int u=0;u<40;u++){
        mma16816(acc[u&3],buf[(u+4)&7],MB0(u>>2),MB1(u>>2));
        if(u<8||(u>=16&&u+8<40)) lds4r(buf[(u+4)&7],vs+(u+8)*512);
        if(u==15){
          bar_sync(6,256);
          #pragma unroll
          for(int v=8;v<16;v++) lds4r(buf[(v+4)&7],vs+(v+8)*512);
        }
      }
      TF(2);
      const uint32_t ra=s16+SM_VRED;
      #pragma unroll
      for(int i=0;i<4;i++) sts4f(ra+kq*2048+i*512,acc[i]);
      bar_sync(3,128);
      float4 a=lds4f(ra+kq*512), c1=lds4f(ra+kq*512+2048), d2=lds4f(ra+kq*512+4096), e2=lds4f(ra+kq*512+6144);
      const uint32_t p0=pack_bf16((a.x+c1.x)+(d2.x+e2.x),(a.y+c1.y)+(d2.y+e2.y)), p1=pack_bf16((a.z+c1.z)+(d2.z+e2.z),(a.w+c1.w)+(d2.w+e2.w));
      const uint32_t off=SM_VMX+(4*c+kq)*256+lane*8;
      #pragma unroll
      for(int r=0;r<2;r++) st_async2(rsc[r]+off,p0,p1,rsc[r]+SM_MB+16);
      sts2(sb+off,p0,p1); __syncwarp(); if(lane==0) mbar_arrive(XV);
      TF(5);
      if(warp==7){ fence_gpu(); if(lane==0) stg_rlx1(g_flag+b*32,s); if((s&3)==3&&s+1<NSEG) kv_chk((s+1)>>2); }
      stg_rlx2((uint32_t*)((char*)g_vmf+exo),p0,p1);
      TF(7);
      if(warp<7){
        #pragma unroll
        for(int i=0;i<8;i++) lds4r(buf[i],os+i*512);
      }
    } else {
      {
        const uint32_t qa=s16+SM_RED+kq*4096+1024;
        #pragma unroll
        for(int i=0;i<2;i++) stsm4(qa+i*512,pack_bf16(acc[2*i][0],acc[2*i][1]),pack_bf16(acc[2*i][2],acc[2*i][3]),pack_bf16(acc[2*i+1][0],acc[2*i+1][1]),pack_bf16(acc[2*i+1][2],acc[2*i+1][3]));
      }
      TF(2);
      bar_sync(1,256);
      TS(1); TF(3);
      {
        const uint32_t ra=s16+SM_RED+2048+kq*512;
        float4 a3=lds4f(ra), c3=lds4f(ra+4096), d3=lds4f(ra+8192), e3=lds4f(ra+12288);
        uint32_t q[4][2][4];
        #pragma unroll
        for(int i=0;i<4;i++){ ldsm4t(q[i][0],qrd^(i*256)); ldsm4t(q[i][1],(qrd^(i*256))+8192); }
        bar_arrive(6,256);
        const uint32_t p2=pack_bf16((a3.x+c3.x)+(d3.x+e3.x),(a3.y+c3.y)+(d3.y+e3.y)), p3=pack_bf16((a3.z+c3.z)+(d3.z+e3.z),(a3.w+c3.w)+(d3.w+e3.w));
        const uint32_t f2=movm(p2), f3=movm(p3);
        TF(4);
        float sc[6][4];
        #pragma unroll
        for(int i=0;i<6;i++){ sc[i][0]=sc[i][1]=sc[i][2]=sc[i][3]=0.f; }
        #pragma unroll
        for(int i=0;i<4;i++)
          #pragma unroll
          for(int jp=0;jp<2;jp++){
            mma16816(sc[(i&1)*2+jp],q[i][jp],kb[2*i],kb[2*i+1]);
            if(i==1) mma16816(sc[4+jp],q[0][jp],f2,f3);
          }
        const uint32_t w0=__float_as_uint(((sc[0][0]+sc[0][2])+(sc[1][0]+sc[1][2]))+((sc[2][0]+sc[2][2])+(sc[3][0]+sc[3][2]))), w1=__float_as_uint(((sc[0][1]+sc[0][3])+(sc[1][1]+sc[1][3]))+((sc[2][1]+sc[2][3])+(sc[3][1]+sc[3][3])));
        const uint32_t w2=__float_as_uint((sc[4][0]+sc[4][2])+(sc[5][0]+sc[5][2])), w3=__float_as_uint((sc[4][1]+sc[4][3])+(sc[5][1]+sc[5][3]));
        const uint32_t off=SM_SCX+(c*4+kq)*512+lane*16;
        #pragma unroll
        for(int r=0;r<2;r++) st_async4(rsc[r]+off,w0,w1,w2,w3,rsc[r]+SM_MB);
        sts4(sb+off,make_uint4(w0,w1,w2,w3)); __syncwarp(); if(lane==0) mbar_arrive(XS);
        TS(2); TF(5);
        stg_rlx2((uint32_t*)((char*)g_kmf+exo),f2,f3);
      }
      uint32_t va[3][2][4];
      #pragma unroll
      for(int i=0;i<3;i++){
        const int T=3*kq+i;
        const uint32_t vaddr=sb+SM_VX+(T>>2)*4096+((lane>>4)*8+(lane&7))*128+(((2*(T&3)+((lane>>3)&1))^(lane&7))<<4);
        ldsm4t(va[i][0],vaddr); ldsm4t(va[i][1],vaddr+2048);
      }
      TF(6);
      { int gd=0; while(!mbar_try(XS,s&1)){ if(dead) break; if(++gd>GUARD){ dead=true; g_err=2; } } }
      TS(3); TF(7);
      float sv[10];
      {
        float4 u[12];
        #pragma unroll
        for(int n=0;n<12;n++) u[n]=lds4f(s16+SM_SCX+n*512);
        uint32_t r[5];
        #pragma unroll
        for(int n=0;n<4;n++) r[n+1]=pack_bf16((u[n].x+u[4+n].x)+u[8+n].x,(u[n].y+u[4+n].y)+u[8+n].y);
        r[0]=pack_bf16((((u[0].z+u[1].z)+(u[2].z+u[3].z))+((u[4].z+u[5].z)+(u[6].z+u[7].z)))+((u[8].z+u[9].z)+(u[10].z+u[11].z)),
                       (((u[0].w+u[1].w)+(u[2].w+u[3].w))+((u[4].w+u[5].w)+(u[6].w+u[7].w)))+((u[8].w+u[9].w)+(u[10].w+u[11].w)));
        #pragma unroll
        for(int n=0;n<5;n++){
          const uint32_t w=pack_bf16(__uint_as_float(r[n]<<16)*0.07216878364870322f,__uint_as_float(r[n]&0xffff0000u)*0.07216878364870322f);
          sv[2*n]=__uint_as_float(w<<16); sv[2*n+1]=__uint_as_float(w&0xffff0000u);
        }
      }
      TF(8);
      float mx=fmaxf(fmaxf(fmaxf(sv[0],sv[1]),fmaxf(sv[2],sv[3])),fmaxf(fmaxf(fmaxf(sv[4],sv[5]),fmaxf(sv[6],sv[7])),fmaxf(sv[8],sv[9])));
      mx=fmaxf(mx,__shfl_xor_sync(~0u,mx,1)); mx=fmaxf(mx,__shfl_xor_sync(~0u,mx,2));
      mx*=-1.4426950408889634f;
      #pragma unroll
      for(int i=0;i<10;i++) sv[i]=ex2(fmaf(sv[i],1.4426950408889634f,mx));
      float sum=((sv[0]+sv[1])+(sv[2]+sv[3]))+(((sv[4]+sv[5])+(sv[6]+sv[7]))+(sv[8]+sv[9]));
      sum+=__shfl_xor_sync(~0u,sum,1); sum+=__shfl_xor_sync(~0u,sum,2);
      const float inv=rcp(sum);
      uint32_t pp[5];
      #pragma unroll
      for(int n=0;n<5;n++) pp[n]=pack_bf16(sv[2*n]*inv,sv[2*n+1]*inv);
      TF(9);
      float o[3][4];
      #pragma unroll
      for(int i=0;i<3;i++){ o[i][0]=o[i][1]=o[i][2]=o[i][3]=0.f; mma16816(o[i],va[i][0],pp[1],pp[2]); }
      { int gd=0; while(!mbar_try(XV,s&1)){ if(dead) break; if(++gd>GUARD){ dead=true; g_err=3; } } }
      uint2 vm[3];
      #pragma unroll
      for(int i=0;i<3;i++) vm[i]=lds2(s8+SM_VMX+(3*kq+i)*256);
      #pragma unroll
      for(int i=0;i<8;i++) lds4r(buf[i],os+i*512);
      #pragma unroll
      for(int i=0;i<3;i++) mma16816(o[i],va[i][1],pp[3],pp[4]);
      #pragma unroll
      for(int i=0;i<3;i++) mma1688(o[i],vm[i].x,vm[i].y,pp[0]);
      stsm4(s16+SM_O+kq*768,pack_bf16(o[0][0],o[0][1]),pack_bf16(o[0][2],o[0][3]),pack_bf16(o[1][0],o[1][1]),pack_bf16(o[1][2],o[1][3]));
      stsm2(s16+SM_O+kq*768+512,pack_bf16(o[2][0],o[2][1]),pack_bf16(o[2][2],o[2][3]));
    }
    TF(10);
    if(warp<7){
      if(!mg) bar_arrive(7,160);
      bar_sync(4,224);
      uint32_t ob[6][4];
      ldsm4t(ob[3],s16+SM_O+3*512);
      #pragma unroll
      for(int i=0;i<6;i++) if(i!=3) ldsm4t(ob[i],s16+SM_O+i*512);
      TF(11);
      float ca[2][2][4];
      #pragma unroll
      for(int i=0;i<2;i++)
        #pragma unroll
        for(int j=0;j<2;j++){ ca[i][j][0]=ca[i][j][1]=ca[i][j][2]=ca[i][j][3]=0.f; }
      #pragma unroll
      for(int x=0;x<12;x++){
        const int ks=x<2?6+x:(x<8?x-2:x);
        const uint32_t b0=ob[ks>>1][(ks&1)*2], b1=ob[ks>>1][(ks&1)*2+1];
        #pragma unroll
        for(int i=0;i<2;i++){
          if(ks<6) mma16816(ca[i][ks&1],wo[ks<6?ks:0][i],b0,b1);
          else mma16816(ca[i][ks&1],buf[((ks-6)*2+i)&7],b0,b1);
          if(x==3||x==4) lds4r(buf[(x-3)*2+i],os+(8+(x-3)*2+i)*512);
        }
      }
      TF(12);
      uint32_t* dst=(uint32_t*)((char*)g_part+(uint32_t)(((tile0+2*warp)*32+h)*512+lane*16));
      #pragma unroll
      for(int i=0;i<2;i++){
        if(i==0||2*warp+1<ntile)
          stg_rlx4(dst+i*4096,(__float_as_uint(ca[i][0][0]+ca[i][1][0])&~3u)|tg,(__float_as_uint(ca[i][0][1]+ca[i][1][1])&~3u)|tg,
                              (__float_as_uint(ca[i][0][2]+ca[i][1][2])&~3u)|tg,(__float_as_uint(ca[i][0][3]+ca[i][1][3])&~3u)|tg);
      }
    }
    TW(1);
    TS(4); TF(13);
    #pragma unroll
    for(int i=0;i<8;i++) lds4r(buf[i],qs+i*512);
    if(isred){
      const uint32_t* src=(const uint32_t*)((char*)g_part+(uint32_t)(((rline>>1)*32+4*warp+(lane>>4))*512+(rline&1)*256+(lane&15)*16));
      uint32_t* mdst=g_mem+(size_t)((s+1)*RCOPY)*2560+rline*32+lane;
      uint4 v[2]; float f[4];
      { uint32_t t0,t1; asm volatile("mov.u32 %0, %%clock;":"=r"(t0)); do{ asm volatile("mov.u32 %0, %%clock;":"=r"(t1)); }while(t1-t0<RDELAY); }
      auto okr=[&](const uint4& v){ return (v.x&v.y&v.z&v.w&tg)!=0; };
      int np=poll1<2>(v,[&](int i){ return ldg_rlx4(src+i*256); },okr,dead,4);
      f[0]=__uint_as_float(v[0].x)+__uint_as_float(v[1].x); f[1]=__uint_as_float(v[0].y)+__uint_as_float(v[1].y); f[2]=__uint_as_float(v[0].z)+__uint_as_float(v[1].z); f[3]=__uint_as_float(v[0].w)+__uint_as_float(v[1].w);
      TW(2); TF(14); PC(1);
      #pragma unroll
      for(int i=0;i<4;i++) f[i]+=__shfl_xor_sync(~0u,f[i],16);
      if(lane<16) sts4f(s16+SM_RSUM+warp*256,f);
      if(warp==0){
        bar_sync(5,256);
        TS(5);
        const float* rp=(const float*)(sm+SM_RSUM)+(lane&3)*16+(lane>>3)*4+((lane>>2)&1);
        float a0=((rp[0]+rp[64])+(rp[128]+rp[192]))+((rp[256]+rp[320])+(rp[384]+rp[448]));
        float a1=((rp[2]+rp[66])+(rp[130]+rp[194]))+((rp[258]+rp[322])+(rp[386]+rp[450]));
        uint32_t o=pack_bf16(a0,a1); if(o==SENT) o=0x7FFF7FFFu;
        #pragma unroll
        for(int cc=0;cc<RCOPY;cc++) stg_rlx1(mdst+cc*2560,o);
        TS(6); TW(3);
      } else bar_arrive(5,256);
    }
    TF(15);
    if(warp==7){
      bar_sync(7,160);
      if(lane==0){ mbar_expect(XS,4096); mbar_expect(XV,2048); }
      if(s+1<NSEG) kv_issue(s+1);
      if(s+3<NSEG) kv_pf(s+3);
      if(isred&&lane<RCOPY&&s+3<=NSEG) asm volatile("prefetch.global.L2 [%0];"::"l"(g_mem+(size_t)((s+3)*RCOPY+lane)*2560+rline*32));
    }
  }
  if(warp==7){ fence_gpu(); if(lane==0) stg_rlx1(g_flag+b*32,NSEG); }
  GT(2);
  cluster_sync();
}

enum { M_XN=0,M_Y,M_H,M_OX,M_K,M_V,M_GATE,M_WQ,M_WK,M_WV,M_W1,M_W2,M_WO,M_NUM };
struct WParams { CUtensorMap m[M_NUM]; const bf16* x; const bf16* b1; const bf16* b2; bf16* out; };
enum { T_RED=0,T_OP=1,T_QA=2,T_M2=3,T_M1=4,T_KV=5,T_END=6 };
#define KVUP 768
#define TRIG 6
constexpr int NRB=16, NSPL=8, NREDI=20;
constexpr int STG=49152, NST=4;
constexpr int W_STAGING=NST*STG;
constexpr int W_BAR=W_STAGING+32768;
constexpr int W_TOTAL=W_BAR+256;
#define WGUARD 2000000

__device__ __forceinline__ void wg_arrive(){ asm volatile("wgmma.fence.sync.aligned;":::"memory"); }
__device__ __forceinline__ void wg_commit(){ asm volatile("wgmma.commit_group.sync.aligned;":::"memory"); }
template<int N> __device__ __forceinline__ void wg_wait(){ asm volatile("wgmma.wait_group.sync.aligned %0;"::"n"(N):"memory"); }
__device__ __forceinline__ void mbar_wait(uint32_t a,uint32_t par){ int gd=0; while(!mbar_try(a,par)){ if(++gd>WGUARD){ g_err=20; break; } } }
__device__ __forceinline__ uint32_t ld_rlx(const uint32_t* p){ uint32_t v; asm volatile("ld.relaxed.gpu.global.u32 %0, [%1];":"=r"(v):"l"(p):"memory"); return v; }
__device__ __forceinline__ uint2 ld_rlx2(const uint2* p){ uint2 v; asm volatile("ld.relaxed.gpu.global.v2.u32 {%0,%1}, [%2];":"=r"(v.x),"=r"(v.y):"l"(p):"memory"); return v; }
__device__ __forceinline__ float4 ld_rlx4f(const float4* p){ float4 v; asm volatile("ld.relaxed.gpu.global.v4.f32 {%0,%1,%2,%3}, [%4];":"=f"(v.x),"=f"(v.y),"=f"(v.z),"=f"(v.w):"l"(p):"memory"); return v; }
__device__ __forceinline__ void red_rel(uint32_t* p){ asm volatile("red.release.gpu.global.add.u32 [%0], 1;"::"l"(p):"memory"); }
__device__ __forceinline__ void tma_st(const CUtensorMap* tm,uint32_t src,int c0,int c1){
  asm volatile("cp.async.bulk.tensor.2d.global.shared::cta.bulk_group [%0, {%2, %3}], [%1];"::"l"(tm),"r"(src),"r"(c0),"r"(c1):"memory"); }
__device__ __forceinline__ void bulk_commit(){ asm volatile("cp.async.bulk.commit_group;":::"memory"); }
__device__ __forceinline__ void bulk_wait_rd(){ asm volatile("cp.async.bulk.wait_group.read 0;":::"memory"); }
__device__ __forceinline__ void bulk_wait(){ asm volatile("cp.async.bulk.wait_group 0;":::"memory"); }

__device__ __forceinline__ void mbar_arrive_cl(uint32_t a){ asm volatile("mbarrier.arrive.shared::cluster.b64 _, [%0];"::"r"(a):"memory"); }
__device__ __forceinline__ void tma2dm(uint32_t dst,const CUtensorMap* tm,int c0,int c1,uint32_t mb){
  asm volatile("cp.async.bulk.tensor.2d.shared::cluster.global.mbarrier::complete_tx::bytes.multicast::cluster [%0], [%1, {%3, %4}], [%2], %5;"::"r"(dst),"l"(tm),"r"(mb),"r"(c0),"r"(c1),"h"((uint16_t)3):"memory"); }
template<int N,int CL> __device__ __forceinline__ void mainloop(float* acc,int nkb,uint32_t sb,int wg,int lane,uint32_t& st,uint32_t& ph){
  const uint32_t eb=CL?mapa(sb+W_BAR+32,lane&1):sb+W_BAR+32;
  uint32_t pst=0;
  #pragma unroll 1
  for(int kb=0;kb<nkb;kb++){
    mbar_wait(sb+W_BAR+st*8,ph);
    const uint32_t a=sb+st*STG+wg*8192, bq=sb+st*STG+16384;
    const uint64_t da=(uint64_t)((a>>4)&0x3fff)|(1ull<<16)|(64ull<<32)|(1ull<<62);
    const uint64_t db=(uint64_t)((bq>>4)&0x3fff)|(512ull<<16)|(64ull<<32)|(1ull<<62);
    wg_arrive();
    #pragma unroll
    for(int k=0;k<4;k++) wgmma<N>(acc,da+2*k,db+128*k,kb|k);
    wg_commit();
    if(kb>0){ wg_wait<1>(); if(CL){ if(lane<2) mbar_arrive_cl(eb+pst*8); } else if(lane==0) mbar_arrive(eb+pst*8); }
    pst=st; if(++st==NST){ st=0; ph^=1; }
  }
  wg_wait<0>();
  if(CL){ if(lane<2) mbar_arrive_cl(eb+pst*8); } else if(lane==0) mbar_arrive(eb+pst*8);
}
struct Epi { uint32_t sb; int wg,wq,lane; bool el; uint32_t sph; volatile int* cmd; };
__device__ __forceinline__ void epi_cmd(Epi& e,int map,int col,int row,int nbox,int cnt){
  if(e.el){ e.cmd[0]=map; e.cmd[1]=col; e.cmd[2]=row; e.cmd[3]=nbox; e.cmd[4]=cnt; }
  bar_arrive(4+e.wg,160);
}
__device__ __forceinline__ void epi_acquire(Epi& e){ mbar_wait(e.sb+W_BAR+96+e.wg*8,e.sph); e.sph^=1; }
__device__ __forceinline__ uint32_t act2(uint32_t u,uint32_t bb,float c1,float c3){
  uint32_t s; asm("add.rn.bf16x2 %0, %1, %2;":"=r"(s):"r"(u),"r"(bb));
  float r[2]={__uint_as_float(s<<16), __uint_as_float(s&0xffff0000u)};
  #pragma unroll
  for(int i=0;i<2;i++){
    const float z=r[i]*fmaf(r[i]*r[i],c3,c1);
    r[i]=r[i]*rcp(1.f+ex2(z));
  }
  return pack_bf16(r[0],r[1]);
}
template<int NB2> __device__ __forceinline__ void store_round(Epi& e,const float* acc,int map,int col0,int row0,int cnt,int act,const uint4* bb){
  const uint32_t stg=e.sb+W_STAGING+e.wg*16384;
  const int r=16*e.wq+(e.lane&7)+((e.lane>>3)&1)*8;
  const uint32_t ra=stg+r*128; const int sw=e.lane&7, hi=e.lane>>4;
  uint32_t pk[NB2*16];
  #pragma unroll
  for(int j=0;j<NB2*16;j++) pk[j]=pack_bf16(acc[2*j],acc[2*j+1]);
  epi_acquire(e);
  #pragma unroll
  for(int j=0;j<NB2*4;j++) stsm4(ra+(j>>2)*8192+((((2*j+hi)&7)^sw)<<4),pk[4*j],pk[4*j+1],pk[4*j+2],pk[4*j+3]);
  if(act){
    __syncwarp();
    const float c1=act==1?-2.302208198144325f:-1.4426950408889634f, c3=act==1?-0.10294323958f:0.f;
    #pragma unroll 1
    for(int i=0;i<2;i++){
      uint4 u[2][2]; uint32_t a[2];
      #pragma unroll
      for(int q=0;q<2;q++){
        const int rr=16*e.wq+8*i+4*q+(e.lane>>3);
        a[q]=stg+rr*128+(((e.lane&7)^(rr&7))<<4);
        u[q][0]=lds4(a[q]); u[q][1]=lds4(a[q]+8192);
      }
      #pragma unroll
      for(int q=0;q<2;q++)
        #pragma unroll
        for(int bx=0;bx<2;bx++){
          uint4& v=u[q][bx];
          v.x=act2(v.x,bb[bx].x,c1,c3); v.y=act2(v.y,bb[bx].y,c1,c3); v.z=act2(v.z,bb[bx].z,c1,c3); v.w=act2(v.w,bb[bx].w,c1,c3);
          sts4(a[q]+bx*8192,v);
        }
    }
  }
  fence_async();
  epi_cmd(e,map,col0,row0,NB2,cnt);
}
template<int N> __device__ __forceinline__ void store_part(const float* acc,float4* dst){
  #pragma unroll
  for(int n=0;n<N/8;n++) __stcg(dst+(n>>4)*4096+(n&15)*128,make_float4(acc[4*n],acc[4*n+1],acc[4*n+2],acc[4*n+3]));
}

__device__ __forceinline__ bool item_ready(int c,int idx){
  if(c==T_RED){ const int rbk=idx/NREDI; return ld_acq(g_cnt+C_OP+rbk)>=2*3*NSPL && ld_acq(g_cnt+C_M2+rbk)>=6; }
  if(c==T_OP){ const int rbk=idx/(3*NSPL), sp=(idx-rbk*3*NSPL)/3; return ld_acq(g_cnt+C_QA+rbk*NSPL+sp)>=8; }
  if(c==T_QA){ const uint32_t need=4*(idx>>5)+4; const uint32_t* f=g_flag+(idx&31)*96; return ld_acq(f)>=need && ld_acq(f+32)>=need && ld_acq(f+64)>=need; }
  if(c==T_M2){ return ld_acq(g_cnt+C_M1+idx/3)>=12; }
  return true;
}

template<int MODE>
__global__ void __launch_bounds__(384,1) k_work(const __grid_constant__ WParams P){
  extern __shared__ __align__(1024) uint8_t sm[];
  const uint32_t sb=(uint32_t)__cvta_generic_to_shared(sm);
  const int tid=threadIdx.x, warp=__shfl_sync(~0u,tid>>5,0), lane=tid&31;
  const uint32_t FULL=sb+W_BAR, EMPTY=sb+W_BAR+32, IFULL=sb+W_BAR+64, IEMPTY=sb+W_BAR+80, REQ=sb+W_BAR+112;
  volatile int* idesc=(volatile int*)(sm+W_BAR+128);
  if(tid==0){
    for(int i=0;i<NST;i++){ mbar_init(FULL+i*8,1); mbar_init(EMPTY+i*8,MODE?8:16); }
    for(int i=0;i<2;i++){ mbar_init(IFULL+i*8,1); mbar_init(IEMPTY+i*8,9); mbar_init(sb+W_BAR+96+i*8,1); }
    mbar_init(REQ,1);
    asm volatile("fence.mbarrier_init.release.cluster;":::"memory");
  }
  __syncthreads();
  if(MODE==0){ cluster_sync(); asm volatile("griddepcontrol.wait;":::"memory"); asm volatile("griddepcontrol.launch_dependents;"); }
  if(warp>=8){
    asm volatile("setmaxnreg.dec.sync.aligned.u32 40;");
    if(warp==11){
      uint32_t it=0;
      int held=-1; int guard=0;
      const int ncls=lane==T_RED?NRB*NREDI:(lane==T_OP?NRB*3*NSPL:(lane==T_QA?NRB*32:(lane==T_M2?NRB*3:(lane==T_M1?NRB*6:(lane==T_KV?NRB*48-KVUP:0)))));
      int sidx=blockIdx.x;
      while(true){
        int type, idx;
        if(it) mbar_wait(REQ,(it&1)^1);
        if(MODE==0){ if(sidx<KVUP){ type=T_KV; idx=sidx; sidx+=gridDim.x; } else { type=T_END; idx=0; } }
        else {
          while(true){
            int cand=held; bool rdy=false;
            if(lane<6){
              if(cand<0){ cand=(int)ld_rlx(g_cnt+C_NEXT+lane*32); if(cand>=ncls) cand=-1; }
              if(cand>=0) rdy=item_ready(lane,cand);
            }
            const uint32_t br=__ballot_sync(~0u,rdy), ba=__ballot_sync(~0u,cand>=0);
            if(!ba){ type=T_END; idx=0; break; }
            if(br){
              const int w=(br>>T_KV)? T_KV : ((br>>T_M2)? T_M2+__ffs(br>>T_M2)-1 : __ffs(br)-1); int got=-1;
              if(lane==w){
                if(held>=0){ got=held; held=-1; }
                else { int tk=(int)atomicAdd(g_cnt+C_NEXT+lane*32,1u); if(tk<ncls){ if(tk==cand||item_ready(lane,tk)) got=tk; else held=tk; } }
              }
              got=__shfl_sync(~0u,got,w);
              if(got>=0){ type=w; idx=got+(w==T_KV?KVUP:0); break; }
            } else {
              __nanosleep(100);
              if(++guard>WGUARD){ g_err=21; type=T_END; idx=0; break; }
            }
          }
        }
        __syncwarp();
        if(lane==0){
          const uint32_t sl=it&1;
          mbar_wait(IEMPTY+sl*8,((it>>1)&1)^1);
          idesc[sl*2]=type; idesc[sl*2+1]=idx;
          mbar_arrive(IFULL+sl*8);
        }
        __syncwarp();
        it++;
        if(type==T_END) break;
      }
    } else if(warp==8){
      if(lane==0){
        uint32_t st=0, ph=1;
        for(uint32_t it=0;;it++){
          const uint32_t sl=it&1;
          mbar_wait(IFULL+sl*8,(it>>1)&1);
          const int type=idesc[sl*2], idx=idesc[sl*2+1];
          mbar_arrive(IEMPTY+sl*8);
          if(type==T_END) break;
          if(type==T_RED){ mbar_arrive(REQ); continue; }
          int ma,mb,row0,col0,k0=0,nkb,nbox;
          if(MODE==0||type==T_KV){ const int pt=idx>>1, rp=pt/48, nt=pt-rp*48; ma=M_XN; mb=nt<24?M_WK:M_WV; row0=(2*rp+(idx&1))*128; col0=(nt<24?nt:nt-24)*256; nkb=10; nbox=4; }
          else if(type==T_M1){ const int rbk=idx/6, nt=idx-rbk*6; ma=M_Y; mb=M_W1; row0=rbk*128; col0=nt*256; nkb=10; nbox=4; }
          else if(type==T_M2){ const int rbk=idx/3, nt=idx-rbk*3; ma=M_H; mb=M_W2; row0=rbk*128; col0=nt*256; nkb=24; nbox=nt<2?4:2; }
          else if(type==T_QA){ ma=M_XN; mb=M_WQ; row0=(idx>>5)*128; col0=(idx&31)*192; nkb=10; nbox=3; }
          else { const int rbk=idx/(3*NSPL), r=idx-rbk*3*NSPL, sp=r/3, nt=r-sp*3; ma=M_OX; mb=M_WO; row0=rbk*128; col0=nt*256; k0=sp*(HD/NSPL); nkb=HD/NSPL/64; nbox=nt<2?4:2; }
          if(MODE) fence_async_all();
          const CUtensorMap* A=&P.m[ma]; const CUtensorMap* B=&P.m[mb];
          const int trig=nkb-(type==T_QA?TRIG-2:TRIG);
          for(int kb=0;kb<nkb;kb++){
            mbar_wait(EMPTY+st*8,ph);
            const uint32_t d=sb+st*STG, fb=FULL+st*8;
            mbar_expect(fb,16384+nbox*8192);
            const int kk=k0+kb*64;
            tma2d(d,A,kk,row0,fb); tma2d(d+8192,A,kk,row0+64,fb);
            if(MODE==0){ const int j=(idx&1)*2; tma2dm(d+16384+j*8192,B,col0+j*64,kk,fb); tma2dm(d+24576+j*8192,B,col0+j*64+64,kk,fb); }
            else for(int j=0;j<nbox;j++) tma2d(d+16384+j*8192,B,col0+j*64,kk,fb);
            if(kb==trig) mbar_arrive(REQ);
            if(++st==NST){ st=0; ph^=1; }
          }
          if(type==T_QA){
            for(int q=0;q<2;q++){
              mbar_wait(EMPTY+st*8,ph);
              const uint32_t d=sb+st*STG, fb=FULL+st*8;
              mbar_expect(fb,49152);
              for(int j=0;j<6;j++) tma2d(d+j*8192,&P.m[M_K+q],col0+(j%3)*64,row0+(j/3)*64,fb);
              if(++st==NST){ st=0; ph^=1; }
            }
          }
        }
      }
      __syncwarp();
    } else if(warp<11){
      const int wg=warp-9; volatile int* cmd=(volatile int*)(sm+W_BAR+160+wg*32);
      const uint32_t stg=sb+W_STAGING+wg*16384;
      while(true){
        bar_sync(4+wg,160);
        const int map=cmd[0], col=cmd[1], row=cmd[2], nbox=cmd[3], cnt=cmd[4];
        __syncwarp();
        if(map==-2) break;
        if(lane==0){
          if(map>=0){
            tma_st(&P.m[map],stg,col,row);
            if(nbox>1) tma_st(&P.m[map],stg+8192,col+64,row);
            bulk_commit();
            bulk_wait_rd();
          }
          mbar_arrive(sb+W_BAR+96+wg*8);
          if(cnt>=0){ if(map>=0){ bulk_wait(); fence_async_all(); } else fence_gpu(); red_rel(g_cnt+cnt); }
        }
        __syncwarp();
      }
      if(lane==0) bulk_wait();
    }
  } else {
    asm volatile("setmaxnreg.inc.sync.aligned.u32 232;");
    const int wg=warp>>2, wq=warp&3, g=lane>>2, t=lane&3;
    const bool el=(tid&127)==0;
    uint32_t st=0, ph=0;
    Epi E{sb,wg,wq,lane,el,1u,(volatile int*)(sm+W_BAR+160+wg*32)};
    float acc[128];
    #pragma unroll 1
    for(uint32_t it=0;;it++){
      const uint32_t sl=it&1;
      mbar_wait(IFULL+sl*8,(it>>1)&1);
      const int type=idesc[sl*2], idx=idesc[sl*2+1];
      __syncwarp();
      if(lane==0) mbar_arrive(IEMPTY+sl*8);
      if(type==T_END) break;
      if(MODE==0||type>=T_M2||type==T_OP){
        int rbk,nt,nkb=10,map,cnt=-1,act=0,sp=0; const bf16* bias=P.b1;
        if(MODE==0||type==T_KV){ const int pt=idx>>1, rp=pt/48; nt=pt-rp*48; rbk=2*rp+(idx&1); map=M_K; cnt=C_KV+rbk; if(nt>=24){ nt-=24; map=M_V; } }
        else if(type==T_M1){ rbk=idx/6; nt=idx-rbk*6; map=M_H; cnt=C_M1+rbk; act=1; }
        else if(type==T_M2){ rbk=idx/3; nt=idx-rbk*3; map=M_GATE; cnt=C_M2+rbk; act=2; bias=P.b2; nkb=24; }
        else { rbk=idx/(3*NSPL); const int r=idx-rbk*3*NSPL; sp=r/3; nt=r-sp*3; map=-1; cnt=C_OP+rbk; nkb=HD/NSPL/64; }
        const bool wide=MODE==0||type>=T_M1||nt<2;
        uint4 bb[4];
        if(MODE&&act){
          #pragma unroll
          for(int i=0;i<4;i++) if(i<2||wide) bb[i]=__ldg((const uint4*)(bias+nt*256+i*64+(lane&7)*8));
        }
        if(wide) mainloop<256,MODE==0>(acc,nkb,sb,wg,lane,st,ph); else mainloop<128,0>(acc,nkb,sb,wg,lane,st,ph);
        if(MODE&&map<0){
          float4* dst=g_opp+(size_t)(((rbk*NSPL+sp)*5+2*nt)*2+wg)*2048+(tid&127);
          store_part<128>(acc,dst);
          if(wide) store_part<128>(acc+64,dst+4096);
          epi_acquire(E);
          epi_cmd(E,-1,0,0,0,cnt);
        } else {
          store_round<2>(E,acc,map,nt*256,rbk*128+wg*64,wide?-1:cnt,act,bb);
          if(wide) store_round<2>(E,acc+64,map,nt*256+128,rbk*128+wg*64,cnt,act,bb+2);
        }
      } else if(type==T_RED){
        const int rbk=idx/NREDI, r=idx-rbk*NREDI, cb=r>>2, jq=r&3;
        const float4* src=g_opp+(size_t)((rbk*NSPL*5+cb)*2+wg)*2048+jq*512+(tid&127);
        float4 v[4][NSPL];
        #pragma unroll
        for(int j=0;j<4;j++)
          #pragma unroll
          for(int s=0;s<NSPL;s++) v[j][s]=ld_rlx4f(src+(size_t)s*5*4096+j*128);
        const int row=rbk*128+wg*64+wq*16+g;
        uint32_t gx[4][2], xx[4][2];
        #pragma unroll
        for(int j=0;j<4;j++)
          #pragma unroll
          for(int hh=0;hh<2;hh++){ const size_t o=(size_t)(row+8*hh)*D+cb*128+(4*jq+j)*8+2*t; gx[j][hh]=ld_rlx((const uint32_t*)(g_gate+o)); xx[j][hh]=ld_rlx((const uint32_t*)(P.x+o)); }
        #pragma unroll
        for(int j=0;j<4;j++){
          const int col=cb*128+(4*jq+j)*8+2*t;
          float4 a=v[j][0];
          #pragma unroll
          for(int s=1;s<NSPL;s++){ a.x+=v[j][s].x; a.y+=v[j][s].y; a.z+=v[j][s].z; a.w+=v[j][s].w; }
          #pragma unroll
          for(int hh=0;hh<2;hh++){
            const size_t o=(size_t)(row+8*hh)*D+col;
            const float s0=rb(hh?a.z:a.x), s1=rb(hh?a.w:a.y);
            const float o0=__uint_as_float(xx[j][hh]<<16)+rb(s0*__uint_as_float(gx[j][hh]<<16)), o1=__uint_as_float(xx[j][hh]&0xffff0000u)+rb(s1*__uint_as_float(gx[j][hh]&0xffff0000u));
            *(uint32_t*)(P.out+o)=pack_bf16(o0,o1);
          }
        }
      } else {
        const int rbk=idx>>5, h=idx&31;
        const int sgl=wq>>1, rh=wq&1, sg=rbk*4+wg*2+sgl;
        uint2 km[12], vm[12];
        {
          const uint2* kp=g_kmf+(size_t)((sg*H+h)*12)*32+lane; const uint2* vp=g_vmf+(size_t)((sg*H+h)*12)*32+lane;
          #pragma unroll
          for(int i=0;i<12;i++){ km[i]=ld_rlx2(kp+i*32); vm[i]=ld_rlx2(vp+i*32); }
        }
        mainloop<192,0>(acc,10,sb,wg,lane,st,ph);
        uint32_t pa[2][4], pm[2];
        {
          float sc[5][4];
          #pragma unroll
          for(int n=0;n<5;n++){ sc[n][0]=sc[n][1]=sc[n][2]=sc[n][3]=0.f; }
          mbar_wait(FULL+st*8,ph);
          const int kr=sgl*32+(lane&7)+((lane>>4)<<3);
          const uint32_t ka=sb+st*STG+wg*24576+kr*128; const int cs=(lane>>3)&1, sw=lane&7;
          #pragma unroll
          for(int T=0;T<12;T++){
            uint32_t qf[4]={pack_bf16(acc[8*T],acc[8*T+1]),pack_bf16(acc[8*T+2],acc[8*T+3]),pack_bf16(acc[8*T+4],acc[8*T+5]),pack_bf16(acc[8*T+6],acc[8*T+7])};
            mma16816(sc[0],qf,km[T].x,km[T].y);
            const uint32_t a=ka+(T>>2)*8192+((((T&3)*2+cs)^sw)<<4);
            uint32_t kb[4]; ldsm4(kb,a);
            mma16816(sc[1],qf,kb[0],kb[1]); mma16816(sc[2],qf,kb[2],kb[3]);
            if(rh){ ldsm4(kb,a+2048); mma16816(sc[3],qf,kb[0],kb[1]); mma16816(sc[4],qf,kb[2],kb[3]); }
          }
          __syncwarp();
          if(lane==0) mbar_arrive(EMPTY+st*8);
          if(++st==NST){ st=0; ph^=1; }
          const float NEG=rb(-1e9f);
          float mx[2]={-3.4e38f,-3.4e38f};
          #pragma unroll
          for(int n=0;n<5;n++)
            #pragma unroll
            for(int i=0;i<4;i++){
              float v=rb(rb(sc[n][i])*0.07216878364870322f);
              if(n>0){ const int key=8*(n-1)+2*t+(i&1), row=16*rh+g+8*(i>>1); if(key>row) v=NEG; }
              sc[n][i]=v; mx[i>>1]=fmaxf(mx[i>>1],v);
            }
          float sum[2]={0.f,0.f};
          #pragma unroll
          for(int r=0;r<2;r++){ mx[r]=fmaxf(mx[r],__shfl_xor_sync(~0u,mx[r],1)); mx[r]=fmaxf(mx[r],__shfl_xor_sync(~0u,mx[r],2)); }
          #pragma unroll
          for(int n=0;n<5;n++)
            #pragma unroll
            for(int i=0;i<4;i++){ const float e=ex2((sc[n][i]-mx[i>>1])*1.4426950408889634f); sc[n][i]=e; sum[i>>1]+=e; }
          #pragma unroll
          for(int r=0;r<2;r++){ sum[r]+=__shfl_xor_sync(~0u,sum[r],1); sum[r]+=__shfl_xor_sync(~0u,sum[r],2); sum[r]=rcp(sum[r]); }
          pm[0]=pack_bf16(sc[0][0]*sum[0],sc[0][1]*sum[0]); pm[1]=pack_bf16(sc[0][2]*sum[1],sc[0][3]*sum[1]);
          #pragma unroll
          for(int ks=0;ks<2;ks++){
            pa[ks][0]=pack_bf16(sc[1+2*ks][0]*sum[0],sc[1+2*ks][1]*sum[0]); pa[ks][1]=pack_bf16(sc[1+2*ks][2]*sum[1],sc[1+2*ks][3]*sum[1]);
            pa[ks][2]=pack_bf16(sc[2+2*ks][0]*sum[0],sc[2+2*ks][1]*sum[0]); pa[ks][3]=pack_bf16(sc[2+2*ks][2]*sum[1],sc[2+2*ks][3]*sum[1]);
          }
        }
        {
          mbar_wait(FULL+st*8,ph);
          const int vr=sgl*32+(lane&7)+(((lane>>3)&1)<<3);
          const uint32_t va=sb+st*STG+wg*24576+vr*128; const int cs=lane>>4, sw=lane&7;
          #pragma unroll
          for(int T=0;T<12;T++){
            float* o0=acc+8*T; float* o1=acc+8*T+4;
            #pragma unroll
            for(int i=0;i<8;i++) o0[i]=0.f;
            mma1688(o0,pm[0],pm[1],vm[T].x); mma1688(o1,pm[0],pm[1],vm[T].y);
            const uint32_t a=va+(T>>2)*8192+((((T&3)*2+cs)^sw)<<4);
            uint32_t vb[4]; ldsm4t(vb,a);
            mma16816(o0,pa[0],vb[0],vb[1]); mma16816(o1,pa[0],vb[2],vb[3]);
            ldsm4t(vb,a+2048);
            mma16816(o0,pa[1],vb[0],vb[1]); mma16816(o1,pa[1],vb[2],vb[3]);
          }
          __syncwarp();
          if(lane==0) mbar_arrive(EMPTY+st*8);
          if(++st==NST){ st=0; ph^=1; }
        }
        store_round<2>(E,acc,M_OX,h*192,rbk*128+wg*64,-1,0,nullptr);
        store_round<1>(E,acc+64,M_OX,h*192+128,rbk*128+wg*64,C_QA+rbk*NSPL+(h>>2),0,nullptr);
      }
    }
    epi_acquire(E);
    epi_cmd(E,-2,0,0,0,-1);
  }
  if(MODE==0) cluster_sync();
}
typedef CUresult (*EncFn)(CUtensorMap*,CUtensorMapDataType,cuuint32_t,void*,const cuuint64_t*,const cuuint64_t*,const cuuint32_t*,const cuuint32_t*,CUtensorMapInterleave,CUtensorMapSwizzle,CUtensorMapL2promotion,CUtensorMapFloatOOBfill);
static CUtensorMap mk2d(const void* base,uint64_t cols,uint64_t rows,uint32_t bc,uint32_t br){
  static EncFn fn=nullptr;
  if(!fn){ void* p=nullptr; cudaDriverEntryPointQueryResult qr; cudaGetDriverEntryPoint("cuTensorMapEncodeTiled",&p,cudaEnableDefault,&qr); fn=(EncFn)p; }
  CUtensorMap m; cuuint64_t gd[2]={cols,rows}; cuuint64_t gs[1]={cols*2}; cuuint32_t bd[2]={bc,br}; cuuint32_t es[2]={1,1};
  fn(&m,CU_TENSOR_MAP_DATA_TYPE_BFLOAT16,2,(void*)base,gd,gs,bd,es,CU_TENSOR_MAP_INTERLEAVE_NONE,CU_TENSOR_MAP_SWIZZLE_128B,CU_TENSOR_MAP_L2_PROMOTION_L2_128B,CU_TENSOR_MAP_FLOAT_OOB_FILL_NONE);
  return m;
}
template<class T> static T* sym(T& s){ void* p; cudaGetSymbolAddress(&p,s); return (T*)p; }
}

int g_reconly=0; int g_kvgrid=132;
extern "C" void kernel_launch(void* const* d_in, const int* in_sizes, int n_in, void* d_out, int out_size) {
  using namespace rk;
  const bf16* x=(const bf16*)d_in[0]; const bf16* mem0=(const bf16*)d_in[1];
  const bf16* Wq=(const bf16*)d_in[2]; const bf16* Wk=(const bf16*)d_in[3]; const bf16* Wv=(const bf16*)d_in[4]; const bf16* Wo=(const bf16*)d_in[5];
  const bf16* w1=(const bf16*)d_in[8]; const bf16* b1=(const bf16*)d_in[9]; const bf16* w2=(const bf16*)d_in[10]; const bf16* b2=(const bf16*)d_in[11];
  cudaStream_t st=cudaStreamPerThread;
  cudaFuncSetAttribute(k_rec,cudaFuncAttributeMaxDynamicSharedMemorySize,SM_TOTAL);
  cudaFuncSetAttribute(k_work<0>,cudaFuncAttributeMaxDynamicSharedMemorySize,W_TOTAL);
  cudaFuncSetAttribute(k_work<1>,cudaFuncAttributeMaxDynamicSharedMemorySize,W_TOTAL);
  bf16* k=(bf16*)sym(g_k); bf16* v=(bf16*)sym(g_v);
  WParams P;
  P.m[M_XN]=mk2d(sym(g_xn),D,S,64,64); P.m[M_Y]=mk2d(sym(g_y),D,S,64,64); P.m[M_H]=mk2d(sym(g_h),F,S,64,64); P.m[M_OX]=mk2d(sym(g_ox),HD,S,64,64);
  P.m[M_K]=mk2d(k,HD,S,64,64); P.m[M_V]=mk2d(v,HD,S,64,64); P.m[M_GATE]=mk2d(sym(g_gate),D,S,64,64);
  P.m[M_WQ]=mk2d(Wq,HD,D,64,64); P.m[M_WK]=mk2d(Wk,HD,D,64,64); P.m[M_WV]=mk2d(Wv,HD,D,64,64);
  P.m[M_W1]=mk2d(w1,F,D,64,64); P.m[M_W2]=mk2d(w2,D,F,64,64); P.m[M_WO]=mk2d(Wo,D,HD,64,64);
  P.x=x; P.b1=b1; P.b2=b2; P.out=(bf16*)d_out;
  k_pre<<<S/8,256,0,st>>>(x,mem0);
  if(!(g_reconly&1)){
    cudaLaunchConfig_t cfg={}; cfg.gridDim=dim3(g_kvgrid); cfg.blockDim=dim3(384); cfg.dynamicSmemBytes=W_TOTAL; cfg.stream=st;
    cudaLaunchAttribute at[2]; at[0].id=cudaLaunchAttributeClusterDimension; at[0].val.clusterDim.x=2; at[0].val.clusterDim.y=1; at[0].val.clusterDim.z=1;
    at[1].id=cudaLaunchAttributeProgrammaticStreamSerialization; at[1].val.programmaticStreamSerializationAllowed=1; cfg.attrs=at; cfg.numAttrs=2;
    cudaLaunchKernelEx(&cfg,k_work<0>,P);
  }
  if(!(g_reconly&4)){
    cudaLaunchConfig_t cfg={}; cfg.gridDim=dim3(NCTA); cfg.blockDim=dim3(256); cfg.dynamicSmemBytes=SM_TOTAL; cfg.stream=st;
    cudaLaunchAttribute at[2]; at[0].id=cudaLaunchAttributeClusterDimension; at[0].val.clusterDim.x=3; at[0].val.clusterDim.y=1; at[0].val.clusterDim.z=1;
    at[1].id=cudaLaunchAttributeProgrammaticStreamSerialization; at[1].val.programmaticStreamSerializationAllowed=1; cfg.attrs=at; cfg.numAttrs=2;
    CUtensorMap tk=mk2d(k,HD,S,64,32), tv=mk2d(v,HD,S,64,32);
    cudaLaunchKernelEx(&cfg,k_rec,tk,tv,Wq,Wk,Wv,Wo);
  }
  if(!(g_reconly&2)){
    cudaLaunchConfig_t cfg={}; cfg.gridDim=dim3(132); cfg.blockDim=dim3(384); cfg.dynamicSmemBytes=W_TOTAL; cfg.stream=st;
    cudaLaunchAttribute at[1]; at[0].id=cudaLaunchAttributeProgrammaticStreamSerialization; at[0].val.programmaticStreamSerializationAllowed=1; cfg.attrs=at; cfg.numAttrs=PDL;
    cudaLaunchKernelEx(&cfg,k_work<1>,P);
  }
}
```

```cpp
#include <cuda_runtime.h>
#include <cuda_bf16.h>
#include <stdint.h>
#include <cuda.h>

namespace rk {
typedef __nv_bfloat16 bf16;
constexpr int S=2048, D=640, H=32, DH=192, HD=6144, NSEG=64, F=1536;
constexpr uint32_t SENT=0xFFFFFFFFu;
#define GUARDN 400000
constexpr int GUARD=GUARDN;
#define RCOPY 2
constexpr int NCTA=96;

__device__ __align__(128) bf16 g_xn[S*D];
__device__ __align__(128) bf16 g_y[S*D];
__device__ __align__(128) bf16 g_h[S*F];
__device__ __align__(128) bf16 g_gate[S*D];
__device__ __align__(128) bf16 g_k[(size_t)S*HD];
__device__ __align__(128) bf16 g_v[(size_t)S*HD];
__device__ __align__(128) bf16 g_km[NSEG*8*HD];
__device__ __align__(128) bf16 g_vm[NSEG*8*HD];
__device__ __align__(128) uint32_t g_flag[NCTA*32];
__device__ __align__(128) bf16 g_ox[(size_t)S*HD];
#define RBL 12
#define NS1 4
#define NS2 16
#define PRIO(br) (((br)>>T_M2)? T_M2+__ffs((br)>>T_M2)-1 : __ffs(br)-1)
__host__ __device__ constexpr int nsp(int rb){ return rb<RBL?1:(rb<15?NS1:NS2); }
__host__ __device__ constexpr int opp_base(int rb){ return rb<=RBL?0:(rb-RBL)*NS1*20480; }
__device__ __align__(128) float4 g_opp[(size_t)(opp_base(15)+NS2*20480)];
constexpr int C_NEXT=0, C_OP=256, C_M2=288, C_M1=320, C_KV=352, C_QA=384, C_NUM=640;
__device__ __align__(128) uint32_t g_cnt[C_NUM];
#define PDL 1
__device__ __align__(128) uint32_t g_mem[(NSEG+1)*RCOPY*80*32];
__device__ __align__(128) uint32_t g_part[80*32*64];
__device__ int g_err;
__device__ unsigned long long g_gt[128*4];
#define GT(i) do{ if(threadIdx.x==0){ unsigned long long g0; asm volatile("mov.u64 %0, %%globaltimer;":"=l"(g0)); g_gt[blockIdx.x*4+(i)]=g0; } }while(0)

__device__ __forceinline__ float rb(float x){ return __bfloat162float(__float2bfloat16(x)); }
__device__ __forceinline__ uint32_t pack_bf16(float lo,float hi){ uint32_t r; asm("cvt.rn.bf16x2.f32 %0, %1, %2;":"=r"(r):"f"(hi),"f"(lo)); return r; }
__device__ __forceinline__ uint32_t movm(uint32_t a){ uint32_t d; asm volatile("movmatrix.sync.aligned.m8n8.trans.b16 %0, %1;":"=r"(d):"r"(a)); return d; }
__device__ __forceinline__ uint4 ldg_rlx4(const uint32_t* p){ uint4 v; asm volatile("ld.relaxed.gpu.global.v4.u32 {%0,%1,%2,%3}, [%4];":"=r"(v.x),"=r"(v.y),"=r"(v.z),"=r"(v.w):"l"(p):"memory"); return v; }
__device__ __forceinline__ void stg_rlx1(uint32_t* p,uint32_t a){ asm volatile("st.relaxed.gpu.global.u32 [%0], %1;"::"l"(p),"r"(a):"memory"); }
__device__ __forceinline__ void stg_rlx2(uint32_t* p,uint32_t a,uint32_t b){ asm volatile("st.relaxed.gpu.global.v2.u32 [%0], {%1,%2};"::"l"(p),"r"(a),"r"(b):"memory"); }
__device__ __forceinline__ void bar_sync(int id,int n){ asm volatile("bar.sync %0, %1;"::"r"(id),"r"(n):"memory"); }
__device__ __forceinline__ void bar_arrive(int id,int n){ asm volatile("bar.arrive %0, %1;"::"r"(id),"r"(n):"memory"); }
__device__ __forceinline__ void mma16816(float* d,const uint32_t* a,uint32_t b0,uint32_t b1){
  asm volatile("mma.sync.aligned.m16n8k16.row.col.f32.bf16.bf16.f32 {%0,%1,%2,%3},{%4,%5,%6,%7},{%8,%9},{%0,%1,%2,%3};"
   :"+f"(d[0]),"+f"(d[1]),"+f"(d[2]),"+f"(d[3]):"r"(a[0]),"r"(a[1]),"r"(a[2]),"r"(a[3]),"r"(b0),"r"(b1));
}
__device__ __forceinline__ void mma1688(float* d,uint32_t a0,uint32_t a1,uint32_t b0){
  asm volatile("mma.sync.aligned.m16n8k8.row.col.f32.bf16.bf16.f32 {%0,%1,%2,%3},{%4,%5},{%6},{%0,%1,%2,%3};"
   :"+f"(d[0]),"+f"(d[1]),"+f"(d[2]),"+f"(d[3]):"r"(a0),"r"(a1),"r"(b0));
}
__device__ __forceinline__ void ldsm4t(uint32_t* r,uint32_t addr){ asm volatile("ldmatrix.sync.aligned.m8n8.x4.trans.shared.b16 {%0,%1,%2,%3}, [%4];":"=r"(r[0]),"=r"(r[1]),"=r"(r[2]),"=r"(r[3]):"r"(addr):"memory"); }
__device__ __forceinline__ void ldsm4(uint32_t* r,uint32_t addr){ asm volatile("ldmatrix.sync.aligned.m8n8.x4.shared.b16 {%0,%1,%2,%3}, [%4];":"=r"(r[0]),"=r"(r[1]),"=r"(r[2]),"=r"(r[3]):"r"(addr):"memory"); }
__device__ __forceinline__ void stsm4(uint32_t a,uint32_t r0,uint32_t r1,uint32_t r2,uint32_t r3){ asm volatile("stmatrix.sync.aligned.m8n8.x4.shared.b16 [%0], {%1,%2,%3,%4};"::"r"(a),"r"(r0),"r"(r1),"r"(r2),"r"(r3):"memory"); }
__device__ __forceinline__ void stsm2(uint32_t a,uint32_t r0,uint32_t r1){ asm volatile("stmatrix.sync.aligned.m8n8.x2.shared.b16 [%0], {%1,%2};"::"r"(a),"r"(r0),"r"(r1):"memory"); }
__device__ __forceinline__ void cp16(uint32_t dst,const void* src){ asm volatile("cp.async.cg.shared.global [%0], [%1], 16;"::"r"(dst),"l"(src):"memory"); }
__device__ __forceinline__ void cp_wait_all(){ asm volatile("cp.async.wait_all;":::"memory"); }
__device__ __forceinline__ void fence_async(){ asm volatile("fence.proxy.async.shared::cta;":::"memory"); }
__device__ __forceinline__ void sts4f(uint32_t a,const float* v){ asm volatile("st.shared.v4.f32 [%0], {%1,%2,%3,%4};"::"r"(a),"f"(v[0]),"f"(v[1]),"f"(v[2]),"f"(v[3]):"memory"); }
__device__ __forceinline__ void sts4(uint32_t a,uint4 v){ asm volatile("st.shared.v4.u32 [%0], {%1,%2,%3,%4};"::"r"(a),"r"(v.x),"r"(v.y),"r"(v.z),"r"(v.w):"memory"); }
__device__ __forceinline__ void sts4r(uint32_t a,const uint32_t* v){ asm volatile("st.shared.v4.u32 [%0], {%1,%2,%3,%4};"::"r"(a),"r"(v[0]),"r"(v[1]),"r"(v[2]),"r"(v[3]):"memory"); }
__device__ __forceinline__ void sts2(uint32_t a,uint32_t x,uint32_t y){ asm volatile("st.shared.v2.u32 [%0], {%1,%2};"::"r"(a),"r"(x),"r"(y):"memory"); }
__device__ __forceinline__ float4 lds4f(uint32_t a){ float4 v; asm volatile("ld.shared.v4.f32 {%0,%1,%2,%3}, [%4];":"=f"(v.x),"=f"(v.y),"=f"(v.z),"=f"(v.w):"r"(a):"memory"); return v; }
__device__ __forceinline__ float2 lds2f(uint32_t a){ float2 v; asm volatile("ld.shared.v2.f32 {%0,%1}, [%2];":"=f"(v.x),"=f"(v.y):"r"(a):"memory"); return v; }
__device__ __forceinline__ uint4 lds4(uint32_t a){ uint4 v; asm volatile("ld.shared.v4.u32 {%0,%1,%2,%3}, [%4];":"=r"(v.x),"=r"(v.y),"=r"(v.z),"=r"(v.w):"r"(a):"memory"); return v; }
__device__ __forceinline__ void lds4r(uint32_t* r,uint32_t a){ asm volatile("ld.shared.v4.u32 {%0,%1,%2,%3}, [%4];":"=r"(r[0]),"=r"(r[1]),"=r"(r[2]),"=r"(r[3]):"r"(a):"memory"); }
__device__ __forceinline__ uint2 lds2(uint32_t a){ uint2 v; asm volatile("ld.shared.v2.u32 {%0,%1}, [%2];":"=r"(v.x),"=r"(v.y):"r"(a):"memory"); return v; }
__device__ __forceinline__ float ex2(float x){ float r; asm("ex2.approx.ftz.f32 %0, %1;":"=f"(r):"f"(x)); return r; }
__device__ __forceinline__ float rcp(float x){ float r; asm("rcp.approx.ftz.f32 %0, %1;":"=f"(r):"f"(x)); return r; }
__device__ __forceinline__ void mbar_init(uint32_t a,int n){ asm volatile("mbarrier.init.shared.b64 [%0], %1;"::"r"(a),"r"(n):"memory"); }
__device__ __forceinline__ void mbar_expect(uint32_t a,int bytes){ asm volatile("mbarrier.arrive.expect_tx.shared.b64 _, [%0], %1;"::"r"(a),"r"(bytes):"memory"); }
__device__ __forceinline__ void mbar_arrive(uint32_t a){ asm volatile("mbarrier.arrive.shared.b64 _, [%0];"::"r"(a):"memory"); }
__device__ __forceinline__ bool mbar_try(uint32_t a,uint32_t par){ uint32_t ok; asm volatile("{\n.reg .pred p;\nmbarrier.try_wait.parity.shared.b64 p, [%1], %2;\nselp.u32 %0,1,0,p;\n}":"=r"(ok):"r"(a),"r"(par):"memory"); return ok; }
__device__ __forceinline__ bool mbar_try_cl(uint32_t a,uint32_t par){ uint32_t ok; asm volatile("{\n.reg .pred p;\nmbarrier.try_wait.parity.acquire.cluster.shared::cta.b64 p, [%1], %2;\nselp.u32 %0,1,0,p;\n}":"=r"(ok):"r"(a),"r"(par):"memory"); return ok; }
__device__ __forceinline__ void bulk_g2s(uint32_t dst,const void* src,int bytes,uint32_t mb){ asm volatile("cp.async.bulk.shared::cluster.global.mbarrier::complete_tx::bytes [%0], [%1], %2, [%3];"::"r"(dst),"l"(src),"r"(bytes),"r"(mb):"memory"); }
__device__ __forceinline__ uint32_t mapa(uint32_t a,uint32_t r){ uint32_t d; asm("mapa.shared::cluster.u32 %0, %1, %2;":"=r"(d):"r"(a),"r"(r)); return d; }
__device__ __forceinline__ void st_async2(uint32_t ra,uint32_t x,uint32_t y,uint32_t rmb){ asm volatile("st.async.weak.shared::cluster.mbarrier::complete_tx::bytes.v2.b32 [%0], {%1,%2}, [%3];"::"r"(ra),"r"(x),"r"(y),"r"(rmb):"memory"); }
__device__ __forceinline__ void st_async4(uint32_t ra,uint32_t x,uint32_t y,uint32_t z,uint32_t w,uint32_t rmb){ asm volatile("st.async.weak.shared::cluster.mbarrier::complete_tx::bytes.v4.b32 [%0], {%1,%2,%3,%4}, [%5];"::"r"(ra),"r"(x),"r"(y),"r"(z),"r"(w),"r"(rmb):"memory"); }
__device__ __forceinline__ void stg_rlx4(uint32_t* p,uint32_t a,uint32_t b,uint32_t c,uint32_t d){ asm volatile("st.relaxed.gpu.global.v4.u32 [%0], {%1,%2,%3,%4};"::"l"(p),"r"(a),"r"(b),"r"(c),"r"(d):"memory"); }
__device__ __forceinline__ void cluster_sync(){ asm volatile("barrier.cluster.arrive.release.aligned;\nbarrier.cluster.wait.acquire.aligned;":::"memory"); }
__device__ __forceinline__ uint32_t ld_acq(const uint32_t* p){ uint32_t v; asm volatile("ld.acquire.gpu.global.u32 %0, [%1];":"=r"(v):"l"(p):"memory"); return v; }
__device__ __forceinline__ void fence_async_all(){ asm volatile("fence.proxy.async;":::"memory"); }
__device__ __forceinline__ void fence_gpu(){ asm volatile("fence.acq_rel.gpu;":::"memory"); }

template<int NL,class V,class LDF,class OKF>
__device__ __forceinline__ int poll1(V* u,LDF ld,OKF ok,bool& dead,int code){
  #pragma unroll
  for(int i=0;i<NL;i++) u[i]=ld(i);
  int guard=0;
  while(true){
    bool f[NL]; bool a=true;
    #pragma unroll
    for(int i=0;i<NL;i++){ f[i]=ok(u[i]); a=a&&f[i]; }
    if(__all_sync(~0u,a)||dead) break;
    #pragma unroll
    for(int i=0;i<NL;i++) if(!f[i]) u[i]=ld(i);
    if(++guard>GUARD){ dead=true; g_err=code; }
  }
  return guard;
}
template<int NL,class V,class LDF,class OKF>
__device__ __forceinline__ void poll2(V* u,LDF ld,OKF ok,bool& dead,int code){
  int guard=0;
  while(true){
    bool f[NL]; bool a=true;
    #pragma unroll
    for(int i=0;i<NL;i++){ f[i]=ok(u[i]); a=a&&f[i]; }
    if(__all_sync(~0u,a)||dead) break;
    #pragma unroll
    for(int i=0;i<NL;i++) if(!f[i]) u[i]=ld(i);
    if(++guard>GUARD){ dead=true; g_err=code; }
  }
}
__device__ __forceinline__ void spin(uint32_t n){ uint32_t t0,t1; asm volatile("mov.u32 %0, %%clock;":"=r"(t0)); do{ asm volatile("mov.u32 %0, %%clock;":"=r"(t1)); }while(t1-t0<n); }
template<int N> __device__ __forceinline__ void wgmma(float* d,uint32_t da,uint32_t db,int sc);
template<int N> __device__ __forceinline__ void wgmma_rs(float* d,const uint32_t* a,uint32_t db,int sc);
template<> __device__ __forceinline__ void wgmma<128>(float* d,uint32_t da,uint32_t db,int sc){
  asm volatile("{\n.reg .pred p;\n.reg .b64 xa, xb;\nmov.b64 xa, {%64, 0x40000040};\nmov.b64 xb, {%65, 0x40000040};\nsetp.ne.b32 p, %66, 0;\nwgmma.mma_async.sync.aligned.m64n128k16.f32.bf16.bf16 {%0,%1,%2,%3,%4,%5,%6,%7,%8,%9,%10,%11,%12,%13,%14,%15,%16,%17,%18,%19,%20,%21,%22,%23,%24,%25,%26,%27,%28,%29,%30,%31,%32,%33,%34,%35,%36,%37,%38,%39,%40,%41,%42,%43,%44,%45,%46,%47,%48,%49,%50,%51,%52,%53,%54,%55,%56,%57,%58,%59,%60,%61,%62,%63}, xa, xb, p, 1, 1, 0, 1;\n}"
   :"+f"(d[0]),"+f"(d[1]),"+f"(d[2]),"+f"(d[3]),"+f"(d[4]),"+f"(d[5]),"+f"(d[6]),"+f"(d[7]),"+f"(d[8]),"+f"(d[9]),"+f"(d[10]),"+f"(d[11]),"+f"(d[12]),"+f"(d[13]),"+f"(d[14]),"+f"(d[15]),"+f"(d[16]),"+f"(d[17]),"+f"(d[18]),"+f"(d[19]),"+f"(d[20]),"+f"(d[21]),"+f"(d[22]),"+f"(d[23]),"+f"(d[24]),"+f"(d[25]),"+f"(d[26]),"+f"(d[27]),"+f"(d[28]),"+f"(d[29]),"+f"(d[30]),"+f"(d[31]),"+f"(d[32]),"+f"(d[33]),"+f"(d[34]),"+f"(d[35]),"+f"(d[36]),"+f"(d[37]),"+f"(d[38]),"+f"(d[39]),"+f"(d[40]),"+f"(d[41]),"+f"(d[42]),"+f"(d[43]),"+f"(d[44]),"+f"(d[45]),"+f"(d[46]),"+f"(d[47]),"+f"(d[48]),"+f"(d[49]),"+f"(d[50]),"+f"(d[51]),"+f"(d[52]),"+f"(d[53]),"+f"(d[54]),"+f"(d[55]),"+f"(d[56]),"+f"(d[57]),"+f"(d[58]),"+f"(d[59]),"+f"(d[60]),"+f"(d[61]),"+f"(d[62]),"+f"(d[63]):"r"(da),"r"(db),"r"(sc));
}
template<> __device__ __forceinline__ void wgmma<192>(float* d,uint32_t da,uint32_t db,int sc){
  asm volatile("{\n.reg .pred p;\n.reg .b64 xa, xb;\nmov.b64 xa, {%96, 0x40000040};\nmov.b64 xb, {%97, 0x40000040};\nsetp.ne.b32 p, %98, 0;\nwgmma.mma_async.sync.aligned.m64n192k16.f32.bf16.bf16 {%0,%1,%2,%3,%4,%5,%6,%7,%8,%9,%10,%11,%12,%13,%14,%15,%16,%17,%18,%19,%20,%21,%22,%23,%24,%25,%26,%27,%28,%29,%30,%31,%32,%33,%34,%35,%36,%37,%38,%39,%40,%41,%42,%43,%44,%45,%46,%47,%48,%49,%50,%51,%52,%53,%54,%55,%56,%57,%58,%59,%60,%61,%62,%63,%64,%65,%66,%67,%68,%69,%70,%71,%72,%73,%74,%75,%76,%77,%78,%79,%80,%81,%82,%83,%84,%85,%86,%87,%88,%89,%90,%91,%92,%93,%94,%95}, xa, xb, p, 1, 1, 0, 1;\n}"
   :"+f"(d[0]),"+f"(d[1]),"+f"(d[2]),"+f"(d[3]),"+f"(d[4]),"+f"(d[5]),"+f"(d[6]),"+f"(d[7]),"+f"(d[8]),"+f"(d[9]),"+f"(d[10]),"+f"(d[11]),"+f"(d[12]),"+f"(d[13]),"+f"(d[14]),"+f"(d[15]),"+f"(d[16]),"+f"(d[17]),"+f"(d[18]),"+f"(d[19]),"+f"(d[20]),"+f"(d[21]),"+f"(d[22]),"+f"(d[23]),"+f"(d[24]),"+f"(d[25]),"+f"(d[26]),"+f"(d[27]),"+f"(d[28]),"+f"(d[29]),"+f"(d[30]),"+f"(d[31]),"+f"(d[32]),"+f"(d[33]),"+f"(d[34]),"+f"(d[35]),"+f"(d[36]),"+f"(d[37]),"+f"(d[38]),"+f"(d[39]),"+f"(d[40]),"+f"(d[41]),"+f"(d[42]),"+f"(d[43]),"+f"(d[44]),"+f"(d[45]),"+f"(d[46]),"+f"(d[47]),"+f"(d[48]),"+f"(d[49]),"+f"(d[50]),"+f"(d[51]),"+f"(d[52]),"+f"(d[53]),"+f"(d[54]),"+f"(d[55]),"+f"(d[56]),"+f"(d[57]),"+f"(d[58]),"+f"(d[59]),"+f"(d[60]),"+f"(d[61]),"+f"(d[62]),"+f"(d[63]),"+f"(d[64]),"+f"(d[65]),"+f"(d[66]),"+f"(d[67]),"+f"(d[68]),"+f"(d[69]),"+f"(d[70]),"+f"(d[71]),"+f"(d[72]),"+f"(d[73]),"+f"(d[74]),"+f"(d[75]),"+f"(d[76]),"+f"(d[77]),"+f"(d[78]),"+f"(d[79]),"+f"(d[80]),"+f"(d[81]),"+f"(d[82]),"+f"(d[83]),"+f"(d[84]),"+f"(d[85]),"+f"(d[86]),"+f"(d[87]),"+f"(d[88]),"+f"(d[89]),"+f"(d[90]),"+f"(d[91]),"+f"(d[92]),"+f"(d[93]),"+f"(d[94]),"+f"(d[95]):"r"(da),"r"(db),"r"(sc));
}
template<> __device__ __forceinline__ void wgmma_rs<80>(float* d,const uint32_t* a,uint32_t db,int sc){
  asm volatile("{\n.reg .pred p;\n.reg .b64 xb;\nmov.b64 xb, {%44, 0x40000040};\nsetp.ne.b32 p, %45, 0;\nwgmma.mma_async.sync.aligned.m64n80k16.f32.bf16.bf16 {%0,%1,%2,%3,%4,%5,%6,%7,%8,%9,%10,%11,%12,%13,%14,%15,%16,%17,%18,%19,%20,%21,%22,%23,%24,%25,%26,%27,%28,%29,%30,%31,%32,%33,%34,%35,%36,%37,%38,%39}, {%40,%41,%42,%43}, xb, p, 1, 1, 0;\n}"
   :"+f"(d[0]),"+f"(d[1]),"+f"(d[2]),"+f"(d[3]),"+f"(d[4]),"+f"(d[5]),"+f"(d[6]),"+f"(d[7]),"+f"(d[8]),"+f"(d[9]),"+f"(d[10]),"+f"(d[11]),"+f"(d[12]),"+f"(d[13]),"+f"(d[14]),"+f"(d[15]),"+f"(d[16]),"+f"(d[17]),"+f"(d[18]),"+f"(d[19]),"+f"(d[20]),"+f"(d[21]),"+f"(d[22]),"+f"(d[23]),"+f"(d[24]),"+f"(d[25]),"+f"(d[26]),"+f"(d[27]),"+f"(d[28]),"+f"(d[29]),"+f"(d[30]),"+f"(d[31]),"+f"(d[32]),"+f"(d[33]),"+f"(d[34]),"+f"(d[35]),"+f"(d[36]),"+f"(d[37]),"+f"(d[38]),"+f"(d[39]):"r"(a[0]),"r"(a[1]),"r"(a[2]),"r"(a[3]),"r"(db),"r"(sc));
}
template<> __device__ __forceinline__ void wgmma_rs<192>(float* d,const uint32_t* a,uint32_t db,int sc){
  asm volatile("{\n.reg .pred p;\n.reg .b64 xb;\nmov.b64 xb, {%100, 0x40000040};\nsetp.ne.b32 p, %101, 0;\nwgmma.mma_async.sync.aligned.m64n192k16.f32.bf16.bf16 {%0,%1,%2,%3,%4,%5,%6,%7,%8,%9,%10,%11,%12,%13,%14,%15,%16,%17,%18,%19,%20,%21,%22,%23,%24,%25,%26,%27,%28,%29,%30,%31,%32,%33,%34,%35,%36,%37,%38,%39,%40,%41,%42,%43,%44,%45,%46,%47,%48,%49,%50,%51,%52,%53,%54,%55,%56,%57,%58,%59,%60,%61,%62,%63,%64,%65,%66,%67,%68,%69,%70,%71,%72,%73,%74,%75,%76,%77,%78,%79,%80,%81,%82,%83,%84,%85,%86,%87,%88,%89,%90,%91,%92,%93,%94,%95}, {%96,%97,%98,%99}, xb, p, 1, 1, 1;\n}"
   :"+f"(d[0]),"+f"(d[1]),"+f"(d[2]),"+f"(d[3]),"+f"(d[4]),"+f"(d[5]),"+f"(d[6]),"+f"(d[7]),"+f"(d[8]),"+f"(d[9]),"+f"(d[10]),"+f"(d[11]),"+f"(d[12]),"+f"(d[13]),"+f"(d[14]),"+f"(d[15]),"+f"(d[16]),"+f"(d[17]),"+f"(d[18]),"+f"(d[19]),"+f"(d[20]),"+f"(d[21]),"+f"(d[22]),"+f"(d[23]),"+f"(d[24]),"+f"(d[25]),"+f"(d[26]),"+f"(d[27]),"+f"(d[28]),"+f"(d[29]),"+f"(d[30]),"+f"(d[31]),"+f"(d[32]),"+f"(d[33]),"+f"(d[34]),"+f"(d[35]),"+f"(d[36]),"+f"(d[37]),"+f"(d[38]),"+f"(d[39]),"+f"(d[40]),"+f"(d[41]),"+f"(d[42]),"+f"(d[43]),"+f"(d[44]),"+f"(d[45]),"+f"(d[46]),"+f"(d[47]),"+f"(d[48]),"+f"(d[49]),"+f"(d[50]),"+f"(d[51]),"+f"(d[52]),"+f"(d[53]),"+f"(d[54]),"+f"(d[55]),"+f"(d[56]),"+f"(d[57]),"+f"(d[58]),"+f"(d[59]),"+f"(d[60]),"+f"(d[61]),"+f"(d[62]),"+f"(d[63]),"+f"(d[64]),"+f"(d[65]),"+f"(d[66]),"+f"(d[67]),"+f"(d[68]),"+f"(d[69]),"+f"(d[70]),"+f"(d[71]),"+f"(d[72]),"+f"(d[73]),"+f"(d[74]),"+f"(d[75]),"+f"(d[76]),"+f"(d[77]),"+f"(d[78]),"+f"(d[79]),"+f"(d[80]),"+f"(d[81]),"+f"(d[82]),"+f"(d[83]),"+f"(d[84]),"+f"(d[85]),"+f"(d[86]),"+f"(d[87]),"+f"(d[88]),"+f"(d[89]),"+f"(d[90]),"+f"(d[91]),"+f"(d[92]),"+f"(d[93]),"+f"(d[94]),"+f"(d[95]):"r"(a[0]),"r"(a[1]),"r"(a[2]),"r"(a[3]),"r"(db),"r"(sc));
}
__global__ void __launch_bounds__(256) k_pre(const bf16* __restrict__ x,const bf16* __restrict__ mem0){
  const int warp=threadIdx.x>>5, lane=threadIdx.x&31;
  const int row=blockIdx.x*8+warp;
  asm volatile("griddepcontrol.launch_dependents;");
  {
    int i=blockIdx.x*256+threadIdx.x; int n=gridDim.x*256;
    for(int k=i;k<(NSEG+1)*RCOPY*80*32;k+=n){
      uint32_t v=SENT;
      if(k<RCOPY*80*32){ int fb=(k%2560)>>5, r=(k>>2)&7, w=k&3; const uint16_t* mp=(const uint16_t*)mem0+r*D+(fb>>1)*16+(fb&1)*4+w; v=mp[0]|((uint32_t)mp[8]<<16);
        if(v==SENT) v=0x7FFF7FFFu; }
      g_mem[k]=v;
    }
    if(i==0) g_err=0;
    if(i<NCTA*32) g_flag[i]=0;
    if(i<C_NUM) g_cnt[i]=0;
  }
  float v[20];
  {
    const uint32_t* p=(const uint32_t*)(x+(size_t)row*D);
    #pragma unroll
    for(int i=0;i<10;i++){ uint32_t u=p[lane+32*i]; v[2*i]=__uint_as_float(u<<16); v[2*i+1]=__uint_as_float(u&0xffff0000u); }
  }
  #pragma unroll
  for(int pass=0;pass<2;pass++){
    float s=0;
    #pragma unroll
    for(int i=0;i<20;i++) s+=v[i];
    #pragma unroll
    for(int o=16;o;o>>=1) s+=__shfl_xor_sync(~0u,s,o);
    float mean=s*(1.f/D);
    float q=0;
    #pragma unroll
    for(int i=0;i<20;i++){ float d=v[i]-mean; q+=d*d; }
    #pragma unroll
    for(int o=16;o;o>>=1) q+=__shfl_xor_sync(~0u,q,o);
    float var=rb(q*(1.f/D)), mb=rb(mean);
    float den=rb(sqrtf(rb(var+1e-5f)));
    uint32_t* o=(uint32_t*)((pass?g_y:g_xn)+(size_t)row*D);
    #pragma unroll
    for(int i=0;i<10;i++){
      float a=rb(rb(v[2*i]-mb)/den), b=rb(rb(v[2*i+1]-mb)/den);
      v[2*i]=a; v[2*i+1]=b;
      o[lane+32*i]=pack_bf16(a,b);
    }
  }
}

#define RDELAY 400
#define BDELAY 0
constexpr int SM_QS=0;
constexpr int SM_VS=49152;
constexpr int SM_OS=131072;
constexpr int SM_O=SM_OS+43008;
constexpr int SM_RSUM=SM_O+3072;
constexpr int SM_RED=180224;
constexpr int SM_KX=SM_RED+16384;
constexpr int SM_VX=SM_KX+4096;
constexpr int SM_SCX=SM_VX+12288;
constexpr int SM_VMX=SM_SCX+6144;
constexpr int SM_VRED=SM_VMX+3072;
constexpr int SM_MB=SM_VRED+8192+1024;
constexpr int SM_TOTAL=SM_MB+64;
static_assert(SM_MB-SM_RED>=49152,"staging");
static_assert(SM_TOTAL<=232448,"smem");

#define TS(i)
#define PC(i) (void)np
#define TW(i)
#define TF(i)

__device__ __forceinline__ void cp_commit(){ asm volatile("cp.async.commit_group;":::"memory"); }
template<int N> __device__ __forceinline__ void cp_wait(){ asm volatile("cp.async.wait_group %0;"::"n"(N):"memory"); }
__device__ __forceinline__ void tma2d(uint32_t dst,const CUtensorMap* tm,int c0,int c1,uint32_t mb){
  asm volatile("cp.async.bulk.tensor.2d.shared::cluster.global.mbarrier::complete_tx::bytes [%0], [%1, {%3, %4}], [%2];"::"r"(dst),"l"(tm),"r"(mb),"r"(c0),"r"(c1):"memory"); }
__device__ __forceinline__ void tma2d_pf(const CUtensorMap* tm,int c0,int c1){
  asm volatile("cp.async.bulk.prefetch.tensor.2d.L2.global [%0, {%1, %2}];"::"l"(tm),"r"(c0),"r"(c1):"memory"); }
__global__ void __launch_bounds__(256,1) k_rec(const __grid_constant__ CUtensorMap tmK,const __grid_constant__ CUtensorMap tmV,const bf16* __restrict__ Wq,const bf16* __restrict__ Wk,const bf16* __restrict__ Wv,const bf16* __restrict__ Wo){
  extern __shared__ __align__(1024) uint8_t sm[];
  const int tid=threadIdx.x, warp=__shfl_sync(~0u,tid>>5,0), lane=tid&31, g=lane>>2, t=lane&3;
  const int b=blockIdx.x, h=b/3, c=b-3*h;
  const uint32_t sb=(uint32_t)__cvta_generic_to_shared(sm);
  const int kq=warp&3, mg=warp>>2;
  const uint32_t s16=sb+lane*16, s8=sb+lane*8;
  const uint32_t qs=s16+SM_QS+warp*6144, vs=s16+SM_VS+kq*20480, os=s16+SM_OS+warp*6144;
  const uint32_t XS=sb+SM_MB, KVB=sb+SM_MB+8, XV=sb+SM_MB+16;
  GT(0);
  asm volatile("griddepcontrol.launch_dependents;");
  if(tid==0){
    mbar_init(XS,5); mbar_init(KVB,1); mbar_init(XV,5);
    asm volatile("fence.mbarrier_init.release.cluster;":::"memory");
    mbar_expect(XS,4096); mbar_expect(XV,2048);
  }
  const int ntile=c==0?14:13, tile0=c==0?0:(1+13*c);
  uint32_t wr[7][4][4];
  uint32_t wo[6][2][4];
  auto ldW=[&](int p,uint32_t stg){
    #pragma unroll
    for(int i=0;i<12;i++){
      const int idx=tid+256*i, row=idx>>3, ch=idx&7, m=row>>7, f=160*((row>>5)&3)+32*p+(row&31);
      const bf16* src=(m==0?Wq:(m==1?Wk:Wv))+(size_t)f*HD+h*DH+64*c+ch*8;
      const int sw=(row>>2)&7;
      cp16(stg+row*128+((ch^sw)<<4),src);
    }
    cp_commit();
  };
  auto ldO=[&](int r,uint32_t stg){
    for(int idx=tid;idx<96*28;idx+=256){
      const int row=idx/28, ch=idx-row*28;
      if(ch<2*ntile) cp16(stg+row*464+ch*16,Wo+(size_t)(h*DH+96*r+row)*D+tile0*16+ch*8);
    }
    cp_commit();
  };
  ldW(0,sb+SM_RED);
  #pragma unroll
  for(int p=0;p<5;p++){
    const uint32_t stg=sb+((p&1)?SM_OS:SM_RED), nstg=sb+((p&1)?SM_RED:SM_OS);
    if(p<4) ldW(p+1,nstg); else ldO(0,nstg);
    cp_wait<1>(); __syncthreads();
    #pragma unroll
    for(int e=0;e<2;e++){
      const int k=2*p+e;
      const int fo=16*((lane>>2)&1)+4*((lane>>1)&1)+2*e+(lane>>4)+8*(lane&1);
      const int sw=(fo>>2)&7;
      #pragma unroll
      for(int j=0;j<4;j++){
        const uint32_t a=stg+((mg*4+kq)*32+fo)*128+(((2*j+((lane>>3)&1))^sw)<<4);
        if(k>=2&&k<9) ldsm4t(wr[(k>=2&&k<9)?k-2:0][j],a);
        else { uint32_t r[4]; ldsm4t(r,a); sts4r(qs+((k<2?k*4:8)+j)*512,r); }
        if(mg){ uint32_t r[4]; ldsm4t(r,a+16384); sts4r(vs+(k*4+j)*512,r); }
      }
    }
    __syncthreads();
  }
  #pragma unroll
  for(int r=0;r<2;r++){
    const uint32_t stg=sb+(r?SM_RED:SM_OS);
    if(r==0){ ldO(1,sb+SM_RED); cp_wait<1>(); } else cp_wait<0>();
    __syncthreads();
    #pragma unroll
    for(int kk=0;kk<6;kk++){
      #pragma unroll
      for(int i=0;i<2;i++){
        int tl=2*warp+i; if(tl>=ntile) tl=0;
        const uint32_t a=stg+(16*kk+(lane&7)+(lane>>4)*8)*464+(2*tl+((lane>>3)&1))*16;
        if(r==0) ldsm4t(wo[kk][i],a);
        else { uint32_t rr[4]; ldsm4t(rr,a); if(warp<7) sts4r(os+(kk*2+i)*512,rr); }
      }
    }
    __syncthreads();
  }
  auto kv_issue=[&](int sn){
    if(lane==0){
      mbar_expect(KVB,32*512);
      tma2d(sb+SM_KX,&tmK,h*DH+64*c,sn*32,KVB);
      #pragma unroll
      for(int i=0;i<3;i++) tma2d(sb+SM_VX+i*4096,&tmV,h*DH+64*i,sn*32,KVB);
    }
    __syncwarp();
  };
  auto kv_chk=[&](int rbk){
    if(lane==0){ int gd=0; while(ld_acq(g_cnt+C_KV+rbk)<64){ if(++gd>GUARD){ g_err=7; break; } } fence_async_all(); }
    __syncwarp();
  };
  auto kv_pf=[&](int sn){
    if(lane==0){ tma2d_pf(&tmK,h*DH+64*c,sn*32); tma2d_pf(&tmV,h*DH+64*c,sn*32); }
    __syncwarp();
  };
  if(warp==7){ fence_async(); kv_chk(0); kv_issue(0); kv_pf(1); kv_pf(2); }
  cluster_sync();
  const bool isred=(b%6)<5; const int rline=(b/6)*5+(b%6);
  bool dead=false;
  const uint32_t qrd=sb+SM_RED+1024+((lane>>3)&1)*4096+(lane>>4)*128+(lane&7)*16+kq*256;
  uint32_t rsc[2];
  rsc[0]=mapa(sb,c==2?0:c+1); rsc[1]=mapa(sb,c==0?2:c-1);
  uint32_t buf[8][4];
  #pragma unroll
  for(int i=0;i<8;i++) lds4r(buf[i],qs+i*512);

  uint32_t tg=3;
  GT(1);
  #define MB0(k) (((k)&1)?mv[(k)>>1].z:mv[(k)>>1].x)
  #define MB1(k) (((k)&1)?mv[(k)>>1].w:mv[(k)>>1].y)
  #pragma unroll 1
  for(int s=0;s<NSEG;s++){
    tg=tg==3?1:tg+1;
    const bool last=s==NSEG-1;
    uint4 mv[5];
    {
      const uint32_t* src=(const uint32_t*)((const char*)g_mem+(uint32_t)((s*RCOPY+(b%RCOPY))*10240+(kq*20+t)*128+g*16));
      auto okf=[&](const uint4& v){ return v.x!=SENT&&v.y!=SENT&&v.z!=SENT&&v.w!=SENT; };
      const uint32_t mx=s16+SM_RED+kq*4096;
      if(mg==0){
        int np=poll1<3>(mv,[&](int i){ return ldg_rlx4(src+i*128); },okf,dead,1);
        TW(0); PC(0);
        #pragma unroll
        for(int p=0;p<3;p++) sts4(mx+(4+p)*512,mv[p]);
        bar_sync(8+kq,64);
        mv[3]=lds4(mx); mv[4]=lds4(mx+512);
      } else {
        int np=poll1<2>(mv+3,[&](int i){ return ldg_rlx4(src+(3+i)*128); },okf,dead,1);
        TW(0); PC(0);
        sts4(mx,mv[3]); sts4(mx+512,mv[4]);
        bar_sync(8+kq,64);
        #pragma unroll
        for(int p=0;p<3;p++) mv[p]=lds4(mx+(4+p)*512);
      }
    }
    TS(0); TF(0);
    float acc[4][4]; uint32_t kb[8];
    #pragma unroll
    for(int i=0;i<4;i++){ acc[i][0]=acc[i][1]=acc[i][2]=acc[i][3]=0.f; }
    #pragma unroll
    for(int k=0;k<10;k++){
      #pragma unroll
      for(int j=0;j<4;j++){
        if(k<2) mma16816(acc[j],buf[(k&1)*4+j],MB0(k),MB1(k));
        else if(k<9) mma16816(acc[j],wr[(k>=2&&k<9)?k-2:0][j],MB0(k),MB1(k));
        else mma16816(acc[j],buf[j],MB0(k),MB1(k));
        if(k==2) lds4r(buf[j],qs+(8+j)*512);
        if(k==4&&mg) lds4r(buf[4+j],vs+j*512);
      }
      if(k==5&&!mg){
        { int gd=0; while(!mbar_try(KVB,s&1)){ if(dead) break; if(++gd>GUARD){ dead=true; g_err=6; } } }
        const uint32_t ka=sb+SM_KX+(8*kq+(lane&7))*128+((((lane>>3)^(2*kq))^(lane&7))<<4);
        ldsm4(kb,ka); ldsm4(kb+4,ka^64);
      }
    }
    TF(1);
    const uint32_t exo=(uint32_t)(((s*8+g)*HD+h*DH+64*c+16*kq+2*t)*2);
    if(mg){
      {
        const uint32_t ra=s16+SM_RED+kq*4096+2048;
        #pragma unroll
        for(int i=0;i<4;i++) sts4f(ra+i*512,acc[i]);
      }
      bar_arrive(1,256);
      #pragma unroll
      for(int j=0;j<4;j++) lds4r(buf[j],vs+(4+j)*512);
      #pragma unroll
      for(int i=0;i<4;i++){ acc[i][0]=acc[i][1]=acc[i][2]=acc[i][3]=0.f; }
      #pragma unroll
      for(int u=0;u<40;u++){
        mma16816(acc[u&3],buf[(u+4)&7],MB0(u>>2),MB1(u>>2));
        if(u<8||(u>=16&&u+8<40)) lds4r(buf[(u+4)&7],vs+(u+8)*512);
        if(u==15){
          bar_sync(6,256);
          #pragma unroll
          for(int v=8;v<16;v++) lds4r(buf[(v+4)&7],vs+(v+8)*512);
        }
      }
      TF(2);
      const uint32_t ra=s16+SM_VRED;
      #pragma unroll
      for(int i=0;i<4;i++) sts4f(ra+kq*2048+i*512,acc[i]);
      bar_sync(3,128);
      float4 a=lds4f(ra+kq*512), c1=lds4f(ra+kq*512+2048), d2=lds4f(ra+kq*512+4096), e2=lds4f(ra+kq*512+6144);
      const uint32_t p0=pack_bf16((a.x+c1.x)+(d2.x+e2.x),(a.y+c1.y)+(d2.y+e2.y)), p1=pack_bf16((a.z+c1.z)+(d2.z+e2.z),(a.w+c1.w)+(d2.w+e2.w));
      const uint32_t off=SM_VMX+(4*c+kq)*256+lane*8;
      if(!last){
        #pragma unroll
        for(int r=0;r<2;r++) st_async2(rsc[r]+off,p0,p1,rsc[r]+SM_MB+16);
        sts2(sb+off,p0,p1); __syncwarp(); if(lane==0) mbar_arrive(XV);
      }
      TF(5);
      if(warp==7){ fence_async_all(); fence_gpu(); if(lane==0) stg_rlx1(g_flag+b*32,s); if((s&3)==3&&s+1<NSEG) kv_chk((s+1)>>2); }
      { const uint32_t v0=movm(p0), v1=movm(p1); stg_rlx1((uint32_t*)((char*)g_vm+exo),v0); stg_rlx1((uint32_t*)((char*)g_vm+exo+16),v1); }
      TF(7);
      if(last) break;
      if(warp<7){
        #pragma unroll
        for(int i=0;i<8;i++) lds4r(buf[i],os+i*512);
      }
    } else {
      {
        const uint32_t qa=s16+SM_RED+kq*4096+1024;
        #pragma unroll
        for(int i=0;i<2;i++) stsm4(qa+i*512,pack_bf16(acc[2*i][0],acc[2*i][1]),pack_bf16(acc[2*i][2],acc[2*i][3]),pack_bf16(acc[2*i+1][0],acc[2*i+1][1]),pack_bf16(acc[2*i+1][2],acc[2*i+1][3]));
      }
      TF(2);
      bar_sync(1,256);
      TS(1); TF(3);
      {
        const uint32_t ra=s16+SM_RED+2048+kq*512;
        float4 a3=lds4f(ra), c3=lds4f(ra+4096), d3=lds4f(ra+8192), e3=lds4f(ra+12288);
        uint32_t q[4][2][4];
        #pragma unroll
        for(int i=0;i<4;i++){ ldsm4t(q[i][0],qrd^(i*256)); ldsm4t(q[i][1],(qrd^(i*256))+8192); }
        bar_arrive(6,256);
        const uint32_t p2=pack_bf16((a3.x+c3.x)+(d3.x+e3.x),(a3.y+c3.y)+(d3.y+e3.y)), p3=pack_bf16((a3.z+c3.z)+(d3.z+e3.z),(a3.w+c3.w)+(d3.w+e3.w));
        const uint32_t f2=movm(p2), f3=movm(p3);
        if(last){ stg_rlx1((uint32_t*)((char*)g_km+exo),f2); stg_rlx1((uint32_t*)((char*)g_km+exo+16),f3); break; }
        TF(4);
        float sc[6][4];
        #pragma unroll
        for(int i=0;i<6;i++){ sc[i][0]=sc[i][1]=sc[i][2]=sc[i][3]=0.f; }
        #pragma unroll
        for(int i=0;i<4;i++)
          #pragma unroll
          for(int jp=0;jp<2;jp++){
            mma16816(sc[(i&1)*2+jp],q[i][jp],kb[2*i],kb[2*i+1]);
            if(i==1) mma16816(sc[4+jp],q[0][jp],f2,f3);
          }
        const uint32_t w0=__float_as_uint(((sc[0][0]+sc[0][2])+(sc[1][0]+sc[1][2]))+((sc[2][0]+sc[2][2])+(sc[3][0]+sc[3][2]))), w1=__float_as_uint(((sc[0][1]+sc[0][3])+(sc[1][1]+sc[1][3]))+((sc[2][1]+sc[2][3])+(sc[3][1]+sc[3][3])));
        const uint32_t w2=__float_as_uint((sc[4][0]+sc[4][2])+(sc[5][0]+sc[5][2])), w3=__float_as_uint((sc[4][1]+sc[4][3])+(sc[5][1]+sc[5][3]));
        const uint32_t off=SM_SCX+(c*4+kq)*512+lane*16;
        #pragma unroll
        for(int r=0;r<2;r++) st_async4(rsc[r]+off,w0,w1,w2,w3,rsc[r]+SM_MB);
        sts4(sb+off,make_uint4(w0,w1,w2,w3)); __syncwarp(); if(lane==0) mbar_arrive(XS);
        TS(2); TF(5);
        stg_rlx1((uint32_t*)((char*)g_km+exo),f2); stg_rlx1((uint32_t*)((char*)g_km+exo+16),f3);
      }
      uint32_t va[3][2][4];
      #pragma unroll
      for(int i=0;i<3;i++){
        const int T=3*kq+i;
        const uint32_t vaddr=sb+SM_VX+(T>>2)*4096+((lane>>4)*8+(lane&7))*128+(((2*(T&3)+((lane>>3)&1))^(lane&7))<<4);
        ldsm4t(va[i][0],vaddr); ldsm4t(va[i][1],vaddr+2048);
      }
      TF(6);
      { int gd=0; while(!mbar_try(XS,s&1)){ if(dead) break; if(++gd>GUARD){ dead=true; g_err=2; } } }
      TS(3); TF(7);
      float sv[10];
      {
        float4 u[12];
        #pragma unroll
        for(int n=0;n<12;n++) u[n]=lds4f(s16+SM_SCX+n*512);
        uint32_t r[5];
        #pragma unroll
        for(int n=0;n<4;n++) r[n+1]=pack_bf16((u[n].x+u[4+n].x)+u[8+n].x,(u[n].y+u[4+n].y)+u[8+n].y);
        r[0]=pack_bf16((((u[0].z+u[1].z)+(u[2].z+u[3].z))+((u[4].z+u[5].z)+(u[6].z+u[7].z)))+((u[8].z+u[9].z)+(u[10].z+u[11].z)),
                       (((u[0].w+u[1].w)+(u[2].w+u[3].w))+((u[4].w+u[5].w)+(u[6].w+u[7].w)))+((u[8].w+u[9].w)+(u[10].w+u[11].w)));
        #pragma unroll
        for(int n=0;n<5;n++){
          const uint32_t w=pack_bf16(__uint_as_float(r[n]<<16)*0.07216878364870322f,__uint_as_float(r[n]&0xffff0000u)*0.07216878364870322f);
          sv[2*n]=__uint_as_float(w<<16); sv[2*n+1]=__uint_as_float(w&0xffff0000u);
        }
      }
      TF(8);
      float mx=fmaxf(fmaxf(fmaxf(sv[0],sv[1]),fmaxf(sv[2],sv[3])),fmaxf(fmaxf(fmaxf(sv[4],sv[5]),fmaxf(sv[6],sv[7])),fmaxf(sv[8],sv[9])));
      mx=fmaxf(mx,__shfl_xor_sync(~0u,mx,1)); mx=fmaxf(mx,__shfl_xor_sync(~0u,mx,2));
      mx*=-1.4426950408889634f;
      #pragma unroll
      for(int i=0;i<10;i++) sv[i]=ex2(fmaf(sv[i],1.4426950408889634f,mx));
      float sum=((sv[0]+sv[1])+(sv[2]+sv[3]))+(((sv[4]+sv[5])+(sv[6]+sv[7]))+(sv[8]+sv[9]));
      sum+=__shfl_xor_sync(~0u,sum,1); sum+=__shfl_xor_sync(~0u,sum,2);
      const float inv=rcp(sum);
      uint32_t pp[5];
      #pragma unroll
      for(int n=0;n<5;n++) pp[n]=pack_bf16(sv[2*n]*inv,sv[2*n+1]*inv);
      TF(9);
      float o[3][4];
      #pragma unroll
      for(int i=0;i<3;i++){ o[i][0]=o[i][1]=o[i][2]=o[i][3]=0.f; mma16816(o[i],va[i][0],pp[1],pp[2]); }
      { int gd=0; while(!mbar_try(XV,s&1)){ if(dead) break; if(++gd>GUARD){ dead=true; g_err=3; } } }
      uint2 vm[3];
      #pragma unroll
      for(int i=0;i<3;i++) vm[i]=lds2(s8+SM_VMX+(3*kq+i)*256);
      #pragma unroll
      for(int i=0;i<8;i++) lds4r(buf[i],os+i*512);
      #pragma unroll
      for(int i=0;i<3;i++) mma16816(o[i],va[i][1],pp[3],pp[4]);
      #pragma unroll
      for(int i=0;i<3;i++) mma1688(o[i],vm[i].x,vm[i].y,pp[0]);
      stsm4(s16+SM_O+kq*768,pack_bf16(o[0][0],o[0][1]),pack_bf16(o[0][2],o[0][3]),pack_bf16(o[1][0],o[1][1]),pack_bf16(o[1][2],o[1][3]));
      stsm2(s16+SM_O+kq*768+512,pack_bf16(o[2][0],o[2][1]),pack_bf16(o[2][2],o[2][3]));
    }
    TF(10);
    if(warp<7){
      if(!mg) bar_arrive(7,160);
      bar_sync(4,224);
      uint32_t ob[6][4];
      ldsm4t(ob[3],s16+SM_O+3*512);
      #pragma unroll
      for(int i=0;i<6;i++) if(i!=3) ldsm4t(ob[i],s16+SM_O+i*512);
      TF(11);
      float ca[2][2][4];
      #pragma unroll
      for(int i=0;i<2;i++)
        #pragma unroll
        for(int j=0;j<2;j++){ ca[i][j][0]=ca[i][j][1]=ca[i][j][2]=ca[i][j][3]=0.f; }
      #pragma unroll
      for(int x=0;x<12;x++){
        const int ks=x<2?6+x:(x<8?x-2:x);
        const uint32_t b0=ob[ks>>1][(ks&1)*2], b1=ob[ks>>1][(ks&1)*2+1];
        #pragma unroll
        for(int i=0;i<2;i++){
          if(ks<6) mma16816(ca[i][ks&1],wo[ks<6?ks:0][i],b0,b1);
          else mma16816(ca[i][ks&1],buf[((ks-6)*2+i)&7],b0,b1);
          if(x==3||x==4) lds4r(buf[(x-3)*2+i],os+(8+(x-3)*2+i)*512);
        }
      }
      TF(12);
      uint32_t* dst=(uint32_t*)((char*)g_part+(uint32_t)(((tile0+2*warp)*32+h)*512+lane*16));
      #pragma unroll
      for(int i=0;i<2;i++){
        if(i==0||2*warp+1<ntile)
          stg_rlx4(dst+i*4096,(__float_as_uint(ca[i][0][0]+ca[i][1][0])&~3u)|tg,(__float_as_uint(ca[i][0][1]+ca[i][1][1])&~3u)|tg,
                              (__float_as_uint(ca[i][0][2]+ca[i][1][2])&~3u)|tg,(__float_as_uint(ca[i][0][3]+ca[i][1][3])&~3u)|tg);
      }
    }
    TW(1);
    TS(4); TF(13);
    #pragma unroll
    for(int i=0;i<8;i++) lds4r(buf[i],qs+i*512);
    if(isred){
      const uint32_t* src=(const uint32_t*)((char*)g_part+(uint32_t)(((rline>>1)*32+4*warp+(lane>>4))*512+(rline&1)*256+(lane&15)*16));
      uint32_t* mdst=g_mem+(size_t)((s+1)*RCOPY)*2560+rline*32+lane;
      uint4 v[2]; float f[4];
      { uint32_t t0,t1; asm volatile("mov.u32 %0, %%clock;":"=r"(t0)); do{ asm volatile("mov.u32 %0, %%clock;":"=r"(t1)); }while(t1-t0<RDELAY); }
      auto okr=[&](const uint4& v){ return ((((v.x^tg)|(v.y^tg))|((v.z^tg)|(v.w^tg)))&3u)==0; };
      int np=poll1<2>(v,[&](int i){ return ldg_rlx4(src+i*256); },okr,dead,4);
      f[0]=__uint_as_float(v[0].x)+__uint_as_float(v[1].x); f[1]=__uint_as_float(v[0].y)+__uint_as_float(v[1].y); f[2]=__uint_as_float(v[0].z)+__uint_as_float(v[1].z); f[3]=__uint_as_float(v[0].w)+__uint_as_float(v[1].w);
      TW(2); TF(14); PC(1);
      #pragma unroll
      for(int i=0;i<4;i++) f[i]+=__shfl_xor_sync(~0u,f[i],16);
      if(lane<16) sts4f(s16+SM_RSUM+warp*256,f);
      if(warp==0){
        bar_sync(5,256);
        TS(5);
        const float* rp=(const float*)(sm+SM_RSUM)+(lane&3)*16+(lane>>3)*4+((lane>>2)&1);
        float a0=((rp[0]+rp[64])+(rp[128]+rp[192]))+((rp[256]+rp[320])+(rp[384]+rp[448]));
        float a1=((rp[2]+rp[66])+(rp[130]+rp[194]))+((rp[258]+rp[322])+(rp[386]+rp[450]));
        uint32_t o=pack_bf16(a0,a1); if(o==SENT) o=0x7FFF7FFFu;
        #pragma unroll
        for(int cc=0;cc<RCOPY;cc++) stg_rlx1(mdst+cc*2560,o);
        TS(6); TW(3);
      } else bar_arrive(5,256);
    }
    TF(15);
    if(warp==7){
      bar_sync(7,160);
      if(lane==0){ mbar_expect(XS,4096); mbar_expect(XV,2048); }
      if(s+1<NSEG) kv_issue(s+1);
      if(s+3<NSEG) kv_pf(s+3);
      if(isred&&lane<RCOPY&&s+3<=NSEG) asm volatile("prefetch.global.L2 [%0];"::"l"(g_mem+(size_t)((s+3)*RCOPY+lane)*2560+rline*32));
    }
  }
  __syncthreads();
  if(warp==7){ fence_async_all(); fence_gpu(); if(lane==0) stg_rlx1(g_flag+b*32,NSEG); }
  GT(2);
  cluster_sync();
}

enum { M_XN=0,M_Y,M_H,M_OX,M_K,M_V,M_GATE,M_WQ,M_WK,M_WV,M_W1,M_W2,M_WO,M_KM,M_VM,M_NUM,M_OUT };
struct WParams { CUtensorMap m[M_NUM]; const bf16* x; const bf16* b1; const bf16* b2; bf16* out; };
enum { T_RED=0,T_OP=1,T_QA=2,T_M2=3,T_M1=4,T_KV=5,T_END=6 };
#define KVUP 640
#define TRIG 10
#define SOV 1
#define LATE 14
#define EARLY 2
constexpr int NRB=16;
constexpr int STG=40960, NST=4, SLOT=30720, BOXS=10240;
constexpr int W_SLOT=NST*STG;
constexpr int W_BAR=W_SLOT+2*SLOT;
constexpr int W_TOTAL=W_BAR+1024;
static_assert(W_TOTAL<=232448,"smem");
#define QT(i)
__device__ __forceinline__ void stsm4n(uint32_t a,uint32_t r0,uint32_t r1,uint32_t r2,uint32_t r3){ asm volatile("stmatrix.sync.aligned.m8n8.x4.shared.b16 [%0], {%1,%2,%3,%4};"::"r"(a),"r"(r0),"r"(r1),"r"(r2),"r"(r3)); }
#define WGUARD 2000000
__host__ __device__ constexpr int n_op(){ int n=0; for(int r=0;r<NRB;r++) n+=4*nsp(r); return n; }
__host__ __device__ constexpr int n_red(){ int n=0; for(int r=0;r<NRB;r++) if(nsp(r)>1) n+=5*nsp(r); return n; }

__device__ __forceinline__ void wg_arrive(){ asm volatile("wgmma.fence.sync.aligned;":::"memory"); }
__device__ __forceinline__ void wg_commit(){ asm volatile("wgmma.commit_group.sync.aligned;":::"memory"); }
template<int N> __device__ __forceinline__ void wg_wait(){ asm volatile("wgmma.wait_group.sync.aligned %0;"::"n"(N):"memory"); }
__device__ __forceinline__ void mbar_wait(uint32_t a,uint32_t par){ int gd=0; while(!mbar_try(a,par)){ if(++gd>WGUARD){ g_err=20; break; } } }
__device__ __forceinline__ uint32_t ld_rlx(const uint32_t* p){ uint32_t v; asm volatile("ld.relaxed.gpu.global.u32 %0, [%1];":"=r"(v):"l"(p):"memory"); return v; }
__device__ __forceinline__ float4 ld_rlx4f(const float4* p){ float4 v; asm volatile("ld.relaxed.gpu.global.v4.f32 {%0,%1,%2,%3}, [%4];":"=f"(v.x),"=f"(v.y),"=f"(v.z),"=f"(v.w):"l"(p):"memory"); return v; }
__device__ __forceinline__ void red_rel(uint32_t* p){ asm volatile("red.release.gpu.global.add.u32 [%0], 1;"::"l"(p):"memory"); }
__device__ __forceinline__ void tma_st(const CUtensorMap* tm,uint32_t src,int c0,int c1){
  asm volatile("cp.async.bulk.tensor.2d.global.shared::cta.bulk_group [%0, {%2, %3}], [%1];"::"l"(tm),"r"(src),"r"(c0),"r"(c1):"memory"); }
__device__ __forceinline__ void bulk_commit(){ asm volatile("cp.async.bulk.commit_group;":::"memory"); }
__device__ __forceinline__ void bulk_wait_rd(){ asm volatile("cp.async.bulk.wait_group.read 0;":::"memory"); }
__device__ __forceinline__ void bulk_wait(){ asm volatile("cp.async.bulk.wait_group 0;":::"memory"); }
__device__ __forceinline__ void mbar_arrive_cl(uint32_t a){ asm volatile("mbarrier.arrive.shared::cluster.b64 _, [%0];"::"r"(a):"memory"); }
__device__ __forceinline__ void tma2dm(uint32_t dst,const CUtensorMap* tm,int c0,int c1,uint32_t mb){
  asm volatile("cp.async.bulk.tensor.2d.shared::cluster.global.mbarrier::complete_tx::bytes.multicast::cluster [%0], [%1, {%3, %4}], [%2], %5;"::"r"(dst),"l"(tm),"r"(mb),"r"(c0),"r"(c1),"h"((uint16_t)3):"memory"); }

template<int N,int CL,int XS> __device__ __forceinline__ void mainloop(float* acc,int nkb,uint32_t sb,int lane,uint32_t pos){
  const uint32_t eb=CL?mapa(sb+W_BAR+32,lane&1):sb+W_BAR+32;
  uint32_t pst=0;
  #pragma unroll
  for(int i=0;i<N/2;i++){ acc[i]=0.f; acc[96+i]=0.f; }
  #pragma unroll 1
  for(int kb=0;kb<nkb;kb++,pos++){
    const uint32_t st=pos&3;
    mbar_wait(sb+W_BAR+st*8,(pos>>2)&1);
    if(!XS&&kb==nkb-1&&(threadIdx.x&127)==0) mbar_arrive(sb+W_BAR+144);
    const uint32_t a=sb+st*STG;
    const uint32_t da=((a>>4)&0x3fff)|(1u<<16);
    const uint32_t db=da+1024+(511u<<16);
    wg_arrive();
    #pragma unroll
    for(int k=0;k<4;k++){ wgmma<N>(acc,da+2*k,db+128*k,kb|k); wgmma<N>(acc+96,da+512+2*k,db+128*k,kb|k); }
    wg_commit();
    if(kb>0){ wg_wait<1>(); if(CL){ if(lane<2) mbar_arrive_cl(eb+pst*8); } else if(lane==0) mbar_arrive(eb+pst*8); }
    pst=st;
  }
  if(XS){
    #pragma unroll
    for(int x=0;x<XS;x++) mbar_wait(sb+W_BAR+((pos+x)&3)*8,((pos+x)>>2)&1);
    if((threadIdx.x&127)==0) mbar_arrive(sb+W_BAR+144);
  }
  wg_wait<0>();
  if(CL){ if(lane<2) mbar_arrive_cl(eb+pst*8); } else if(lane==0) mbar_arrive(eb+pst*8);
}
__device__ __forceinline__ uint32_t act2(uint32_t u,uint32_t bb,float c1,float c3){
  uint32_t s; asm("add.rn.bf16x2 %0, %1, %2;":"=r"(s):"r"(u),"r"(bb));
  float r[2]={__uint_as_float(s<<16), __uint_as_float(s&0xffff0000u)};
  #pragma unroll
  for(int i=0;i<2;i++){
    const float z=r[i]*fmaf(r[i]*r[i],c3,c1);
    r[i]=r[i]*rcp(1.f+ex2(z));
  }
  return pack_bf16(r[0],r[1]);
}
__device__ __forceinline__ uint32_t fin1(uint32_t s,uint32_t x,uint32_t gq){
  const uint32_t p=pack_bf16(__uint_as_float(s<<16)*__uint_as_float(gq<<16),__uint_as_float(s&0xffff0000u)*__uint_as_float(gq&0xffff0000u));
  return pack_bf16(__uint_as_float(x<<16)+__uint_as_float(p<<16),__uint_as_float(x&0xffff0000u)+__uint_as_float(p&0xffff0000u));
}
template<int NT> __device__ __forceinline__ void stage_pk(const uint32_t* p,uint32_t ra,int lane){
  const int sw=lane&7, hi=lane>>4;
  #pragma unroll
  for(int T=0;T<NT;T++) stsm4n(ra+(T>>2)*BOXS+((((2*T+hi)&7)^sw)<<4),p[4*T],p[4*T+1],p[4*T+2],p[4*T+3]);
}
__device__ __noinline__ void post_pass(uint32_t sl,int nbox,int em,uint32_t ba,float c1,float c3,const bf16* x,bf16* out,uint32_t go){
  const int lane=threadIdx.x&31, r=lane>>3, c=lane&7;
  __syncwarp();
  #pragma unroll 1
  for(int j=0;j<nbox;j++){
    uint4 u[4]; uint32_t a[4];
    #pragma unroll
    for(int i=0;i<4;i++){ const int rr=4*i+r; a[i]=sl+j*BOXS+rr*128+((c^(rr&7))<<4); u[i]=lds4(a[i]); }
    if(em==1){
      const uint4 bb=lds4(ba+j*128+c*16);
      #pragma unroll
      for(int i=0;i<4;i++){
        uint4& v=u[i];
        v.x=act2(v.x,bb.x,c1,c3); v.y=act2(v.y,bb.y,c1,c3); v.z=act2(v.z,bb.z,c1,c3); v.w=act2(v.w,bb.w,c1,c3);
        sts4(a[i],v);
      }
    } else {
      uint4 xx[4],gg[4];
      #pragma unroll
      for(int i=0;i<4;i++){ const uint32_t o=go+(4*i+r)*D+j*64+c*8; xx[i]=__ldg((const uint4*)(x+o)); gg[i]=ldg_rlx4((const uint32_t*)(g_gate+o)); }
      #pragma unroll
      for(int i=0;i<4;i++){ const uint32_t o=go+(4*i+r)*D+j*64+c*8;
        *(uint4*)(out+o)=make_uint4(fin1(u[i].x,xx[i].x,gg[i].x),fin1(u[i].y,xx[i].y,gg[i].y),fin1(u[i].z,xx[i].z,gg[i].z),fin1(u[i].w,xx[i].w,gg[i].w)); }
    }
  }
}
template<int Q,int NS> __device__ __forceinline__ void red_item(const WParams& P,int rbk,int r,int tid){
  const int lane=tid&31, g=lane>>2, t=lane&3, wq=(tid>>5)&3;
  const float4* src=g_opp+opp_base(rbk)+(size_t)(r*Q)*128+(tid&127);
  float4 v[Q][NS];
  #pragma unroll
  for(int j=0;j<Q;j++)
    #pragma unroll
    for(int s=0;s<NS;s++) v[j][s]=ld_rlx4f(src+(size_t)s*20480+j*128);
  uint32_t gx[Q][2], xx[Q][2]; uint32_t off[Q];
  #pragma unroll
  for(int j=0;j<Q;j++){
    const int qi=r*Q+j, m=qi>=80, J=qi-80*m;
    off[j]=(uint32_t)((rbk*128+m*64+wq*16+g)*D+8*J+2*t);
    #pragma unroll
    for(int hh=0;hh<2;hh++){ gx[j][hh]=ld_rlx((const uint32_t*)(g_gate+off[j]+hh*8*D)); xx[j][hh]=__ldg((const uint32_t*)(P.x+off[j]+hh*8*D)); }
  }
  #pragma unroll
  for(int j=0;j<Q;j++){
    float4 a=v[j][0];
    #pragma unroll
    for(int s=1;s<NS;s++){ a.x+=v[j][s].x; a.y+=v[j][s].y; a.z+=v[j][s].z; a.w+=v[j][s].w; }
    *(uint32_t*)(P.out+off[j])=fin1(pack_bf16(a.x,a.y),xx[j][0],gx[j][0]);
    *(uint32_t*)(P.out+off[j]+8*D)=fin1(pack_bf16(a.z,a.w),xx[j][1],gx[j][1]);
  }
}
template<int N,int MODE> __device__ __forceinline__ void gemm_item(const WParams& P,int type,int rbk,int a,uint32_t pos,uint32_t sb,int tid,uint32_t ra,uint32_t& e0,uint32_t& eb,int& sq){
  const int lane=tid&31, wg=tid>>7;
  const uint32_t E0=sb+W_BAR+96+wg*16;
  float acc[192];
  const int ns=nsp(rbk), nt=a&3;
  const int nkb=(MODE&&type==T_M2)?24:((MODE&&type==T_OP)?96/ns:10);
  mainloop<N,MODE==0,0>(acc,nkb,sb,lane,pos);
  if(MODE==0||type>=T_M2||ns==1){
    uint32_t p[2][N/4];
    #pragma unroll
    for(int m=0;m<2;m++)
      #pragma unroll
      for(int i=0;i<N/4;i++) p[m][i]=pack_bf16(acc[96*m+2*i],acc[96*m+2*i+1]);
    const float c1=type==T_M1?-2.302208198144325f:-1.4426950408889634f, c3=type==T_M1?-0.10294323958f:0.f;
    const int wq=(tid>>5)&3;
    if(MODE&&(type==T_M1||type==T_M2)){ mbar_wait(sb+W_BAR+224+wg*8,eb); eb^=1; }
    #pragma unroll
    for(int m=0;m<2;m++){
      mbar_wait(E0+m*8,e0);
      stage_pk<N/16>(p[m],ra+m*SLOT,lane);
      if(MODE&&type!=T_KV) post_pass(sb+W_SLOT+m*SLOT+wq*2048,N/64,type==T_OP?2:1,sb+W_BAR+256+wg*384,c1,c3,P.x,P.out,(uint32_t)((rbk*128+m*64+wq*16)*D+(nt<2?nt*192:128+nt*128)));
      fence_async();
      bar_arrive(sq,160); sq^=1;
    }
    e0^=1;
  } else {
    float4* dst=g_opp+opp_base(rbk)+(size_t)(a>>2)*20480+(nt<2?nt*24:16+nt*16)*128+(tid&127);
    #pragma unroll
    for(int m=0;m<2;m++)
      #pragma unroll
      for(int n=0;n<N/8;n++) __stcg(dst+(m*80+n)*128,make_float4(acc[96*m+4*n],acc[96*m+4*n+1],acc[96*m+4*n+2],acc[96*m+4*n+3]));
    mbar_wait(E0,e0); mbar_wait(E0+8,e0); e0^=1;
    bar_arrive(sq,160); sq^=1;
  }
}
__device__ __forceinline__ void decode(int c,int idx,int& rbk,int& a){
  if(c==T_KV){ rbk=2*(idx>>7)+(idx&1); a=(idx>>1)&63; }
  else if(c==T_M1){ rbk=idx>>3; a=idx&7; }
  else if(c==T_M2){ rbk=idx>>2; a=idx&3; }
  else if(c==T_QA){ rbk=idx>>5; a=idx&31; }
  else {
    rbk=0;
    #pragma unroll 1
    while(true){ const int ns=nsp(rbk), n=c==T_OP?4*ns:(ns>1?5*ns:0); if(idx<n) break; idx-=n; rbk++; }
    a=idx;
  }
}
__device__ __forceinline__ void flag_wait(int rbk,int a){
  const uint32_t need=4*rbk+4; const uint32_t* f=g_flag+a*96; int gd=0;
  while(ld_acq(f)<need||ld_acq(f+32)<need||ld_acq(f+64)<need){ __nanosleep(40); if(++gd>WGUARD){ g_err=22; break; } }
  fence_async_all();
}
__device__ __forceinline__ void cnt_wait(int c,uint32_t thr){
  int gd=0;
  while(ld_acq(g_cnt+c)<thr){ __nanosleep(40); if(++gd>WGUARD){ g_err=23; break; } }
}
template<int MODE>
__global__ void __launch_bounds__(384,1) k_work(const __grid_constant__ WParams P){
  extern __shared__ __align__(1024) uint8_t sm[];
  const uint32_t sb=(uint32_t)__cvta_generic_to_shared(sm);
  const int tid=threadIdx.x, warp=__shfl_sync(~0u,tid>>5,0), lane=tid&31;
  const uint32_t FULL=sb+W_BAR, EMPTY=sb+W_BAR+32, IFULL=sb+W_BAR+64, IEMPTY=sb+W_BAR+80, EF=sb+W_BAR+96, REQ=sb+W_BAR+128, TOK=sb+W_BAR+136;
  volatile int* idesc=(volatile int*)(sm+W_BAR+160);
  if(tid==0){
    for(int i=0;i<NST;i++){ mbar_init(FULL+i*8,1); mbar_init(EMPTY+i*8,MODE?4:8); mbar_init(EF+i*8,1); }
    for(int i=0;i<2;i++){ mbar_init(IFULL+i*8,1); mbar_init(IEMPTY+i*8,6); mbar_init(sb+W_BAR+224+i*8,1); }
    mbar_init(REQ,1); mbar_init(TOK,1); mbar_init(sb+W_BAR+144,1);
    asm volatile("fence.mbarrier_init.release.cluster;":::"memory");
  }
  __syncthreads();
  if(MODE==0){ cluster_sync(); asm volatile("griddepcontrol.wait;":::"memory"); asm volatile("griddepcontrol.launch_dependents;"); }
  if(warp>=8){
    asm volatile("setmaxnreg.dec.sync.aligned.u32 40;");
    if(warp==11){
      uint32_t it=0, pos=0;
      int held=-1; int guard=0; bool fin=false;
      const int cl=lane>>2, cj=lane&3;
      const int ncls=cl==T_RED?n_red():(cl==T_OP?n_op():(cl==T_QA?NRB*32:(cl==T_M2?NRB*4:(cl==T_M1?NRB*8:(cl==T_KV?NRB*64-KVUP:0)))));
      const int cofs=cl==T_KV?KVUP:0;
      int sidx=blockIdx.x;
      while(true){
        int type=T_END, idx=0, erl=0;
        if(!fin){
          if(it) mbar_wait(REQ,(it&1)^1);
          if(MODE==0){ if(sidx<KVUP){ type=T_KV; idx=sidx; sidx+=gridDim.x; } }
          else {
            while(true){
              int cand=held;
              if(cand<0&&ncls){ cand=(int)ld_rlx(g_cnt+C_NEXT+cl*32); if(cand>=ncls) cand=-1; }
              const uint32_t* fp=nullptr; uint32_t thr=0, sl1=0; bool only1=false, no1=cl>=T_M2;
              if(cand>=0&&cl<=T_M2){
                int rbk,a; decode(cl,cand,rbk,a); const int ns=nsp(rbk);
                if(cl==T_QA){ if(cj<3){ fp=g_flag+a*96+cj*32; thr=4*rbk+4; sl1=EARLY; } else { fp=g_cnt+C_KV+min(rbk+1,NRB-1); thr=64; only1=true; } }
                else if(cj==0){ fp=g_cnt+(cl==T_RED?C_OP+rbk:(cl==T_OP?C_QA+rbk*16+(a>>2):C_M1+rbk)); thr=cl==T_RED?4*ns:(cl==T_OP?32/ns:8); sl1=thr; }
                else if(cj==1){ if(cl==T_RED||(cl==T_OP&&ns==1)){ fp=g_cnt+C_M2+rbk; thr=4; } if(rbk<NRB-1) no1=true; }
                else if(cj==2&&cl<T_QA&&ns>1){ fp=g_cnt+C_NEXT+(cl+1)*32; thr=cl==T_OP?(rbk+1)*32:4*RBL+4*NS1*(min(rbk,14)+1-RBL)+(rbk==15?4*NS2:0); only1=true; }
              }
              uint32_t v=0; if(fp) v=ld_acq(fp);
              uint32_t b2=__ballot_sync(~0u,cand>=0&&(v>=thr||only1)), b1=__ballot_sync(~0u,cand>=0&&!no1&&v+sl1>=thr);
              const uint32_t ba=__ballot_sync(~0u,cand>=0), bh=__ballot_sync(~0u,held>=0);
              b2&=b2>>1; b2&=b2>>2; b1&=b1>>1; b1&=b1>>2;
              const bool opf=__ballot_sync(~0u,cl==T_OP&&cand<4*RBL)!=0;
              if(opf&&(bh&~(15u<<(4*T_OP)))) b2&=~(1u<<(4*T_OP));
              b2&=0x111111u; b1&=0x111u; if(bh) b1&=(__popc(bh)==4)?bh:0u;
              if(!EARLY) b1=0;
              if(!ba) break;
              if(b2|b1){
                const uint32_t bb=b2?b2:b1;
                #define RD(c) ((bb>>(4*(c)))&1)
                const int w=RD(T_KV)?T_KV:(RD(T_M2)?T_M2:(RD(T_M1)?T_M1:((opf&&RD(T_OP))?T_OP:(RD(T_QA)?T_QA:(RD(T_OP)?T_OP:T_RED)))));
                int got=-1;
                if(cl==w){
                  if(held>=0){ got=held; held=-1; }
                  else {
                    int tk=0; if(cj==0) tk=(int)atomicAdd(g_cnt+C_NEXT+cl*32,1u);
                    tk=__shfl_sync(15u<<(4*cl),tk,4*cl);
                    if(tk<ncls){ if(tk==cand||cl>T_M2) got=tk; else held=tk; }
                  }
                  if(got>=0) got+=cofs;
                }
                got=__shfl_sync(~0u,got,4*w);
                if(got>=0){ type=w; idx=got; erl=!b2; break; }
              } else {
                __nanosleep(100);
                if(++guard>WGUARD){ g_err=21; break; }
              }
            }
          }
        }
        __syncwarp();
        if(lane==0){
          const uint32_t sl=it&1;
          int rbk=0,a=0; if(type!=T_END) decode(type,idx,rbk,a);
          mbar_wait(IEMPTY+sl*8,((it>>1)&1)^1);
          idesc[sl*8]=type; idesc[sl*8+1]=rbk; idesc[sl*8+2]=a; idesc[sl*8+3]=pos; idesc[sl*8+4]=idx; idesc[sl*8+5]=erl;
          mbar_arrive(IFULL+sl*8);
          pos+=type==T_RED?0:(type==T_M2?24:(type==T_OP?96/nsp(rbk):(type==T_QA?12:10)));
        }
        __syncwarp();
        it++;
        if(type==T_END){ if(fin) break; fin=true; }
      }
    } else if(warp==8){
      if(lane==0){
        uint32_t st=0, ph=1;
        for(uint32_t it=0;;it++){
          const uint32_t sl=it&1;
          mbar_wait(IFULL+sl*8,(it>>1)&1);
          const int type=idesc[sl*8], rbk=idesc[sl*8+1], a=idesc[sl*8+2], erl=idesc[sl*8+5];
          mbar_arrive(IEMPTY+sl*8);
          if(type==T_END) break;
          if(type==T_RED){ mbar_arrive(REQ); continue; }
          int ma=M_XN,mb,col0=a*192,k0=0,nkb=10,nbox=3; const int row0=rbk*128;
          if(MODE==0||type==T_KV){ mb=a<32?M_WK:M_WV; col0=(a&31)*192; }
          else if(type==T_M1){ ma=M_Y; mb=M_W1; }
          else if(type==T_QA){ mb=M_WQ; }
          else {
            const int nt=a&3; col0=nt<2?nt*192:128+nt*128; nbox=nt<2?3:2;
            if(type==T_M2){ ma=M_H; mb=M_W2; nkb=24; } else { ma=M_OX; mb=M_WO; nkb=96/nsp(rbk); k0=(a>>2)*nkb*64; }
          }
          if(MODE&&erl&&type==T_OP) cnt_wait(C_QA+rbk*16+(a>>2),32/nsp(rbk));
          if(MODE) fence_async_all();
          const CUtensorMap* A=&P.m[ma]; const CUtensorMap* B=&P.m[mb];
          const int trig=(MODE&&type<=T_QA&&rbk>=LATE)?nkb-1:max(nkb-(type==T_QA?TRIG-2:TRIG),0);
          for(int kb=0;kb<nkb;kb++){
            mbar_wait(EMPTY+st*8,ph);
            const uint32_t d=sb+st*STG, fb=FULL+st*8;
            mbar_expect(fb,16384+nbox*8192);
            const int kk=k0+kb*64;
            tma2d(d,A,kk,row0,fb); tma2d(d+8192,A,kk,row0+64,fb);
            if(MODE==0){
              const int r=rbk&1, j=2*r;
              tma2dm(d+16384+j*8192,B,col0+j*64,kk,fb);
              if((kb&1)==r) tma2dm(d+24576,B,col0+64,kk,fb);
            }
            else for(int j=0;j<nbox;j++) tma2d(d+16384+j*8192,B,col0+j*64,kk,fb);
            if(kb==trig) mbar_arrive(REQ);
            if(++st==NST){ st=0; ph^=1; }
          }
          if(MODE&&type==T_QA){
            for(int m=0;m<2;m++){
              mbar_wait(EMPTY+st*8,ph);
              const uint32_t d=sb+st*STG, fb=FULL+st*8;
              mbar_expect(fb,SLOT);
              for(int j=0;j<3;j++) tma2d(d+j*BOXS,&P.m[M_K],col0+j*64,row0+m*64,fb);
              if(erl&&!m) flag_wait(rbk,a);
              for(int j=0;j<3;j++) tma2d(d+j*BOXS+8192,&P.m[M_KM],col0+j*64,rbk*32+m*16,fb);
              if(++st==NST){ st=0; ph^=1; }
            }
          }
        }
      }
      __syncwarp();
    } else if(warp<11){
      const int wg=warp-9;
      const uint32_t S0=sb+W_SLOT, E0=EF+wg*16; int sq=4+2*wg;
      for(uint32_t it=wg;;it+=2){
        mbar_wait(IFULL+wg*8,(it>>1)&1);
        const int type=idesc[wg*8], rbk=idesc[wg*8+1], a=idesc[wg*8+2], erl=idesc[wg*8+5];
        __syncwarp();
        if(lane==0) mbar_arrive(IEMPTY+wg*8);
        if(type==T_END) break;
        if(MODE&&type==T_OP&&nsp(rbk)>1&&lane==0){ mbar_arrive(E0); mbar_arrive(E0+8); }
        const int row0=rbk*128;
        int map=-1,col0=a*192,nbox=3,cnt=-1;
        if(MODE==0||type==T_KV){ map=a<32?M_K:M_V; col0=(a&31)*192; cnt=C_KV+rbk; }
        else if(type==T_M1){ map=M_H; cnt=C_M1+rbk; }
        else if(type==T_QA){ map=M_OX; cnt=C_QA+rbk*16+((a*nsp(rbk))>>5); }
        else if(type!=T_RED){
          const int nt=a&3; col0=nt<2?nt*192:128+nt*128; nbox=nt<2?3:2;
          if(type==T_M2){ map=M_GATE; cnt=C_M2+rbk; } else if(nsp(rbk)==1) map=M_OUT;
        }
        if(MODE&&(type==T_M1||type==T_M2)&&lane==0){ const uint32_t bb=sb+W_BAR+224+wg*8; mbar_expect(bb,nbox*128); bulk_g2s(sb+W_BAR+256+wg*384,(type==T_M1?P.b1:P.b2)+col0,nbox*128,bb); }
        if(it&&lane==0) mbar_wait(TOK,(it&1)^1);
        if(MODE&&map<0){
          if(lane==0) mbar_arrive(TOK);
          if(type==T_RED&&lane==0){ if(erl) cnt_wait(C_OP+rbk,4*nsp(rbk)); mbar_arrive(E0); mbar_arrive(E0+8); }
          if(type==T_OP){ { __syncwarp(); bar_sync(sq,160); sq^=1; } if(lane==0){ fence_gpu(); red_rel(g_cnt+C_OP+rbk); } }
        } else if(MODE&&map==M_OUT){
          if(lane==0){ mbar_arrive(E0); mbar_arrive(E0+8); }
          { __syncwarp(); bar_sync(sq,160); sq^=1; }
          { __syncwarp(); bar_sync(sq,160); sq^=1; }
          if(lane==0) mbar_arrive(TOK);
        } else {
          if(MODE&&type==T_QA){
            if(lane==0){
              fence_async_all();
              for(int m=0;m<2;m++){
                mbar_expect(E0+m*8,SLOT);
                for(int j=0;j<3;j++) tma2d(S0+m*SLOT+j*BOXS,&P.m[M_V],col0+j*64,row0+m*64,E0+m*8);
              }
              if(erl) flag_wait(rbk,a);
              for(int m=0;m<2;m++)
                for(int j=0;j<3;j++) tma2d(S0+m*SLOT+j*BOXS+8192,&P.m[M_VM],col0+j*64,rbk*32+m*16,E0+m*8);
            }
          } else if(lane==0){ mbar_arrive(E0); mbar_arrive(E0+8); }
          for(int m=0;m<2;m++){
            { __syncwarp(); bar_sync(sq,160); sq^=1; }
            if(lane==0){
              for(int j=0;j<nbox;j++) tma_st(&P.m[map],S0+m*SLOT+j*BOXS,col0+j*64,row0+m*64);
              bulk_commit();
            }
          }
          if(lane==0){
            bulk_wait_rd(); mbar_arrive(TOK);
            bulk_wait(); fence_async_all(); red_rel(g_cnt+cnt);
          }
        }
        __syncwarp();
      }
      if(lane==0) bulk_wait();
    }
  } else {
    asm volatile("setmaxnreg.inc.sync.aligned.u32 232;");
    const int wg=warp>>2, wq=warp&3, g=lane>>2, t=lane&3;
    const uint32_t E0=EF+wg*16;
    const uint32_t ra=sb+W_SLOT+(16*wq+(lane&7)+((lane>>3)&1)*8)*128;
    uint32_t e0=0, eb=0; int sq=4+2*wg;
    #pragma unroll 1
    for(uint32_t it=0;;it++){
      mbar_wait(IFULL+wg*8,it&1);
      const int type=idesc[wg*8], rbk=idesc[wg*8+1], a=idesc[wg*8+2]; const uint32_t pos=idesc[wg*8+3];
      __syncwarp();
      if(lane==0) mbar_arrive(IEMPTY+wg*8);
      if(type==T_END) break;
      mbar_wait(sb+W_BAR+144,wg^1);
      if(MODE&&type==T_RED){
        bar_sync(8+wg,128);
        if((tid&127)==0) mbar_arrive(sb+W_BAR+144);
        mbar_wait(E0,e0); mbar_wait(E0+8,e0); e0^=1;
        if(nsp(rbk)==NS1) red_item<32/NS1,NS1>(P,rbk,a,tid); else red_item<32/NS2,NS2>(P,rbk,a,tid);
      } else {
        if(MODE==0||type!=T_QA){
          if(MODE==0||type>=T_M1||(a&3)<2) gemm_item<192,MODE>(P,type,rbk,a,pos,sb,tid,ra,e0,eb,sq); else gemm_item<128,MODE>(P,type,rbk,a,pos,sb,tid,ra,e0,eb,sq);
        } else {
          float acc[192];
          QT(0);
          mainloop<192,0,2>(acc,10,sb,lane,pos);
          QT(1);
          const int sgl=wq>>1, rh=wq&1;
          uint32_t pa[2][20];
          {
            uint32_t q[96];
            float s[2][40];
            QT(2);
            #pragma unroll
            for(int m=0;m<2;m++){
              const uint32_t ks=(pos+10+m)&3;
              const uint32_t dk=((sb+ks*STG)>>4)|(1u<<16);
              #pragma unroll
              for(int i=48*m;i<48*m+48;i++) q[i]=pack_bf16(acc[2*i],acc[2*i+1]);
              mbar_wait(FULL+ks*8,((pos+10+m)>>2)&1);
              #pragma unroll
              for(int i=0;i<40;i++) s[m][i]=0.f;
              wg_arrive();
              #pragma unroll
              for(int T=0;T<12;T++) wgmma_rs<80>(s[m],q+48*m+4*T,dk+(T>>2)*(BOXS/16)+(T&3)*2,T);
              wg_commit();
              wg_wait<0>();
              if(lane==0) mbar_arrive(EMPTY+ks*8);
              QT(3+m);
            }
            const float NEG=rb(-1e9f);
            #pragma unroll
            for(int m=0;m<2;m++){
              float sc[5][4];
              float mx[2]={-3.4e38f,-3.4e38f};
              #pragma unroll
              for(int n=0;n<5;n++)
                #pragma unroll
                for(int i=0;i<4;i+=2){
                  const float u0=n?(sgl?s[m][12+4*n+i]:s[m][4*n-4+i]):(sgl?s[m][36+i]:s[m][32+i]);
                  const float u1=n?(sgl?s[m][13+4*n+i]:s[m][4*n-3+i]):(sgl?s[m][37+i]:s[m][33+i]);
                  const uint32_t r=pack_bf16(u0,u1);
                  const uint32_t w=pack_bf16(__uint_as_float(r<<16)*0.07216878364870322f,__uint_as_float(r&0xffff0000u)*0.07216878364870322f);
                  float v0=__uint_as_float(w<<16), v1=__uint_as_float(w&0xffff0000u);
                  if(n>0){ const int key=8*(n-1)+2*t, row=16*rh+g+4*i; if(key>row) v0=NEG; if(key+1>row) v1=NEG; }
                  sc[n][i]=v0; sc[n][i+1]=v1; mx[i>>1]=fmaxf(mx[i>>1],fmaxf(v0,v1));
                }
              float sum[2]={0.f,0.f};
              #pragma unroll
              for(int r=0;r<2;r++){ mx[r]=fmaxf(mx[r],__shfl_xor_sync(~0u,mx[r],1)); mx[r]=fmaxf(mx[r],__shfl_xor_sync(~0u,mx[r],2)); }
              #pragma unroll
              for(int n=0;n<5;n++)
                #pragma unroll
                for(int i=0;i<4;i++){ const float e=ex2((sc[n][i]-mx[i>>1])*1.4426950408889634f); sc[n][i]=e; sum[i>>1]+=e; }
              #pragma unroll
              for(int r=0;r<2;r++){ sum[r]+=__shfl_xor_sync(~0u,sum[r],1); sum[r]+=__shfl_xor_sync(~0u,sum[r],2); sum[r]=rcp(sum[r]); }
              #pragma unroll
              for(int n=0;n<5;n++){
                const uint32_t p0=pack_bf16(sc[n][0]*sum[0],sc[n][1]*sum[0]), p1=pack_bf16(sc[n][2]*sum[1],sc[n][3]*sum[1]);
                const int o=n?2*(n-1):16, d=n?8:2;
                pa[m][o]=sgl?0u:p0; pa[m][o+1]=sgl?0u:p1; pa[m][o+d]=sgl?p0:0u; pa[m][o+d+1]=sgl?p1:0u;
              }
            }
          }
          QT(5); QT(6);
          const uint32_t dv=((sb+W_SLOT)>>4)|((uint32_t)(BOXS/16)<<16);
          #pragma unroll
          for(int m=0;m<2;m++){
            float o[96];
            #pragma unroll
            for(int i=0;i<96;i++) o[i]=0.f;
            mbar_wait(E0+m*8,e0);
            QT(7+3*m);
            wg_arrive();
            #pragma unroll
            for(int k=0;k<5;k++) wgmma_rs<192>(o,pa[m]+4*k,dv+m*(SLOT/16)+128*k,k);
            wg_commit();
            wg_wait<0>();
            QT(8+3*m);
            bar_sync(8+wg,128);
            { uint32_t p[48];
              #pragma unroll
              for(int i=0;i<48;i++) p[i]=pack_bf16(o[2*i],o[2*i+1]);
              stage_pk<12>(p,ra+m*SLOT,lane); }
            fence_async();
            bar_arrive(sq,160); sq^=1;
            QT(9+3*m);
          }
          e0^=1;
        }
      }
    }
  }
  if(MODE==0) cluster_sync();
}
typedef CUresult (*EncFn)(CUtensorMap*,CUtensorMapDataType,cuuint32_t,void*,const cuuint64_t*,const cuuint64_t*,const cuuint32_t*,const cuuint32_t*,CUtensorMapInterleave,CUtensorMapSwizzle,CUtensorMapL2promotion,CUtensorMapFloatOOBfill);
static CUtensorMap mk2d(const void* base,uint64_t cols,uint64_t rows,uint32_t bc,uint32_t br){
  static EncFn fn=nullptr;
  if(!fn){ void* p=nullptr; cudaDriverEntryPointQueryResult qr; cudaGetDriverEntryPoint("cuTensorMapEncodeTiled",&p,cudaEnableDefault,&qr); fn=(EncFn)p; }
  CUtensorMap m; cuuint64_t gd[2]={cols,rows}; cuuint64_t gs[1]={cols*2}; cuuint32_t bd[2]={bc,br}; cuuint32_t es[2]={1,1};
  fn(&m,CU_TENSOR_MAP_DATA_TYPE_BFLOAT16,2,(void*)base,gd,gs,bd,es,CU_TENSOR_MAP_INTERLEAVE_NONE,CU_TENSOR_MAP_SWIZZLE_128B,CU_TENSOR_MAP_L2_PROMOTION_L2_128B,CU_TENSOR_MAP_FLOAT_OOB_FILL_NONE);
  return m;
}
template<class T> static T* sym(T& s){ void* p; cudaGetSymbolAddress(&p,s); return (T*)p; }
}

int g_reconly=0; int g_kvgrid=132;
extern "C" void kernel_launch(void* const* d_in, const int* in_sizes, int n_in, void* d_out, int out_size) {
  using namespace rk;
  const bf16* x=(const bf16*)d_in[0]; const bf16* mem0=(const bf16*)d_in[1];
  const bf16* Wq=(const bf16*)d_in[2]; const bf16* Wk=(const bf16*)d_in[3]; const bf16* Wv=(const bf16*)d_in[4]; const bf16* Wo=(const bf16*)d_in[5];
  const bf16* w1=(const bf16*)d_in[8]; const bf16* b1=(const bf16*)d_in[9]; const bf16* w2=(const bf16*)d_in[10]; const bf16* b2=(const bf16*)d_in[11];
  cudaStream_t st=cudaStreamPerThread;
  cudaFuncSetAttribute(k_rec,cudaFuncAttributeMaxDynamicSharedMemorySize,SM_TOTAL);
  cudaFuncSetAttribute(k_work<0>,cudaFuncAttributeMaxDynamicSharedMemorySize,W_TOTAL);
  cudaFuncSetAttribute(k_work<1>,cudaFuncAttributeMaxDynamicSharedMemorySize,W_TOTAL);
  bf16* k=(bf16*)sym(g_k); bf16* v=(bf16*)sym(g_v);
  WParams P;
  P.m[M_XN]=mk2d(sym(g_xn),D,S,64,64); P.m[M_Y]=mk2d(sym(g_y),D,S,64,64); P.m[M_H]=mk2d(sym(g_h),F,S,64,64); P.m[M_OX]=mk2d(sym(g_ox),HD,S,64,64);
  P.m[M_K]=mk2d(k,HD,S,64,64); P.m[M_V]=mk2d(v,HD,S,64,64); P.m[M_GATE]=mk2d(sym(g_gate),D,S,64,64);
  P.m[M_WQ]=mk2d(Wq,HD,D,64,64); P.m[M_WK]=mk2d(Wk,HD,D,64,64); P.m[M_WV]=mk2d(Wv,HD,D,64,64);
  P.m[M_W1]=mk2d(w1,F,D,64,64); P.m[M_W2]=mk2d(w2,D,F,64,64); P.m[M_WO]=mk2d(Wo,D,HD,64,64);
  P.m[M_KM]=mk2d(sym(g_km),HD,NSEG*8,64,16); P.m[M_VM]=mk2d(sym(g_vm),HD,NSEG*8,64,16);
  P.x=x; P.b1=b1; P.b2=b2; P.out=(bf16*)d_out;
  k_pre<<<S/8,256,0,st>>>(x,mem0);
  if(!(g_reconly&1)){
    cudaLaunchConfig_t cfg={}; cfg.gridDim=dim3(g_kvgrid); cfg.blockDim=dim3(384); cfg.dynamicSmemBytes=W_TOTAL; cfg.stream=st;
    cudaLaunchAttribute at[2]; at[0].id=cudaLaunchAttributeClusterDimension; at[0].val.clusterDim.x=2; at[0].val.clusterDim.y=1; at[0].val.clusterDim.z=1;
    at[1].id=cudaLaunchAttributeProgrammaticStreamSerialization; at[1].val.programmaticStreamSerializationAllowed=1; cfg.attrs=at; cfg.numAttrs=2;
    cudaLaunchKernelEx(&cfg,k_work<0>,P);
  }
  if(!(g_reconly&4)){
    cudaLaunchConfig_t cfg={}; cfg.gridDim=dim3(NCTA); cfg.blockDim=dim3(256); cfg.dynamicSmemBytes=SM_TOTAL; cfg.stream=st;
    cudaLaunchAttribute at[2]; at[0].id=cudaLaunchAttributeClusterDimension; at[0].val.clusterDim.x=3; at[0].val.clusterDim.y=1; at[0].val.clusterDim.z=1;
    at[1].id=cudaLaunchAttributeProgrammaticStreamSerialization; at[1].val.programmaticStreamSerializationAllowed=1; cfg.attrs=at; cfg.numAttrs=2;
    CUtensorMap tk=mk2d(k,HD,S,64,32), tv=mk2d(v,HD,S,64,32);
    cudaLaunchKernelEx(&cfg,k_rec,tk,tv,Wq,Wk,Wv,Wo);
  }
  if(!(g_reconly&2)){
    cudaLaunchConfig_t cfg={}; cfg.gridDim=dim3(132); cfg.blockDim=dim3(384); cfg.dynamicSmemBytes=W_TOTAL; cfg.stream=st;
    cudaLaunchAttribute at[1]; at[0].id=cudaLaunchAttributeProgrammaticStreamSerialization; at[0].val.programmaticStreamSerializationAllowed=1; cfg.attrs=at; cfg.numAttrs=PDL;
    cudaLaunchKernelEx(&cfg,k_work<1>,P);
  }
}
```

```cpp
#include <cuda_runtime.h>
#include <cuda_bf16.h>
#include <stdint.h>
#include <cuda.h>

namespace rk {
typedef __nv_bfloat16 bf16;
constexpr int S=2048, D=640, H=32, DH=192, HD=6144, NSEG=64, F=1536;
constexpr uint32_t SENT=0xFFFFFFFFu;
#define GUARDN 400000
constexpr int GUARD=GUARDN;
#define RCOPY 2
constexpr int NCTA=96;

__device__ __align__(128) bf16 g_xn[S*D];
__device__ __align__(128) bf16 g_y[S*D];
__device__ __align__(128) bf16 g_h[S*F];
__device__ __align__(128) bf16 g_gate[S*D];
__device__ __align__(128) bf16 g_k[(size_t)S*HD];
__device__ __align__(128) bf16 g_v[(size_t)S*HD];
__device__ __align__(128) bf16 g_km[NSEG*8*HD];
__device__ __align__(128) bf16 g_vm[NSEG*8*HD];
__device__ __align__(128) uint32_t g_flag[NCTA*32];
__device__ __align__(128) bf16 g_ox[(size_t)S*HD];
#define RBL 12
#define NS1 4
#define NS2 16
#define PRIO(br) (((br)>>T_M2)? T_M2+__ffs((br)>>T_M2)-1 : __ffs(br)-1)
__host__ __device__ constexpr int nsp(int rb){ return rb<RBL?1:(rb<15?NS1:NS2); }
__host__ __device__ constexpr int opp_base(int rb){ return rb<=RBL?0:(rb-RBL)*NS1*20480; }
__device__ __align__(128) float4 g_opp[(size_t)(opp_base(15)+NS2*20480)];
constexpr int C_NEXT=0, C_OP=256, C_M2=288, C_M1=320, C_KV=352, C_QA=384, C_NUM=640;
__device__ __align__(128) uint32_t g_cnt[C_NUM];
#define PDL 1
__device__ __align__(128) uint32_t g_mem[(NSEG+1)*RCOPY*80*32];
__device__ __align__(128) uint32_t g_part[80*32*64];
__device__ int g_err;
__device__ unsigned long long g_gt[128*4];
#define GT(i) do{ if(threadIdx.x==0){ unsigned long long g0; asm volatile("mov.u64 %0, %%globaltimer;":"=l"(g0)); g_gt[blockIdx.x*4+(i)]=g0; } }while(0)

__device__ __forceinline__ float rb(float x){ return __bfloat162float(__float2bfloat16(x)); }
__device__ __forceinline__ uint32_t pack_bf16(float lo,float hi){ uint32_t r; asm("cvt.rn.bf16x2.f32 %0, %1, %2;":"=r"(r):"f"(hi),"f"(lo)); return r; }
__device__ __forceinline__ uint32_t movm(uint32_t a){ uint32_t d; asm volatile("movmatrix.sync.aligned.m8n8.trans.b16 %0, %1;":"=r"(d):"r"(a)); return d; }
__device__ __forceinline__ uint4 ldg_rlx4(const uint32_t* p){ uint4 v; asm volatile("ld.relaxed.gpu.global.v4.u32 {%0,%1,%2,%3}, [%4];":"=r"(v.x),"=r"(v.y),"=r"(v.z),"=r"(v.w):"l"(p):"memory"); return v; }
__device__ __forceinline__ void stg_rlx1(uint32_t* p,uint32_t a){ asm volatile("st.relaxed.gpu.global.u32 [%0], %1;"::"l"(p),"r"(a):"memory"); }
__device__ __forceinline__ void stg_rlx2(uint32_t* p,uint32_t a,uint32_t b){ asm volatile("st.relaxed.gpu.global.v2.u32 [%0], {%1,%2};"::"l"(p),"r"(a),"r"(b):"memory"); }
__device__ __forceinline__ void bar_sync(int id,int n){ asm volatile("bar.sync %0, %1;"::"r"(id),"r"(n):"memory"); }
__device__ __forceinline__ void bar_arrive(int id,int n){ asm volatile("bar.arrive %0, %1;"::"r"(id),"r"(n):"memory"); }
__device__ __forceinline__ void mma16816(float* d,const uint32_t* a,uint32_t b0,uint32_t b1){
  asm volatile("mma.sync.aligned.m16n8k16.row.col.f32.bf16.bf16.f32 {%0,%1,%2,%3},{%4,%5,%6,%7},{%8,%9},{%0,%1,%2,%3};"
   :"+f"(d[0]),"+f"(d[1]),"+f"(d[2]),"+f"(d[3]):"r"(a[0]),"r"(a[1]),"r"(a[2]),"r"(a[3]),"r"(b0),"r"(b1));
}
__device__ __forceinline__ void mma1688(float* d,uint32_t a0,uint32_t a1,uint32_t b0){
  asm volatile("mma.sync.aligned.m16n8k8.row.col.f32.bf16.bf16.f32 {%0,%1,%2,%3},{%4,%5},{%6},{%0,%1,%2,%3};"
   :"+f"(d[0]),"+f"(d[1]),"+f"(d[2]),"+f"(d[3]):"r"(a0),"r"(a1),"r"(b0));
}
__device__ __forceinline__ void ldsm4t(uint32_t* r,uint32_t addr){ asm volatile("ldmatrix.sync.aligned.m8n8.x4.trans.shared.b16 {%0,%1,%2,%3}, [%4];":"=r"(r[0]),"=r"(r[1]),"=r"(r[2]),"=r"(r[3]):"r"(addr):"memory"); }
__device__ __forceinline__ void ldsm4(uint32_t* r,uint32_t addr){ asm volatile("ldmatrix.sync.aligned.m8n8.x4.shared.b16 {%0,%1,%2,%3}, [%4];":"=r"(r[0]),"=r"(r[1]),"=r"(r[2]),"=r"(r[3]):"r"(addr):"memory"); }
__device__ __forceinline__ void stsm4(uint32_t a,uint32_t r0,uint32_t r1,uint32_t r2,uint32_t r3){ asm volatile("stmatrix.sync.aligned.m8n8.x4.shared.b16 [%0], {%1,%2,%3,%4};"::"r"(a),"r"(r0),"r"(r1),"r"(r2),"r"(r3):"memory"); }
__device__ __forceinline__ void stsm2(uint32_t a,uint32_t r0,uint32_t r1){ asm volatile("stmatrix.sync.aligned.m8n8.x2.shared.b16 [%0], {%1,%2};"::"r"(a),"r"(r0),"r"(r1):"memory"); }
__device__ __forceinline__ void cp16(uint32_t dst,const void* src){ asm volatile("cp.async.cg.shared.global [%0], [%1], 16;"::"r"(dst),"l"(src):"memory"); }
__device__ __forceinline__ void cp_wait_all(){ asm volatile("cp.async.wait_all;":::"memory"); }
__device__ __forceinline__ void fence_async(){ asm volatile("fence.proxy.async.shared::cta;":::"memory"); }
__device__ __forceinline__ void sts4f(uint32_t a,const float* v){ asm volatile("st.shared.v4.f32 [%0], {%1,%2,%3,%4};"::"r"(a),"f"(v[0]),"f"(v[1]),"f"(v[2]),"f"(v[3]):"memory"); }
__device__ __forceinline__ void sts4(uint32_t a,uint4 v){ asm volatile("st.shared.v4.u32 [%0], {%1,%2,%3,%4};"::"r"(a),"r"(v.x),"r"(v.y),"r"(v.z),"r"(v.w):"memory"); }
__device__ __forceinline__ void sts4r(uint32_t a,const uint32_t* v){ asm volatile("st.shared.v4.u32 [%0], {%1,%2,%3,%4};"::"r"(a),"r"(v[0]),"r"(v[1]),"r"(v[2]),"r"(v[3]):"memory"); }
__device__ __forceinline__ void sts2(uint32_t a,uint32_t x,uint32_t y){ asm volatile("st.shared.v2.u32 [%0], {%1,%2};"::"r"(a),"r"(x),"r"(y):"memory"); }
__device__ __forceinline__ float4 lds4f(uint32_t a){ float4 v; asm volatile("ld.shared.v4.f32 {%0,%1,%2,%3}, [%4];":"=f"(v.x),"=f"(v.y),"=f"(v.z),"=f"(v.w):"r"(a):"memory"); return v; }
__device__ __forceinline__ float2 lds2f(uint32_t a){ float2 v; asm volatile("ld.shared.v2.f32 {%0,%1}, [%2];":"=f"(v.x),"=f"(v.y):"r"(a):"memory"); return v; }
__device__ __forceinline__ uint4 lds4(uint32_t a){ uint4 v; asm volatile("ld.shared.v4.u32 {%0,%1,%2,%3}, [%4];":"=r"(v.x),"=r"(v.y),"=r"(v.z),"=r"(v.w):"r"(a):"memory"); return v; }
__device__ __forceinline__ void lds4r(uint32_t* r,uint32_t a){ asm volatile("ld.shared.v4.u32 {%0,%1,%2,%3}, [%4];":"=r"(r[0]),"=r"(r[1]),"=r"(r[2]),"=r"(r[3]):"r"(a):"memory"); }
__device__ __forceinline__ uint2 lds2(uint32_t a){ uint2 v; asm volatile("ld.shared.v2.u32 {%0,%1}, [%2];":"=r"(v.x),"=r"(v.y):"r"(a):"memory"); return v; }
__device__ __forceinline__ float ex2(float x){ float r; asm("ex2.approx.ftz.f32 %0, %1;":"=f"(r):"f"(x)); return r; }
__device__ __forceinline__ float rcp(float x){ float r; asm("rcp.approx.ftz.f32 %0, %1;":"=f"(r):"f"(x)); return r; }
__device__ __forceinline__ void mbar_init(uint32_t a,int n){ asm volatile("mbarrier.init.shared.b64 [%0], %1;"::"r"(a),"r"(n):"memory"); }
__device__ __forceinline__ void mbar_expect(uint32_t a,int bytes){ asm volatile("mbarrier.arrive.expect_tx.shared.b64 _, [%0], %1;"::"r"(a),"r"(bytes):"memory"); }
__device__ __forceinline__ void mbar_arrive(uint32_t a){ asm volatile("mbarrier.arrive.shared.b64 _, [%0];"::"r"(a):"memory"); }
__device__ __forceinline__ bool mbar_try(uint32_t a,uint32_t par){ uint32_t ok; asm volatile("{\n.reg .pred p;\nmbarrier.try_wait.parity.shared.b64 p, [%1], %2;\nselp.u32 %0,1,0,p;\n}":"=r"(ok):"r"(a),"r"(par):"memory"); return ok; }
__device__ __forceinline__ bool mbar_try_cl(uint32_t a,uint32_t par){ uint32_t ok; asm volatile("{\n.reg .pred p;\nmbarrier.try_wait.parity.acquire.cluster.shared::cta.b64 p, [%1], %2;\nselp.u32 %0,1,0,p;\n}":"=r"(ok):"r"(a),"r"(par):"memory"); return ok; }
__device__ __forceinline__ void bulk_g2s(uint32_t dst,const void* src,int bytes,uint32_t mb){ asm volatile("cp.async.bulk.shared::cluster.global.mbarrier::complete_tx::bytes [%0], [%1], %2, [%3];"::"r"(dst),"l"(src),"r"(bytes),"r"(mb):"memory"); }
__device__ __forceinline__ uint32_t mapa(uint32_t a,uint32_t r){ uint32_t d; asm("mapa.shared::cluster.u32 %0, %1, %2;":"=r"(d):"r"(a),"r"(r)); return d; }
__device__ __forceinline__ void st_async2(uint32_t ra,uint32_t x,uint32_t y,uint32_t rmb){ asm volatile("st.async.weak.shared::cluster.mbarrier::complete_tx::bytes.v2.b32 [%0], {%1,%2}, [%3];"::"r"(ra),"r"(x),"r"(y),"r"(rmb):"memory"); }
__device__ __forceinline__ void st_async4(uint32_t ra,uint32_t x,uint32_t y,uint32_t z,uint32_t w,uint32_t rmb){ asm volatile("st.async.weak.shared::cluster.mbarrier::complete_tx::bytes.v4.b32 [%0], {%1,%2,%3,%4}, [%5];"::"r"(ra),"r"(x),"r"(y),"r"(z),"r"(w),"r"(rmb):"memory"); }
__device__ __forceinline__ void stg_rlx4(uint32_t* p,uint32_t a,uint32_t b,uint32_t c,uint32_t d){ asm volatile("st.relaxed.gpu.global.v4.u32 [%0], {%1,%2,%3,%4};"::"l"(p),"r"(a),"r"(b),"r"(c),"r"(d):"memory"); }
__device__ __forceinline__ void cluster_sync(){ asm volatile("barrier.cluster.arrive.release.aligned;\nbarrier.cluster.wait.acquire.aligned;":::"memory"); }
__device__ __forceinline__ uint32_t ld_acq(const uint32_t* p){ uint32_t v; asm volatile("ld.acquire.gpu.global.u32 %0, [%1];":"=r"(v):"l"(p):"memory"); return v; }
__device__ __forceinline__ void fence_async_all(){ asm volatile("fence.proxy.async;":::"memory"); }
__device__ __forceinline__ void fence_gpu(){ asm volatile("fence.acq_rel.gpu;":::"memory"); }

template<int NL,class V,class LDF,class OKF>
__device__ __forceinline__ int poll1(V* u,LDF ld,OKF ok,bool& dead,int code){
  #pragma unroll
  for(int i=0;i<NL;i++) u[i]=ld(i);
  int guard=0;
  while(true){
    bool f[NL]; bool a=true;
    #pragma unroll
    for(int i=0;i<NL;i++){ f[i]=ok(u[i]); a=a&&f[i]; }
    if(__all_sync(~0u,a)||dead) break;
    #pragma unroll
    for(int i=0;i<NL;i++) if(!f[i]) u[i]=ld(i);
    if(++guard>GUARD){ dead=true; g_err=code; }
  }
  return guard;
}
template<int NL,class V,class LDF,class OKF>
__device__ __forceinline__ int poll2(V* u,LDF ld,OKF ok,bool& dead,int code){
  int guard=0;
  while(true){
    bool f[NL]; bool a=true;
    #pragma unroll
    for(int i=0;i<NL;i++){ f[i]=ok(u[i]); a=a&&f[i]; }
    if(__all_sync(~0u,a)||dead) break;
    #pragma unroll
    for(int i=0;i<NL;i++) if(!f[i]) u[i]=ld(i);
    if(++guard>GUARD){ dead=true; g_err=code; }
  }
  return guard;
}
__device__ __forceinline__ void spin(uint32_t n){ uint32_t t0,t1; asm volatile("mov.u32 %0, %%clock;":"=r"(t0)); do{ asm volatile("mov.u32 %0, %%clock;":"=r"(t1)); }while(t1-t0<n); }
template<int N> __device__ __forceinline__ void wgmma(float* d,uint32_t da,uint32_t db,int sc);
template<int N> __device__ __forceinline__ void wgmma_rs(float* d,const uint32_t* a,uint32_t db,int sc);
template<> __device__ __forceinline__ void wgmma<128>(float* d,uint32_t da,uint32_t db,int sc){
  asm volatile("{\n.reg .pred p;\n.reg .b64 xa, xb;\nmov.b64 xa, {%64, 0x40000040};\nmov.b64 xb, {%65, 0x40000040};\nsetp.ne.b32 p, %66, 0;\nwgmma.mma_async.sync.aligned.m64n128k16.f32.bf16.bf16 {%0,%1,%2,%3,%4,%5,%6,%7,%8,%9,%10,%11,%12,%13,%14,%15,%16,%17,%18,%19,%20,%21,%22,%23,%24,%25,%26,%27,%28,%29,%30,%31,%32,%33,%34,%35,%36,%37,%38,%39,%40,%41,%42,%43,%44,%45,%46,%47,%48,%49,%50,%51,%52,%53,%54,%55,%56,%57,%58,%59,%60,%61,%62,%63}, xa, xb, p, 1, 1, 0, 1;\n}"
   :"+f"(d[0]),"+f"(d[1]),"+f"(d[2]),"+f"(d[3]),"+f"(d[4]),"+f"(d[5]),"+f"(d[6]),"+f"(d[7]),"+f"(d[8]),"+f"(d[9]),"+f"(d[10]),"+f"(d[11]),"+f"(d[12]),"+f"(d[13]),"+f"(d[14]),"+f"(d[15]),"+f"(d[16]),"+f"(d[17]),"+f"(d[18]),"+f"(d[19]),"+f"(d[20]),"+f"(d[21]),"+f"(d[22]),"+f"(d[23]),"+f"(d[24]),"+f"(d[25]),"+f"(d[26]),"+f"(d[27]),"+f"(d[28]),"+f"(d[29]),"+f"(d[30]),"+f"(d[31]),"+f"(d[32]),"+f"(d[33]),"+f"(d[34]),"+f"(d[35]),"+f"(d[36]),"+f"(d[37]),"+f"(d[38]),"+f"(d[39]),"+f"(d[40]),"+f"(d[41]),"+f"(d[42]),"+f"(d[43]),"+f"(d[44]),"+f"(d[45]),"+f"(d[46]),"+f"(d[47]),"+f"(d[48]),"+f"(d[49]),"+f"(d[50]),"+f"(d[51]),"+f"(d[52]),"+f"(d[53]),"+f"(d[54]),"+f"(d[55]),"+f"(d[56]),"+f"(d[57]),"+f"(d[58]),"+f"(d[59]),"+f"(d[60]),"+f"(d[61]),"+f"(d[62]),"+f"(d[63]):"r"(da),"r"(db),"r"(sc));
}
template<> __device__ __forceinline__ void wgmma<192>(float* d,uint32_t da,uint32_t db,int sc){
  asm volatile("{\n.reg .pred p;\n.reg .b64 xa, xb;\nmov.b64 xa, {%96, 0x40000040};\nmov.b64 xb, {%97, 0x40000040};\nsetp.ne.b32 p, %98, 0;\nwgmma.mma_async.sync.aligned.m64n192k16.f32.bf16.bf16 {%0,%1,%2,%3,%4,%5,%6,%7,%8,%9,%10,%11,%12,%13,%14,%15,%16,%17,%18,%19,%20,%21,%22,%23,%24,%25,%26,%27,%28,%29,%30,%31,%32,%33,%34,%35,%36,%37,%38,%39,%40,%41,%42,%43,%44,%45,%46,%47,%48,%49,%50,%51,%52,%53,%54,%55,%56,%57,%58,%59,%60,%61,%62,%63,%64,%65,%66,%67,%68,%69,%70,%71,%72,%73,%74,%75,%76,%77,%78,%79,%80,%81,%82,%83,%84,%85,%86,%87,%88,%89,%90,%91,%92,%93,%94,%95}, xa, xb, p, 1, 1, 0, 1;\n}"
   :"+f"(d[0]),"+f"(d[1]),"+f"(d[2]),"+f"(d[3]),"+f"(d[4]),"+f"(d[5]),"+f"(d[6]),"+f"(d[7]),"+f"(d[8]),"+f"(d[9]),"+f"(d[10]),"+f"(d[11]),"+f"(d[12]),"+f"(d[13]),"+f"(d[14]),"+f"(d[15]),"+f"(d[16]),"+f"(d[17]),"+f"(d[18]),"+f"(d[19]),"+f"(d[20]),"+f"(d[21]),"+f"(d[22]),"+f"(d[23]),"+f"(d[24]),"+f"(d[25]),"+f"(d[26]),"+f"(d[27]),"+f"(d[28]),"+f"(d[29]),"+f"(d[30]),"+f"(d[31]),"+f"(d[32]),"+f"(d[33]),"+f"(d[34]),"+f"(d[35]),"+f"(d[36]),"+f"(d[37]),"+f"(d[38]),"+f"(d[39]),"+f"(d[40]),"+f"(d[41]),"+f"(d[42]),"+f"(d[43]),"+f"(d[44]),"+f"(d[45]),"+f"(d[46]),"+f"(d[47]),"+f"(d[48]),"+f"(d[49]),"+f"(d[50]),"+f"(d[51]),"+f"(d[52]),"+f"(d[53]),"+f"(d[54]),"+f"(d[55]),"+f"(d[56]),"+f"(d[57]),"+f"(d[58]),"+f"(d[59]),"+f"(d[60]),"+f"(d[61]),"+f"(d[62]),"+f"(d[63]),"+f"(d[64]),"+f"(d[65]),"+f"(d[66]),"+f"(d[67]),"+f"(d[68]),"+f"(d[69]),"+f"(d[70]),"+f"(d[71]),"+f"(d[72]),"+f"(d[73]),"+f"(d[74]),"+f"(d[75]),"+f"(d[76]),"+f"(d[77]),"+f"(d[78]),"+f"(d[79]),"+f"(d[80]),"+f"(d[81]),"+f"(d[82]),"+f"(d[83]),"+f"(d[84]),"+f"(d[85]),"+f"(d[86]),"+f"(d[87]),"+f"(d[88]),"+f"(d[89]),"+f"(d[90]),"+f"(d[91]),"+f"(d[92]),"+f"(d[93]),"+f"(d[94]),"+f"(d[95]):"r"(da),"r"(db),"r"(sc));
}
template<> __device__ __forceinline__ void wgmma_rs<80>(float* d,const uint32_t* a,uint32_t db,int sc){
  asm volatile("{\n.reg .pred p;\n.reg .b64 xb;\nmov.b64 xb, {%44, 0x40000040};\nsetp.ne.b32 p, %45, 0;\nwgmma.mma_async.sync.aligned.m64n80k16.f32.bf16.bf16 {%0,%1,%2,%3,%4,%5,%6,%7,%8,%9,%10,%11,%12,%13,%14,%15,%16,%17,%18,%19,%20,%21,%22,%23,%24,%25,%26,%27,%28,%29,%30,%31,%32,%33,%34,%35,%36,%37,%38,%39}, {%40,%41,%42,%43}, xb, p, 1, 1, 0;\n}"
   :"+f"(d[0]),"+f"(d[1]),"+f"(d[2]),"+f"(d[3]),"+f"(d[4]),"+f"(d[5]),"+f"(d[6]),"+f"(d[7]),"+f"(d[8]),"+f"(d[9]),"+f"(d[10]),"+f"(d[11]),"+f"(d[12]),"+f"(d[13]),"+f"(d[14]),"+f"(d[15]),"+f"(d[16]),"+f"(d[17]),"+f"(d[18]),"+f"(d[19]),"+f"(d[20]),"+f"(d[21]),"+f"(d[22]),"+f"(d[23]),"+f"(d[24]),"+f"(d[25]),"+f"(d[26]),"+f"(d[27]),"+f"(d[28]),"+f"(d[29]),"+f"(d[30]),"+f"(d[31]),"+f"(d[32]),"+f"(d[33]),"+f"(d[34]),"+f"(d[35]),"+f"(d[36]),"+f"(d[37]),"+f"(d[38]),"+f"(d[39]):"r"(a[0]),"r"(a[1]),"r"(a[2]),"r"(a[3]),"r"(db),"r"(sc));
}
template<> __device__ __forceinline__ void wgmma_rs<192>(float* d,const uint32_t* a,uint32_t db,int sc){
  asm volatile("{\n.reg .pred p;\n.reg .b64 xb;\nmov.b64 xb, {%100, 0x40000040};\nsetp.ne.b32 p, %101, 0;\nwgmma.mma_async.sync.aligned.m64n192k16.f32.bf16.bf16 {%0,%1,%2,%3,%4,%5,%6,%7,%8,%9,%10,%11,%12,%13,%14,%15,%16,%17,%18,%19,%20,%21,%22,%23,%24,%25,%26,%27,%28,%29,%30,%31,%32,%33,%34,%35,%36,%37,%38,%39,%40,%41,%42,%43,%44,%45,%46,%47,%48,%49,%50,%51,%52,%53,%54,%55,%56,%57,%58,%59,%60,%61,%62,%63,%64,%65,%66,%67,%68,%69,%70,%71,%72,%73,%74,%75,%76,%77,%78,%79,%80,%81,%82,%83,%84,%85,%86,%87,%88,%89,%90,%91,%92,%93,%94,%95}, {%96,%97,%98,%99}, xb, p, 1, 1, 1;\n}"
   :"+f"(d[0]),"+f"(d[1]),"+f"(d[2]),"+f"(d[3]),"+f"(d[4]),"+f"(d[5]),"+f"(d[6]),"+f"(d[7]),"+f"(d[8]),"+f"(d[9]),"+f"(d[10]),"+f"(d[11]),"+f"(d[12]),"+f"(d[13]),"+f"(d[14]),"+f"(d[15]),"+f"(d[16]),"+f"(d[17]),"+f"(d[18]),"+f"(d[19]),"+f"(d[20]),"+f"(d[21]),"+f"(d[22]),"+f"(d[23]),"+f"(d[24]),"+f"(d[25]),"+f"(d[26]),"+f"(d[27]),"+f"(d[28]),"+f"(d[29]),"+f"(d[30]),"+f"(d[31]),"+f"(d[32]),"+f"(d[33]),"+f"(d[34]),"+f"(d[35]),"+f"(d[36]),"+f"(d[37]),"+f"(d[38]),"+f"(d[39]),"+f"(d[40]),"+f"(d[41]),"+f"(d[42]),"+f"(d[43]),"+f"(d[44]),"+f"(d[45]),"+f"(d[46]),"+f"(d[47]),"+f"(d[48]),"+f"(d[49]),"+f"(d[50]),"+f"(d[51]),"+f"(d[52]),"+f"(d[53]),"+f"(d[54]),"+f"(d[55]),"+f"(d[56]),"+f"(d[57]),"+f"(d[58]),"+f"(d[59]),"+f"(d[60]),"+f"(d[61]),"+f"(d[62]),"+f"(d[63]),"+f"(d[64]),"+f"(d[65]),"+f"(d[66]),"+f"(d[67]),"+f"(d[68]),"+f"(d[69]),"+f"(d[70]),"+f"(d[71]),"+f"(d[72]),"+f"(d[73]),"+f"(d[74]),"+f"(d[75]),"+f"(d[76]),"+f"(d[77]),"+f"(d[78]),"+f"(d[79]),"+f"(d[80]),"+f"(d[81]),"+f"(d[82]),"+f"(d[83]),"+f"(d[84]),"+f"(d[85]),"+f"(d[86]),"+f"(d[87]),"+f"(d[88]),"+f"(d[89]),"+f"(d[90]),"+f"(d[91]),"+f"(d[92]),"+f"(d[93]),"+f"(d[94]),"+f"(d[95]):"r"(a[0]),"r"(a[1]),"r"(a[2]),"r"(a[3]),"r"(db),"r"(sc));
}
__global__ void __launch_bounds__(256) k_pre(const bf16* __restrict__ x,const bf16* __restrict__ mem0){
  const int warp=threadIdx.x>>5, lane=threadIdx.x&31;
  const int row=blockIdx.x*8+warp;
  asm volatile("griddepcontrol.launch_dependents;");
  {
    int i=blockIdx.x*256+threadIdx.x; int n=gridDim.x*256;
    for(int k=i;k<(NSEG+1)*RCOPY*80*32;k+=n){
      uint32_t v=SENT;
      if(k<RCOPY*80*32){ int fb=(k%2560)>>5, r=(k>>2)&7, w=k&3; const uint16_t* mp=(const uint16_t*)mem0+r*D+(fb>>1)*16+(fb&1)*4+w; v=mp[0]|((uint32_t)mp[8]<<16);
        if(v==SENT) v=0x7FFF7FFFu; }
      g_mem[k]=v;
    }
    if(i==0) g_err=0;
    if(i<NCTA*32) g_flag[i]=0;
    if(i<C_NUM) g_cnt[i]=0;
  }
  float v[20];
  {
    const uint32_t* p=(const uint32_t*)(x+(size_t)row*D);
    #pragma unroll
    for(int i=0;i<10;i++){ uint32_t u=p[lane+32*i]; v[2*i]=__uint_as_float(u<<16); v[2*i+1]=__uint_as_float(u&0xffff0000u); }
  }
  #pragma unroll
  for(int pass=0;pass<2;pass++){
    float s=0;
    #pragma unroll
    for(int i=0;i<20;i++) s+=v[i];
    #pragma unroll
    for(int o=16;o;o>>=1) s+=__shfl_xor_sync(~0u,s,o);
    float mean=s*(1.f/D);
    float q=0;
    #pragma unroll
    for(int i=0;i<20;i++){ float d=v[i]-mean; q+=d*d; }
    #pragma unroll
    for(int o=16;o;o>>=1) q+=__shfl_xor_sync(~0u,q,o);
    float var=rb(q*(1.f/D)), mb=rb(mean);
    float den=rb(sqrtf(rb(var+1e-5f)));
    uint32_t* o=(uint32_t*)((pass?g_y:g_xn)+(size_t)row*D);
    #pragma unroll
    for(int i=0;i<10;i++){
      float a=rb(rb(v[2*i]-mb)/den), b=rb(rb(v[2*i+1]-mb)/den);
      v[2*i]=a; v[2*i+1]=b;
      o[lane+32*i]=pack_bf16(a,b);
    }
  }
}

#define RPOS 11
#define ADELAY 300
#define KP 4
#define UXP 16
#define OPF 99
#define RDELAY 400
#define BDELAY 0
#define MSPLIT 0
constexpr int SM_QS=0;
constexpr int SM_KS=49152;
constexpr int SM_OS=131072;
constexpr int SM_RED=180224;
constexpr int SM_P=SM_RED+3584;
constexpr int SM_PM=SM_RED+4096+3584;
constexpr int SM_MB=SM_PM+128;
constexpr int SM_RSUM=SM_RED+8192+3584;
constexpr int SM_KX=SM_RED+16384;
constexpr int SM_VX=SM_KX+4096;
constexpr int SM_SCX=SM_VX+14336;
constexpr int SM_KRED=SM_SCX+6144;
constexpr int SM_VMX=SM_KRED+8192;
constexpr int SM_TOTAL=SM_VMX+3072;
static_assert(SM_TOTAL<=232448,"smem");
__device__ __forceinline__ void wg32_rs(float* d,const uint32_t* a,uint32_t db){
  asm volatile("{\n.reg .b64 xb;\nmov.b64 xb, {%20, 0x40000040};\nwgmma.mma_async.sync.aligned.m64n32k16.f32.bf16.bf16 {%0,%1,%2,%3,%4,%5,%6,%7,%8,%9,%10,%11,%12,%13,%14,%15}, {%16,%17,%18,%19}, xb, 1, 1, 1, 0;\n}"
   :"+f"(d[0]),"+f"(d[1]),"+f"(d[2]),"+f"(d[3]),"+f"(d[4]),"+f"(d[5]),"+f"(d[6]),"+f"(d[7]),"+f"(d[8]),"+f"(d[9]),"+f"(d[10]),"+f"(d[11]),"+f"(d[12]),"+f"(d[13]),"+f"(d[14]),"+f"(d[15])
   :"r"(a[0]),"r"(a[1]),"r"(a[2]),"r"(a[3]),"r"(db));
}
__device__ __forceinline__ void wg32_rs0(float* d,const uint32_t* a,uint32_t db){
  asm volatile("{\n.reg .b64 xb;\nmov.b64 xb, {%20, 0x40000040};\nwgmma.mma_async.sync.aligned.m64n32k16.f32.bf16.bf16 {%0,%1,%2,%3,%4,%5,%6,%7,%8,%9,%10,%11,%12,%13,%14,%15}, {%16,%17,%18,%19}, xb, 0, 1, 1, 0;\n}"
   :"=f"(d[0]),"=f"(d[1]),"=f"(d[2]),"=f"(d[3]),"=f"(d[4]),"=f"(d[5]),"=f"(d[6]),"=f"(d[7]),"=f"(d[8]),"=f"(d[9]),"=f"(d[10]),"=f"(d[11]),"=f"(d[12]),"=f"(d[13]),"=f"(d[14]),"=f"(d[15])
   :"r"(a[0]),"r"(a[1]),"r"(a[2]),"r"(a[3]),"r"(db));
}
__device__ __forceinline__ void wg32_ss(float* d,uint32_t da,uint32_t db){
  asm volatile("{\n.reg .b64 xa, xb;\nmov.b64 xa, {%16, 0x00000180};\nmov.b64 xb, {%17, 0x40000040};\nwgmma.mma_async.sync.aligned.m64n32k16.f32.bf16.bf16 {%0,%1,%2,%3,%4,%5,%6,%7,%8,%9,%10,%11,%12,%13,%14,%15}, xa, xb, 1, 1, 1, 0, 0;\n}"
   :"+f"(d[0]),"+f"(d[1]),"+f"(d[2]),"+f"(d[3]),"+f"(d[4]),"+f"(d[5]),"+f"(d[6]),"+f"(d[7]),"+f"(d[8]),"+f"(d[9]),"+f"(d[10]),"+f"(d[11]),"+f"(d[12]),"+f"(d[13]),"+f"(d[14]),"+f"(d[15])
   :"r"(da),"r"(db));
}
__device__ __forceinline__ void wg32_ss0(float* d,uint32_t da,uint32_t db){
  asm volatile("{\n.reg .b64 xa, xb;\nmov.b64 xa, {%16, 0x00000180};\nmov.b64 xb, {%17, 0x40000040};\nwgmma.mma_async.sync.aligned.m64n32k16.f32.bf16.bf16 {%0,%1,%2,%3,%4,%5,%6,%7,%8,%9,%10,%11,%12,%13,%14,%15}, xa, xb, 0, 1, 1, 0, 0;\n}"
   :"=f"(d[0]),"=f"(d[1]),"=f"(d[2]),"=f"(d[3]),"=f"(d[4]),"=f"(d[5]),"=f"(d[6]),"=f"(d[7]),"=f"(d[8]),"=f"(d[9]),"=f"(d[10]),"=f"(d[11]),"=f"(d[12]),"=f"(d[13]),"=f"(d[14]),"=f"(d[15])
   :"r"(da),"r"(db));
}
template<int V> struct IC{ static constexpr int v=V; };
__device__ __forceinline__ uint32_t lds1(uint32_t a){ uint32_t v; asm volatile("ld.shared.u32 %0, [%1];":"=r"(v):"r"(a):"memory"); return v; }
__device__ __forceinline__ void sts1(uint32_t a,uint32_t x){ asm volatile("st.shared.u32 [%0], %1;"::"r"(a),"r"(x):"memory"); }

#define TS(i)
#define TSB(i)
#define PC(i) (void)np
#define TW(i)
#define TF(i)
#define TFP(i)

__device__ __forceinline__ void cp_commit(){ asm volatile("cp.async.commit_group;":::"memory"); }
template<int N> __device__ __forceinline__ void cp_wait(){ asm volatile("cp.async.wait_group %0;"::"n"(N):"memory"); }
__device__ __forceinline__ void tma2d(uint32_t dst,const CUtensorMap* tm,int c0,int c1,uint32_t mb){
  asm volatile("cp.async.bulk.tensor.2d.shared::cluster.global.mbarrier::complete_tx::bytes [%0], [%1, {%3, %4}], [%2];"::"r"(dst),"l"(tm),"r"(mb),"r"(c0),"r"(c1):"memory"); }
__device__ __forceinline__ void tma2d_pf(const CUtensorMap* tm,int c0,int c1){
  asm volatile("cp.async.bulk.prefetch.tensor.2d.L2.global [%0, {%1, %2}];"::"l"(tm),"r"(c0),"r"(c1):"memory"); }
__global__ void __launch_bounds__(256,1) k_rec(const __grid_constant__ CUtensorMap tmK,const __grid_constant__ CUtensorMap tmV,const bf16* __restrict__ Wq,const bf16* __restrict__ Wk,const bf16* __restrict__ Wv,const bf16* __restrict__ Wo,const uint32_t zero){
  extern __shared__ __align__(1024) uint8_t sm[];
  const int tid=threadIdx.x, warp=__shfl_sync(~0u,tid>>5,0), lane=tid&31, g=lane>>2, t=lane&3;
  const int b=blockIdx.x, h=b/3, c=b-3*h;
  const uint32_t sb=(uint32_t)__cvta_generic_to_shared(sm);
  const int kq=warp&3, mg=warp>>2, wt=warp-mg;
  const uint32_t s16=sb+lane*16;
  const uint32_t qs=s16+(mg?SM_KS+kq*20480:SM_QS+kq*12288), mo=((lane>>3)&1), os=sb+SM_OS+kq*12288+mo*6144+(lane>>4)*128+(lane&7)*16, us=sb+SM_VX+wt*2048+mo*512+(lane>>4)*128+(lane&7)*16;
  const uint32_t XS=sb+SM_MB, KVB=sb+SM_MB+8, XV=sb+SM_MB+16, XL=sb+SM_MB+24;
  GT(0);
  asm volatile("griddepcontrol.launch_dependents;");
  const int ntile=c==0?14:13, tile0=c==0?0:(1+13*c);
  uint32_t pw[40][4];
  auto ldW=[&](int p,uint32_t stg){
    #pragma unroll
    for(int i=0;i<12;i++){
      const int idx=tid+256*i, row=idx>>3, ch=idx&7, m=row>>7, f=160*((row>>5)&3)+32*p+(row&31);
      const bf16* src=(m==0?Wq:(m==1?Wk:Wv))+(size_t)f*HD+h*DH+64*c+ch*8;
      const int sw=(row>>2)&7;
      cp16(stg+row*128+((ch^sw)<<4),src);
    }
    cp_commit();
  };
  auto ldO=[&](int r,uint32_t stg){
    for(int idx=tid;idx<96*28;idx+=256){
      const int row=idx/28, ch=idx-row*28;
      if(ch<2*ntile) cp16(stg+row*464+ch*16,Wo+(size_t)(h*DH+((4*c+6*r+(row>>4))%12)*16+(row&15))*D+tile0*16+ch*8);
    }
    cp_commit();
  };
  ldW(0,sb+SM_RED);
  #pragma unroll
  for(int p=0;p<5;p++){
    const uint32_t stg=sb+((p&1)?SM_OS:SM_RED), nstg=sb+((p&1)?SM_RED:SM_OS);
    if(p<4) ldW(p+1,nstg); else ldO(0,nstg);
    cp_wait<1>(); __syncthreads();
    #pragma unroll
    for(int e=0;e<2;e++){
      const int k=2*p+e;
      const int fo=16*((lane>>2)&1)+4*((lane>>1)&1)+2*e+(lane>>4)+8*(lane&1);
      const int sw=(fo>>2)&7;
      #pragma unroll
      for(int j=0;j<4;j++){
        const uint32_t a=stg+((mg*4+kq)*32+fo)*128+(((2*j+((lane>>3)&1))^sw)<<4);
        if(mg?k<10-KP:k<6){ uint32_t r[4]; ldsm4t(r,a); sts4r(qs+(k*4+j)*512,r); }
        else if(!mg) ldsm4t(pw[k>=6?(k-6)*4+j:0],a);
        else ldsm4t(pw[k>=10-KP?(k-10+KP)*4+j:0],a);
        if(mg){
          const int u=k*4+j;
          const uint32_t av=stg+((8+kq)*32+fo)*128+(((2*((j+kq)&3)+((lane>>3)&1))^sw)<<4);
          if(u<4*KP){ uint32_t r[4]; ldsm4t(r,av); sts4r(qs+(40-4*KP+u)*512,r); } else ldsm4t(pw[u],av);
        }
      }
    }
    __syncthreads();
  }
  #pragma unroll
  for(int r=0;r<2;r++){
    const uint32_t stg=sb+(r?SM_RED:SM_OS);
    if(r==0){ ldO(1,sb+SM_RED); cp_wait<1>(); } else cp_wait<0>();
    __syncthreads();
    uint32_t rr[12][4];
    #pragma unroll
    for(int kk=0;kk<6;kk++){
      #pragma unroll
      for(int i=0;i<2;i++){
        int tl=2*wt+i; if(tl>=ntile) tl=0;
        const uint32_t a=stg+(16*kk+(lane&7)+(lane>>4)*8)*464+(2*tl+((lane>>3)&1))*16;
        if(mg) ldsm4t(rr[kk*2+i],a); else ldsm4t(pw[16+r*12+kk*2+i],a);
      }
    }
    __syncthreads();
    if(mg){
      #pragma unroll
      for(int f=0;f<12;f++) stsm4(os+(r*12+f)*256,rr[f][0],rr[f][1],rr[f][2],rr[f][3]);
    }
  }
  if(tid==96){
    mbar_init(XS,5); mbar_init(KVB,1); mbar_init(XV,1); mbar_init(XL,4);
    asm volatile("fence.mbarrier_init.release.cluster;":::"memory");
    mbar_expect(XS,4096); mbar_expect(XV,2048);
  }
  auto kv_issue=[&](int sn){
    if(lane==0){
      mbar_expect(KVB,32*512);
      tma2d(sb+SM_KX,&tmK,h*DH+64*c,sn*32,KVB);
      #pragma unroll
      for(int i=0;i<3;i++) tma2d(sb+SM_VX+i*4096,&tmV,h*DH+64*i,sn*32,KVB);
    }
    __syncwarp();
  };
  auto kv_chk=[&](int rbk){
    if(lane==0){ int gd=0; while(ld_acq(g_cnt+C_KV+rbk)<64){ if(++gd>GUARD){ g_err=7; break; } } fence_async_all(); }
    __syncwarp();
  };
  auto kv_pf=[&](int sn){
    if(lane==0){ tma2d_pf(&tmK,h*DH+64*c,sn*32); tma2d_pf(&tmV,h*DH+64*c,sn*32); }
    __syncwarp();
  };
  fence_async();
  __syncthreads();
  if(warp==3){ kv_chk(0); kv_issue(0); kv_pf(1); kv_pf(2); }
  cluster_sync();
  const bool isred=(b%6)<5; const int rline=(b/6)*5+(b%6);
  bool dead=false;
  const uint32_t qrd=sb+SM_RED+1024+((lane>>3)&1)*4096+(lane>>4)*128+(lane&7)*16+kq*256;
  uint32_t rsc[2];
  rsc[0]=mapa(sb,c==2?0:c+1); rsc[1]=mapa(sb,c==0?2:c-1);
  GT(1);
  auto loop=[&](auto MGc){
  constexpr int MG=decltype(MGc)::v;
  uint32_t buf[8][4];
  uint32_t tg=3;
  #define MB0(k) (((k)&1)?mv[(k)>>1].z:mv[(k)>>1].x)
  #define MB1(k) (((k)&1)?mv[(k)>>1].w:mv[(k)>>1].y)
  #pragma unroll 1
  for(int s=0;s<NSEG;s++){
    const bool last=s==NSEG-1;
    float u[2][16];
    const bool rduty=isred&&MG&&s;
    const uint32_t* rsrc=(const uint32_t*)((char*)g_part+(uint32_t)(((rline>>1)*32+8*kq+(lane>>4))*512+(rline&1)*256+(lane&15)*16));
    uint4 v[4];
    {
      uint32_t t0; asm volatile("mov.u32 %0, %%clock;":"=r"(t0));
      if(!MG&&warp<3){ uint32_t t1; do{ asm volatile("mov.u32 %0, %%clock;":"=r"(t1)); }while(t1-t0<ADELAY); }
      { int gd=0; while(!mbar_try(KVB,s&1)){ if(dead||last) break; if(++gd>GUARD){ dead=true; g_err=6; } } }
      TFP(16);
      const uint32_t da=(((sb+SM_OS)>>4)&0x3fff)|(8u<<16);
      const uint32_t dv=(((sb+SM_VX)>>4)&0x3fff)|(1u<<16);
      const uint32_t vb[3]={dv+c*256,dv+(c==2?0:c+1)*256,dv+(c==0?2:c-1)*256};
      asm volatile("wgmma.fence.sync.aligned;":::"memory");
      if constexpr(MG){
        #pragma unroll
        for(int i=0;i<2;i++)
          #pragma unroll
          for(int x=0;x<12;x++){
            if(x==0) wg32_ss0(u[i],da+i*16,vb[0]); else wg32_ss(u[i],da+(x*2+i)*16,vb[x>>2]+(x&3)*2);
            if(i*12+x==RPOS){
              TFP(17);
              { uint32_t t1; do{ asm volatile("mov.u32 %0, %%clock;":"=r"(t1)); }while(t1-t0<RDELAY); }
              #pragma unroll
              for(int j=0;j<4;j++) asm volatile("{\n.reg .pred p;\nsetp.ne.b32 p, %5, 0;\nmov.b32 %0, 0;\nmov.b32 %1, 0;\nmov.b32 %2, 0;\nmov.b32 %3, 0;\n@p ld.relaxed.gpu.global.v4.u32 {%0,%1,%2,%3}, [%4];\n}":"=r"(v[j].x),"=r"(v[j].y),"=r"(v[j].z),"=r"(v[j].w):"l"(rsrc+j*256),"r"((int)rduty):"memory");
              asm volatile("wgmma.fence.sync.aligned;":::"memory");
            }
          }
      } else {
        #pragma unroll
        for(int i=0;i<2;i++)
          #pragma unroll
          for(int x=0;x<12;x++){
            if(x==0) wg32_rs0(u[i],pw[16+i],vb[0]); else wg32_rs(u[i],pw[16+x*2+i],vb[x>>2]+(x&3)*2);
          }
      }
      asm volatile("wgmma.commit_group.sync.aligned;":::"memory");
      TFP(18);
    }
    if(rduty){
      uint32_t* mdst=g_mem+(size_t)(s*RCOPY)*2560+rline*32+lane;
      float f[4];
      auto okr=[&](const uint4& v){ return ((((v.x^tg)|(v.y^tg))|((v.z^tg)|(v.w^tg)))&3u)==0; };
      int np=poll2<4>(v,[&](int i){ return ldg_rlx4(rsrc+i*256); },okr,dead,4);
      f[0]=(__uint_as_float(v[0].x)+__uint_as_float(v[1].x))+(__uint_as_float(v[2].x)+__uint_as_float(v[3].x));
      f[1]=(__uint_as_float(v[0].y)+__uint_as_float(v[1].y))+(__uint_as_float(v[2].y)+__uint_as_float(v[3].y));
      f[2]=(__uint_as_float(v[0].z)+__uint_as_float(v[1].z))+(__uint_as_float(v[2].z)+__uint_as_float(v[3].z));
      f[3]=(__uint_as_float(v[0].w)+__uint_as_float(v[1].w))+(__uint_as_float(v[2].w)+__uint_as_float(v[3].w));
      s--; TW(2); TF(14); PC(1); s++;
      #pragma unroll
      for(int i=0;i<4;i++) f[i]+=__shfl_xor_sync(~0u,f[i],16);
      if(lane<16) sts4f(s16+SM_RSUM+(kq>>1)*4096+(kq&1)*256,f);
      if(warp==4){
        bar_sync(5,128);
        s--; TSB(5); s++;
        const float* rp=(const float*)(sm+SM_RSUM)+(lane&3)*16+(lane>>3)*4+((lane>>2)&1);
        float a0=(rp[0]+rp[64])+(rp[1024]+rp[1088]);
        float a1=(rp[2]+rp[66])+(rp[1026]+rp[1090]);
        uint32_t o=pack_bf16(a0,a1); if(o==SENT) o=0x7FFF7FFFu;
        #pragma unroll
        for(int cc=0;cc<RCOPY;cc++) stg_rlx1(mdst+cc*2560,o);
        s--; TSB(6); TW(3); s++;
      } else bar_arrive(5,128);
    }
    tg=tg==3?1:tg+1;
    {
      asm volatile("wgmma.wait_group.sync.aligned 0;":::"memory");
      TFP(19);
      bar_sync(7,256);
      TFP(20);
      if(MG||warp!=3){
        #pragma unroll
        for(int i=0;i<2;i++)
          #pragma unroll
          for(int kk=0;kk<2;kk++)
            stsm4(us+i*1024+kk*256,pack_bf16(u[i][8*kk],u[i][8*kk+1]),pack_bf16(u[i][8*kk+2],u[i][8*kk+3]),pack_bf16(u[i][8*kk+4],u[i][8*kk+5]),pack_bf16(u[i][8*kk+6],u[i][8*kk+7]));
      }
      #pragma unroll
      for(int i=0;i<8;i++) lds4r(buf[i],qs+i*512);
      TFP(15);
    }
    uint4 mv[5];
    {
      const uint32_t* src=(const uint32_t*)((const char*)g_mem+(uint32_t)((s*RCOPY+(b%RCOPY))*10240+(kq*20+t)*128+g*16));
      auto okf=[&](const uint4& v){ return v.x!=SENT&&v.y!=SENT&&v.z!=SENT&&v.w!=SENT; };
      const uint32_t mx=s16+SM_RED+kq*4096;
      if constexpr(MG==0){
        int np=poll1<3>(mv,[&](int i){ return ldg_rlx4(src+i*128); },okf,dead,1);
        TW(0); PC(0);
        #pragma unroll
        for(int p=0;p<3;p++) sts4(mx+(4+p)*512,mv[p]);
        bar_sync(8+kq,64);
        mv[3]=lds4(mx); mv[4]=lds4(mx+512);
      } else {
        int np=poll1<2>(mv+3,[&](int i){ return ldg_rlx4(src+(3+i)*128); },okf,dead,1);
        TW(0); PC(0);
        sts4(mx,mv[3]); sts4(mx+512,mv[4]);
        bar_sync(8+kq,64);
        #pragma unroll
        for(int p=0;p<3;p++) mv[p]=lds4(mx+(4+p)*512);
      }
    }
    TS(0); TF(0);
    float acc[4][4]; uint32_t ux[2][2][4];
    #pragma unroll
    for(int i=0;i<4;i++){ acc[i][0]=acc[i][1]=acc[i][2]=acc[i][3]=0.f; }
    #define UXDEP (((ux[0][0][0]^ux[0][1][0])^(ux[1][0][0]^ux[1][1][0]))&zero)
    const uint32_t exo=(uint32_t)(((s*8+g)*HD+h*DH+64*c+16*kq+2*t)*2);
    if constexpr(MG){
      #pragma unroll
      for(int y=0;y<10;y++){
        const int k=KP==4?(y<2?y:(y<4?y+4:(y<6?y-2:(y<8?y+2:y-4)))):(y<2?y:(y<2+KP?y+8-KP:y-KP));
        #pragma unroll
        for(int j=0;j<4;j++){
          if(k<10-KP){ mma16816(acc[j],buf[(k&1)*4+j],MB0(k),MB1(k)); lds4r(buf[(k&1)*4+j],qs+(k*4+j+8)*512); }
          else mma16816(acc[j],pw[k>=10-KP?(k-10+KP)*4+j:0],MB0(k),MB1(k));
        }
      }
      TF(1);
      {
        const uint32_t ra=s16+SM_KRED+kq*2048;
        #pragma unroll
        for(int i=0;i<4;i++) sts4f(ra+i*512,acc[i]);
      }
      bar_arrive(1,256);
#define VK(u) ((u)>>2)
      #pragma unroll
      for(int i=0;i<4;i++){ acc[i][0]=acc[i][1]=acc[i][2]=acc[i][3]=0.f; }
      #pragma unroll
      for(int y=0;y<40;y++){
        constexpr int NS_=4*KP;
        const int u=y<8?y:(y<20?y-8+NS_:(y<12+NS_?y-12:y));
        const int sl=(u+40-NS_)&7;
        if(u<NS_){ mma16816(acc[u&3],buf[sl],MB0(VK(u)),MB1(VK(u))); if(u+8<NS_) lds4r(buf[sl],qs+(48-NS_+u)*512); }
        else mma16816(acc[u&3],pw[u],MB0(VK(u)),MB1(VK(u)));
        if(y>=OPF&&y<OPF+8) ldsm4(buf[(y-OPF)&7],os+((y-OPF)&7)*256);
        if(y>=UXP&&y<UXP+4) ldsm4(ux[(y-UXP)>>1][(y-UXP)&1],us+((y-UXP)>>1)*1024+((y-UXP)&1)*256);
      }
      TF(2);
      const uint32_t ra=s16+SM_RED+1536;
      #pragma unroll
      for(int i=1;i<4;i++) sts4f(ra+kq*4096+i*512,acc[i]);
      bar_sync(3,128);
      float4 c1=lds4f(ra+((kq+3)&3)*4096+512), d2=lds4f(ra+((kq+2)&3)*4096+1024), e2=lds4f(ra+((kq+1)&3)*4096+1536);
      const uint32_t p0=pack_bf16((acc[0][0]+c1.x)+(d2.x+e2.x),(acc[0][1]+c1.y)+(d2.y+e2.y)), p1=pack_bf16((acc[0][2]+c1.z)+(d2.z+e2.z),(acc[0][3]+c1.w)+(d2.w+e2.w));
      if(!last) bar_arrive(12+UXDEP,256);
      const uint32_t v0=movm(p0), v1=movm(p1);
      const uint32_t off=SM_VMX+(kq>>1)*512+lane*16+(kq&1)*8;
      if(!last){
        #pragma unroll
        for(int r=0;r<2;r++) st_async2(rsc[r]+off+(2-r)*1024,v0,v1,rsc[r]+SM_MB+16);
        sts2(sb+off,v0,v1); __syncwarp(); if(lane==0) mbar_arrive(XL);
      }
      TF(5);
      if(OPF>=40){
        #pragma unroll
        for(int i=0;i<8;i++) ldsm4(buf[i],os+i*256);
      }
      stg_rlx1((uint32_t*)((char*)g_vm+exo),v0); stg_rlx1((uint32_t*)((char*)g_vm+exo+16),v1);
      if(last) break;
    } else {
      uint32_t kb[8];
      #pragma unroll
      for(int y=0;y<10;y++){
        const int k=y<2?y:(y<4?y+4:(y<6?y-2:(y<8?y+2:y-4)));
        #pragma unroll
        for(int j=0;j<4;j++){
          if(k<6){ mma16816(acc[j],buf[(k&1)*4+j],MB0(k),MB1(k)); if(k<4) lds4r(buf[(k&1)*4+j],qs+(k*4+j+8)*512); }
          else mma16816(acc[j],pw[k>=6?(k-6)*4+j:0],MB0(k),MB1(k));
        }
        if(y==7){
          const uint32_t ka=sb+SM_KX+(8*kq+(lane&7))*128+((((lane>>3)^(2*kq))^(lane&7))<<4);
          ldsm4(kb,ka); ldsm4(kb+4,ka^64);
        }
      }
      TF(1);
      {
        const uint32_t qa=s16+SM_RED+kq*4096+1024;
        #pragma unroll
        for(int i=0;i<2;i++) stsm4(qa+i*512,pack_bf16(acc[2*i][0],acc[2*i][1]),pack_bf16(acc[2*i][2],acc[2*i][3]),pack_bf16(acc[2*i+1][0],acc[2*i+1][1]),pack_bf16(acc[2*i+1][2],acc[2*i+1][3]));
      }
      TF(2);
      bar_sync(1,256);
      TS(1); TF(3);
      const uint32_t ra=s16+SM_KRED+kq*512;
      float4 a3=lds4f(ra), c3=lds4f(ra+2048), d3=lds4f(ra+4096), e3=lds4f(ra+6144);
      uint32_t q[4][2][4];
      #pragma unroll
      for(int i=0;i<4;i++){ ldsm4t(q[i][0],qrd^(i*256)); ldsm4t(q[i][1],(qrd^(i*256))+8192); }
      const uint32_t p2=pack_bf16((a3.x+c3.x)+(d3.x+e3.x),(a3.y+c3.y)+(d3.y+e3.y)), p3=pack_bf16((a3.z+c3.z)+(d3.z+e3.z),(a3.w+c3.w)+(d3.w+e3.w));
      const uint32_t f2=movm(p2), f3=movm(p3);
      if(last){ stg_rlx1((uint32_t*)((char*)g_km+exo),f2); stg_rlx1((uint32_t*)((char*)g_km+exo+16),f3); break; }
      float sc[6][4];
      #pragma unroll
      for(int i=0;i<6;i++){ sc[i][0]=sc[i][1]=sc[i][2]=sc[i][3]=0.f; }
      #pragma unroll
      for(int i=0;i<4;i++)
        #pragma unroll
        for(int jp=0;jp<2;jp++){
          mma16816(sc[(i&1)*2+jp],q[i][jp],kb[2*i],kb[2*i+1]);
          if(i==1) mma16816(sc[4+jp],q[0][jp],f2,f3);
        }
      const uint32_t w0=__float_as_uint(((sc[0][0]+sc[0][2])+(sc[1][0]+sc[1][2]))+((sc[2][0]+sc[2][2])+(sc[3][0]+sc[3][2]))), w1=__float_as_uint(((sc[0][1]+sc[0][3])+(sc[1][1]+sc[1][3]))+((sc[2][1]+sc[2][3])+(sc[3][1]+sc[3][3])));
      const uint32_t w2=__float_as_uint((sc[4][0]+sc[4][2])+(sc[5][0]+sc[5][2])), w3=__float_as_uint((sc[4][1]+sc[4][3])+(sc[5][1]+sc[5][3]));
      const uint32_t off=SM_SCX+(c*4+kq)*512+lane*16;
      #pragma unroll
      for(int r=0;r<2;r++) st_async4(rsc[r]+off,w0,w1,w2,w3,rsc[r]+SM_MB);
      sts4(sb+off,make_uint4(w0,w1,w2,w3)); __syncwarp(); if(lane==0) mbar_arrive(XS);
      TS(2); TF(5);
      stg_rlx1((uint32_t*)((char*)g_km+exo),f2); stg_rlx1((uint32_t*)((char*)g_km+exo+16),f3);
    }
    if(!MG&&warp==3){
      uint32_t kvc; asm volatile("ld.relaxed.gpu.global.u32 %0, [%1];":"=r"(kvc):"l"(g_cnt+C_KV+(((s+2)>>2)&15)):"memory");
      bar_arrive(12,256);
      TF(6);
      { int gd=0; while(!mbar_try(XS,s&1)){ if(dead) break; if(++gd>GUARD){ dead=true; g_err=2; } } }
      TF(7);
      float sv[10];
      {
        float4 u[12];
        #pragma unroll
        for(int n=0;n<12;n++) u[n]=lds4f(s16+SM_SCX+n*512);
        uint32_t r[5];
        #pragma unroll
        for(int n=0;n<4;n++) r[n+1]=pack_bf16((u[n].x+u[4+n].x)+u[8+n].x,(u[n].y+u[4+n].y)+u[8+n].y);
        r[0]=pack_bf16((((u[0].z+u[1].z)+(u[2].z+u[3].z))+((u[4].z+u[5].z)+(u[6].z+u[7].z)))+((u[8].z+u[9].z)+(u[10].z+u[11].z)),
                       (((u[0].w+u[1].w)+(u[2].w+u[3].w))+((u[4].w+u[5].w)+(u[6].w+u[7].w)))+((u[8].w+u[9].w)+(u[10].w+u[11].w)));
        #pragma unroll
        for(int n=0;n<5;n++){
          const uint32_t w=pack_bf16(__uint_as_float(r[n]<<16)*0.07216878364870322f,__uint_as_float(r[n]&0xffff0000u)*0.07216878364870322f);
          sv[2*n]=__uint_as_float(w<<16); sv[2*n+1]=__uint_as_float(w&0xffff0000u);
        }
      }
      TF(8);
      float mx=fmaxf(fmaxf(fmaxf(sv[2],sv[3]),fmaxf(sv[4],sv[5])),fmaxf(fmaxf(fmaxf(sv[6],sv[7]),fmaxf(sv[8],sv[9])),fmaxf(sv[0],sv[1])));
      mx=fmaxf(mx,__shfl_xor_sync(~0u,mx,1)); mx=fmaxf(mx,__shfl_xor_sync(~0u,mx,2));
      mx*=-1.4426950408889634f;
      #pragma unroll
      for(int i=0;i<10;i++) sv[i]=ex2(fmaf(sv[i],1.4426950408889634f,mx));
      sts1(sb+SM_PM+lane*4,pack_bf16(sv[0],sv[1]));
      sts4(s16+SM_P,make_uint4(pack_bf16(sv[2],sv[3]),pack_bf16(sv[4],sv[5]),pack_bf16(sv[6],sv[7]),pack_bf16(sv[8],sv[9])));
      TF(9);
      bar_sync(4,256);
      TF(11);
      if((s&3)==3) fence_gpu();
      if(lane==0) stg_rlx1(g_flag+b*32,s+1);
      if((s&3)==2&&s+2<NSEG){ if(kvc<64) kv_chk((s+2)>>2); else { fence_gpu(); fence_async_all(); } }
      TF(12);
      if(lane==0){ mbar_expect(XS,4096); mbar_expect(XV,2048); }
      TF(14);
      if(s+4<NSEG) kv_pf(s+3);
      if(isred&&lane<RCOPY&&s+3<=NSEG) asm volatile("prefetch.global.L2 [%0];"::"l"(g_mem+(size_t)((s+3)*RCOPY+lane)*2560+rline*32));
      TF(13);
    } else {
      if constexpr(!MG){
        #pragma unroll
        for(int i=0;i<2;i++){ ldsm4(ux[i][0],us+i*1024); ldsm4(ux[i][1],us+i*1024+256); }
        bar_sync(12+UXDEP,256);
        if(s+2<NSEG&&lane==0){
          tma2d(sb+SM_VX+kq*4096,&tmV,h*DH+64*kq,(s+1)*32,KVB);
          if(kq==0) mbar_expect(KVB,32*512);
          if(kq==1) tma2d(sb+SM_KX,&tmK,h*DH+64*c,(s+1)*32,KVB);
        }
        __syncwarp();
      }
      float ca[2][2][4];
      #pragma unroll
      for(int i=0;i<2;i++)
        #pragma unroll
        for(int j=0;j<2;j++){ ca[i][j][0]=ca[i][j][1]=ca[i][j][2]=ca[i][j][3]=0.f; }
      TF(6);
      { int gd=0; while(!mbar_try(XL,s&1)){ if(dead) break; if(++gd>GUARD){ dead=true; g_err=5; } } }
      TF(7);
      uint4 vm[6];
      vm[0]=lds4(s16+SM_VMX); vm[1]=lds4(s16+SM_VMX+512);
      #define VB0(x) (((x)&1)?vm[(x)>>1].z:vm[(x)>>1].x)
      #define VB1(x) (((x)&1)?vm[(x)>>1].w:vm[(x)>>1].y)
      if constexpr(MG){
        #pragma unroll
        for(int x=0;x<12;x++){
          if(x==4){
            TF(8);
            { int gd=0; while(!mbar_try(XV,s&1)){ if(dead) break; if(++gd>GUARD){ dead=true; g_err=3; } } }
            TF(9);
            #pragma unroll
            for(int i=2;i<6;i++) vm[i]=lds4(s16+SM_VMX+i*512);
          }
          #pragma unroll
          for(int i=0;i<2;i++){
            mma16816(ca[i][x&1],buf[(x*2+i)&7],VB0(x),VB1(x));
            if(x<8) ldsm4(buf[(x*2+i)&7],os+(x*2+i+8)*256);
          }
        }
      } else {
        #pragma unroll
        for(int x=0;x<12;x++){
          if(x==4){
            TF(8);
            { int gd=0; while(!mbar_try(XV,s&1)){ if(dead) break; if(++gd>GUARD){ dead=true; g_err=3; } } }
            TF(9);
            #pragma unroll
            for(int i=2;i<6;i++) vm[i]=lds4(s16+SM_VMX+i*512);
          }
          #pragma unroll
          for(int i=0;i<2;i++) mma16816(ca[i][x&1],pw[16+x*2+i],VB0(x),VB1(x));
        }
      }
      TF(10);
      bar_sync(4,256);
      TS(3); TF(11);
      const uint4 pq=lds4(s16+SM_P); const uint32_t pm=lds1(sb+SM_PM+lane*4);
      const uint32_t one[4]={0x3F803F80u,0x3F803F80u,0x3F803F80u,0x3F803F80u};
      float d[2][4], e[4];
      #pragma unroll
      for(int i=0;i<4;i++){ d[0][i]=0.f; d[1][i]=0.f; e[i]=0.f; }
      mma16816(e,one,pq.x,pq.y); mma16816(d[0],ux[0][0],pq.x,pq.y); mma16816(d[1],ux[1][0],pq.x,pq.y);
      mma16816(e,one,pq.z,pq.w); mma16816(d[0],ux[0][1],pq.z,pq.w); mma16816(d[1],ux[1][1],pq.z,pq.w);
      mma1688(e,one[0],one[0],pm);
      #pragma unroll
      for(int i=0;i<2;i++) mma1688(d[i],pack_bf16(ca[i][0][0]+ca[i][1][0],ca[i][0][1]+ca[i][1][1]),pack_bf16(ca[i][0][2]+ca[i][1][2],ca[i][0][3]+ca[i][1][3]),pm);
      const float i0=rcp(e[0]), i1=rcp(e[1]);
      TF(12);
      uint32_t* dst=(uint32_t*)((char*)g_part+(uint32_t)(((tile0+2*wt)*32+h)*512+lane*16));
      #pragma unroll
      for(int i=0;i<2;i++){
        if(i==0||2*wt+1<ntile)
          stg_rlx4(dst+i*4096,(__float_as_uint(d[i][0]*i0)&~3u)|tg,(__float_as_uint(d[i][1]*i1)&~3u)|tg,
                              (__float_as_uint(d[i][2]*i0)&~3u)|tg,(__float_as_uint(d[i][3]*i1)&~3u)|tg);
      }
      TW(1);
      TS(4); TF(13);
    }
  }
  };
  if(mg) loop(IC<1>{}); else loop(IC<0>{});
  __syncthreads();
  if(warp==7){ fence_async_all(); fence_gpu(); if(lane==0) stg_rlx1(g_flag+b*32,NSEG); }
  GT(2);
  cluster_sync();
}

enum { M_XN=0,M_Y,M_H,M_OX,M_K,M_V,M_GATE,M_WQ,M_WK,M_WV,M_W1,M_W2,M_WO,M_KM,M_VM,M_NUM,M_OUT };
struct WParams { CUtensorMap m[M_NUM]; const bf16* x; const bf16* b1; const bf16* b2; bf16* out; };
enum { T_RED=0,T_OP=1,T_QA=2,T_M2=3,T_M1=4,T_KV=5,T_END=6 };
#define KVUP 768
#define TRIG 10
#define SOV 1
#define LATE 14
#define EARLY 2
constexpr int NRB=16;
constexpr int STG=40960, NST=4, SLOT=30720, BOXS=10240;
constexpr int W_SLOT=NST*STG;
constexpr int W_BAR=W_SLOT+2*SLOT;
constexpr int W_TOTAL=W_BAR+1024;
static_assert(W_TOTAL<=232448,"smem");
#define QT(i)
__device__ __forceinline__ void stsm4n(uint32_t a,uint32_t r0,uint32_t r1,uint32_t r2,uint32_t r3){ asm volatile("stmatrix.sync.aligned.m8n8.x4.shared.b16 [%0], {%1,%2,%3,%4};"::"r"(a),"r"(r0),"r"(r1),"r"(r2),"r"(r3)); }
#define WGUARD 2000000
__host__ __device__ constexpr int n_op(){ int n=0; for(int r=0;r<NRB;r++) n+=4*nsp(r); return n; }
__host__ __device__ constexpr int n_red(){ int n=0; for(int r=0;r<NRB;r++) if(nsp(r)>1) n+=5*nsp(r); return n; }

__device__ __forceinline__ void wg_arrive(){ asm volatile("wgmma.fence.sync.aligned;":::"memory"); }
__device__ __forceinline__ void wg_commit(){ asm volatile("wgmma.commit_group.sync.aligned;":::"memory"); }
template<int N> __device__ __forceinline__ void wg_wait(){ asm volatile("wgmma.wait_group.sync.aligned %0;"::"n"(N):"memory"); }
__device__ __forceinline__ void mbar_wait(uint32_t a,uint32_t par){ int gd=0; while(!mbar_try(a,par)){ if(++gd>WGUARD){ g_err=20; break; } } }
__device__ __forceinline__ uint32_t ld_rlx(const uint32_t* p){ uint32_t v; asm volatile("ld.relaxed.gpu.global.u32 %0, [%1];":"=r"(v):"l"(p):"memory"); return v; }
__device__ __forceinline__ float4 ld_rlx4f(const float4* p){ float4 v; asm volatile("ld.relaxed.gpu.global.v4.f32 {%0,%1,%2,%3}, [%4];":"=f"(v.x),"=f"(v.y),"=f"(v.z),"=f"(v.w):"l"(p):"memory"); return v; }
__device__ __forceinline__ void red_rel(uint32_t* p){ asm volatile("red.release.gpu.global.add.u32 [%0], 1;"::"l"(p):"memory"); }
__device__ __forceinline__ void tma_st(const CUtensorMap* tm,uint32_t src,int c0,int c1){
  asm volatile("cp.async.bulk.tensor.2d.global.shared::cta.bulk_group [%0, {%2, %3}], [%1];"::"l"(tm),"r"(src),"r"(c0),"r"(c1):"memory"); }
__device__ __forceinline__ void bulk_commit(){ asm volatile("cp.async.bulk.commit_group;":::"memory"); }
__device__ __forceinline__ void bulk_wait_rd(){ asm volatile("cp.async.bulk.wait_group.read 0;":::"memory"); }
__device__ __forceinline__ void bulk_wait(){ asm volatile("cp.async.bulk.wait_group 0;":::"memory"); }
__device__ __forceinline__ void mbar_arrive_cl(uint32_t a){ asm volatile("mbarrier.arrive.shared::cluster.b64 _, [%0];"::"r"(a):"memory"); }
__device__ __forceinline__ void tma2dm(uint32_t dst,const CUtensorMap* tm,int c0,int c1,uint32_t mb){
  asm volatile("cp.async.bulk.tensor.2d.shared::cluster.global.mbarrier::complete_tx::bytes.multicast::cluster [%0], [%1, {%3, %4}], [%2], %5;"::"r"(dst),"l"(tm),"r"(mb),"r"(c0),"r"(c1),"h"((uint16_t)3):"memory"); }

template<int N,int CL,int XS> __device__ __forceinline__ void mainloop(float* acc,int nkb,uint32_t sb,int lane,uint32_t pos){
  const uint32_t eb=CL?mapa(sb+W_BAR+32,lane&1):sb+W_BAR+32;
  uint32_t pst=0;
  #pragma unroll
  for(int i=0;i<N/2;i++){ acc[i]=0.f; acc[96+i]=0.f; }
  #pragma unroll 1
  for(int kb=0;kb<nkb;kb++,pos++){
    const uint32_t st=pos&3;
    mbar_wait(sb+W_BAR+st*8,(pos>>2)&1);
    if(!XS&&kb==nkb-1&&(threadIdx.x&127)==0) mbar_arrive(sb+W_BAR+144);
    const uint32_t a=sb+st*STG;
    const uint32_t da=((a>>4)&0x3fff)|(1u<<16);
    const uint32_t db=da+1024+(511u<<16);
    wg_arrive();
    #pragma unroll
    for(int k=0;k<4;k++){ wgmma<N>(acc,da+2*k,db+128*k,kb|k); wgmma<N>(acc+96,da+512+2*k,db+128*k,kb|k); }
    wg_commit();
    if(kb>0){ wg_wait<1>(); if(CL){ if(lane<2) mbar_arrive_cl(eb+pst*8); } else if(lane==0) mbar_arrive(eb+pst*8); }
    pst=st;
  }
  if(XS){
    #pragma unroll
    for(int x=0;x<XS;x++) mbar_wait(sb+W_BAR+((pos+x)&3)*8,((pos+x)>>2)&1);
    if((threadIdx.x&127)==0) mbar_arrive(sb+W_BAR+144);
  }
  wg_wait<0>();
  if(CL){ if(lane<2) mbar_arrive_cl(eb+pst*8); } else if(lane==0) mbar_arrive(eb+pst*8);
}
__device__ __forceinline__ uint32_t act2(uint32_t u,uint32_t bb,float c1,float c3){
  uint32_t s; asm("add.rn.bf16x2 %0, %1, %2;":"=r"(s):"r"(u),"r"(bb));
  float r[2]={__uint_as_float(s<<16), __uint_as_float(s&0xffff0000u)};
  #pragma unroll
  for(int i=0;i<2;i++){
    const float z=r[i]*fmaf(r[i]*r[i],c3,c1);
    r[i]=r[i]*rcp(1.f+ex2(z));
  }
  return pack_bf16(r[0],r[1]);
}
__device__ __forceinline__ uint32_t fin1(uint32_t s,uint32_t x,uint32_t gq){
  const uint32_t p=pack_bf16(__uint_as_float(s<<16)*__uint_as_float(gq<<16),__uint_as_float(s&0xffff0000u)*__uint_as_float(gq&0xffff0000u));
  return pack_bf16(__uint_as_float(x<<16)+__uint_as_float(p<<16),__uint_as_float(x&0xffff0000u)+__uint_as_float(p&0xffff0000u));
}
template<int NT> __device__ __forceinline__ void stage_pk(const uint32_t* p,uint32_t ra,int lane){
  const int sw=lane&7, hi=lane>>4;
  #pragma unroll
  for(int T=0;T<NT;T++) stsm4n(ra+(T>>2)*BOXS+((((2*T+hi)&7)^sw)<<4),p[4*T],p[4*T+1],p[4*T+2],p[4*T+3]);
}
__device__ __noinline__ void post_pass(uint32_t sl,int nbox,int em,uint32_t ba,float c1,float c3,const bf16* x,bf16* out,uint32_t go){
  const int lane=threadIdx.x&31, r=lane>>3, c=lane&7;
  __syncwarp();
  #pragma unroll 1
  for(int j=0;j<nbox;j++){
    uint4 u[4]; uint32_t a[4];
    #pragma unroll
    for(int i=0;i<4;i++){ const int rr=4*i+r; a[i]=sl+j*BOXS+rr*128+((c^(rr&7))<<4); u[i]=lds4(a[i]); }
    if(em==1){
      const uint4 bb=lds4(ba+j*128+c*16);
      #pragma unroll
      for(int i=0;i<4;i++){
        uint4& v=u[i];
        v.x=act2(v.x,bb.x,c1,c3); v.y=act2(v.y,bb.y,c1,c3); v.z=act2(v.z,bb.z,c1,c3); v.w=act2(v.w,bb.w,c1,c3);
        sts4(a[i],v);
      }
    } else {
      uint4 xx[4],gg[4];
      #pragma unroll
      for(int i=0;i<4;i++){ const uint32_t o=go+(4*i+r)*D+j*64+c*8; xx[i]=__ldg((const uint4*)(x+o)); gg[i]=ldg_rlx4((const uint32_t*)(g_gate+o)); }
      #pragma unroll
      for(int i=0;i<4;i++){ const uint32_t o=go+(4*i+r)*D+j*64+c*8;
        *(uint4*)(out+o)=make_uint4(fin1(u[i].x,xx[i].x,gg[i].x),fin1(u[i].y,xx[i].y,gg[i].y),fin1(u[i].z,xx[i].z,gg[i].z),fin1(u[i].w,xx[i].w,gg[i].w)); }
    }
  }
}
template<int Q,int NS> __device__ __forceinline__ void red_item(const WParams& P,int rbk,int r,int tid){
  const int lane=tid&31, g=lane>>2, t=lane&3, wq=(tid>>5)&3;
  const float4* src=g_opp+opp_base(rbk)+(size_t)(r*Q)*128+(tid&127);
  float4 v[Q][NS];
  #pragma unroll
  for(int j=0;j<Q;j++)
    #pragma unroll
    for(int s=0;s<NS;s++) v[j][s]=ld_rlx4f(src+(size_t)s*20480+j*128);
  uint32_t gx[Q][2], xx[Q][2]; uint32_t off[Q];
  #pragma unroll
  for(int j=0;j<Q;j++){
    const int qi=r*Q+j, m=qi>=80, J=qi-80*m;
    off[j]=(uint32_t)((rbk*128+m*64+wq*16+g)*D+8*J+2*t);
    #pragma unroll
    for(int hh=0;hh<2;hh++){ gx[j][hh]=ld_rlx((const uint32_t*)(g_gate+off[j]+hh*8*D)); xx[j][hh]=__ldg((const uint32_t*)(P.x+off[j]+hh*8*D)); }
  }
  #pragma unroll
  for(int j=0;j<Q;j++){
    float4 a=v[j][0];
    #pragma unroll
    for(int s=1;s<NS;s++){ a.x+=v[j][s].x; a.y+=v[j][s].y; a.z+=v[j][s].z; a.w+=v[j][s].w; }
    *(uint32_t*)(P.out+off[j])=fin1(pack_bf16(a.x,a.y),xx[j][0],gx[j][0]);
    *(uint32_t*)(P.out+off[j]+8*D)=fin1(pack_bf16(a.z,a.w),xx[j][1],gx[j][1]);
  }
}
template<int N,int MODE> __device__ __forceinline__ void gemm_item(const WParams& P,int type,int rbk,int a,uint32_t pos,uint32_t sb,int tid,uint32_t ra,uint32_t& e0,uint32_t& eb,int& sq){
  const int lane=tid&31, wg=tid>>7;
  const uint32_t E0=sb+W_BAR+96+wg*16;
  float acc[192];
  const int ns=nsp(rbk), nt=a&3;
  const int nkb=(MODE&&type==T_M2)?24:((MODE&&type==T_OP)?96/ns:10);
  mainloop<N,MODE==0,0>(acc,nkb,sb,lane,pos);
  if(MODE==0||type>=T_M2||ns==1){
    uint32_t p[2][N/4];
    #pragma unroll
    for(int m=0;m<2;m++)
      #pragma unroll
      for(int i=0;i<N/4;i++) p[m][i]=pack_bf16(acc[96*m+2*i],acc[96*m+2*i+1]);
    const float c1=type==T_M1?-2.302208198144325f:-1.4426950408889634f, c3=type==T_M1?-0.10294323958f:0.f;
    const int wq=(tid>>5)&3;
    if(MODE&&(type==T_M1||type==T_M2)){ mbar_wait(sb+W_BAR+224+wg*8,eb); eb^=1; }
    #pragma unroll
    for(int m=0;m<2;m++){
      mbar_wait(E0+m*8,e0);
      stage_pk<N/16>(p[m],ra+m*SLOT,lane);
      if(MODE&&type!=T_KV) post_pass(sb+W_SLOT+m*SLOT+wq*2048,N/64,type==T_OP?2:1,sb+W_BAR+256+wg*384,c1,c3,P.x,P.out,(uint32_t)((rbk*128+m*64+wq*16)*D+(nt<2?nt*192:128+nt*128)));
      fence_async();
      bar_arrive(sq,160); sq^=1;
    }
    e0^=1;
  } else {
    float4* dst=g_opp+opp_base(rbk)+(size_t)(a>>2)*20480+(nt<2?nt*24:16+nt*16)*128+(tid&127);
    #pragma unroll
    for(int m=0;m<2;m++)
      #pragma unroll
      for(int n=0;n<N/8;n++) __stcg(dst+(m*80+n)*128,make_float4(acc[96*m+4*n],acc[96*m+4*n+1],acc[96*m+4*n+2],acc[96*m+4*n+3]));
    mbar_wait(E0,e0); mbar_wait(E0+8,e0); e0^=1;
    bar_arrive(sq,160); sq^=1;
  }
}
__device__ __forceinline__ void decode(int c,int idx,int& rbk,int& a){
  if(c==T_KV){ rbk=2*(idx>>7)+(idx&1); a=(idx>>1)&63; }
  else if(c==T_M1){ rbk=idx>>3; a=idx&7; }
  else if(c==T_M2){ rbk=idx>>2; a=idx&3; }
  else if(c==T_QA){ rbk=idx>>5; a=idx&31; }
  else {
    rbk=0;
    #pragma unroll 1
    while(true){ const int ns=nsp(rbk), n=c==T_OP?4*ns:(ns>1?5*ns:0); if(idx<n) break; idx-=n; rbk++; }
    a=idx;
  }
}
__device__ __forceinline__ void flag_wait(int rbk,int a){
  const uint32_t need=4*rbk+4; const uint32_t* f=g_flag+a*96; int gd=0;
  while(ld_acq(f)<need||ld_acq(f+32)<need||ld_acq(f+64)<need){ __nanosleep(40); if(++gd>WGUARD){ g_err=22; break; } }
  fence_async_all();
}
__device__ __forceinline__ void cnt_wait(int c,uint32_t thr){
  int gd=0;
  while(ld_acq(g_cnt+c)<thr){ __nanosleep(40); if(++gd>WGUARD){ g_err=23; break; } }
}
template<int MODE>
__global__ void __launch_bounds__(384,1) k_work(const __grid_constant__ WParams P){
  extern __shared__ __align__(1024) uint8_t sm[];
  const uint32_t sb=(uint32_t)__cvta_generic_to_shared(sm);
  const int tid=threadIdx.x, warp=__shfl_sync(~0u,tid>>5,0), lane=tid&31;
  const uint32_t FULL=sb+W_BAR, EMPTY=sb+W_BAR+32, IFULL=sb+W_BAR+64, IEMPTY=sb+W_BAR+80, EF=sb+W_BAR+96, REQ=sb+W_BAR+128, TOK=sb+W_BAR+136;
  volatile int* idesc=(volatile int*)(sm+W_BAR+160);
  if(tid==0){
    for(int i=0;i<NST;i++){ mbar_init(FULL+i*8,1); mbar_init(EMPTY+i*8,MODE?4:8); mbar_init(EF+i*8,1); }
    for(int i=0;i<2;i++){ mbar_init(IFULL+i*8,1); mbar_init(IEMPTY+i*8,6); mbar_init(sb+W_BAR+224+i*8,1); }
    mbar_init(REQ,1); mbar_init(TOK,1); mbar_init(sb+W_BAR+144,1);
    asm volatile("fence.mbarrier_init.release.cluster;":::"memory");
  }
  __syncthreads();
  if(MODE==0){ cluster_sync(); asm volatile("griddepcontrol.wait;":::"memory"); asm volatile("griddepcontrol.launch_dependents;"); }
  if(warp>=8){
    asm volatile("setmaxnreg.dec.sync.aligned.u32 40;");
    if(warp==11){
      uint32_t it=0, pos=0;
      int held=-1; int guard=0; bool fin=false;
      const int cl=lane>>2, cj=lane&3;
      const int ncls=cl==T_RED?n_red():(cl==T_OP?n_op():(cl==T_QA?NRB*32:(cl==T_M2?NRB*4:(cl==T_M1?NRB*8:(cl==T_KV?NRB*64-KVUP:0)))));
      const int cofs=cl==T_KV?KVUP:0;
      int sidx=blockIdx.x;
      while(true){
        int type=T_END, idx=0, erl=0;
        if(!fin){
          if(it) mbar_wait(REQ,(it&1)^1);
          if(MODE==0){ if(sidx<KVUP){ type=T_KV; idx=sidx; sidx+=gridDim.x; } }
          else {
            while(true){
              int cand=held;
              if(cand<0&&ncls){ cand=(int)ld_rlx(g_cnt+C_NEXT+cl*32); if(cand>=ncls) cand=-1; }
              const uint32_t* fp=nullptr; uint32_t thr=0, sl1=0; bool only1=false, no1=cl>=T_M2;
              if(cand>=0&&cl<=T_M2){
                int rbk,a; decode(cl,cand,rbk,a); const int ns=nsp(rbk);
                if(cl==T_QA){ if(cj<3){ fp=g_flag+a*96+cj*32; thr=4*rbk+4; sl1=EARLY; } else { fp=g_cnt+C_KV+min(rbk+1,NRB-1); thr=64; only1=true; } }
                else if(cj==0){ fp=g_cnt+(cl==T_RED?C_OP+rbk:(cl==T_OP?C_QA+rbk*16+(a>>2):C_M1+rbk)); thr=cl==T_RED?4*ns:(cl==T_OP?32/ns:8); sl1=thr; }
                else if(cj==1){ if(cl==T_RED||(cl==T_OP&&ns==1)){ fp=g_cnt+C_M2+rbk; thr=4; } if(rbk<NRB-1) no1=true; }
                else if(cj==2&&cl<T_QA&&ns>1){ fp=g_cnt+C_NEXT+(cl+1)*32; thr=cl==T_OP?(rbk+1)*32:4*RBL+4*NS1*(min(rbk,14)+1-RBL)+(rbk==15?4*NS2:0); only1=true; }
              }
              uint32_t v=0; if(fp) v=ld_acq(fp);
              uint32_t b2=__ballot_sync(~0u,cand>=0&&(v>=thr||only1)), b1=__ballot_sync(~0u,cand>=0&&!no1&&v+sl1>=thr);
              const uint32_t ba=__ballot_sync(~0u,cand>=0), bh=__ballot_sync(~0u,held>=0);
              b2&=b2>>1; b2&=b2>>2; b1&=b1>>1; b1&=b1>>2;
              const bool opf=__ballot_sync(~0u,cl==T_OP&&cand<4*RBL)!=0;
              if(opf&&(bh&~(15u<<(4*T_OP)))) b2&=~(1u<<(4*T_OP));
              b2&=0x111111u; b1&=0x111u; if(bh) b1&=(__popc(bh)==4)?bh:0u;
              if(!EARLY) b1=0;
              if(!ba) break;
              if(b2|b1){
                const uint32_t bb=b2?b2:b1;
                #define RD(c) ((bb>>(4*(c)))&1)
                const int w=RD(T_KV)?T_KV:(RD(T_M2)?T_M2:(RD(T_M1)?T_M1:((opf&&RD(T_OP))?T_OP:(RD(T_QA)?T_QA:(RD(T_OP)?T_OP:T_RED)))));
                int got=-1;
                if(cl==w){
                  if(held>=0){ got=held; held=-1; }
                  else {
                    int tk=0; if(cj==0) tk=(int)atomicAdd(g_cnt+C_NEXT+cl*32,1u);
                    tk=__shfl_sync(15u<<(4*cl),tk,4*cl);
                    if(tk<ncls){ if(tk==cand||cl>T_M2) got=tk; else held=tk; }
                  }
                  if(got>=0) got+=cofs;
                }
                got=__shfl_sync(~0u,got,4*w);
                if(got>=0){ type=w; idx=got; erl=!b2; break; }
              } else {
                __nanosleep(100);
                if(++guard>WGUARD){ g_err=21; break; }
              }
            }
          }
        }
        __syncwarp();
        if(lane==0){
          const uint32_t sl=it&1;
          int rbk=0,a=0; if(type!=T_END) decode(type,idx,rbk,a);
          mbar_wait(IEMPTY+sl*8,((it>>1)&1)^1);
          idesc[sl*8]=type; idesc[sl*8+1]=rbk; idesc[sl*8+2]=a; idesc[sl*8+3]=pos; idesc[sl*8+4]=idx; idesc[sl*8+5]=erl;
          mbar_arrive(IFULL+sl*8);
          pos+=type==T_RED?0:(type==T_M2?24:(type==T_OP?96/nsp(rbk):(type==T_QA?12:10)));
        }
        __syncwarp();
        it++;
        if(type==T_END){ if(fin) break; fin=true; }
      }
    } else if(warp==8){
      if(lane==0){
        uint32_t st=0, ph=1;
        for(uint32_t it=0;;it++){
          const uint32_t sl=it&1;
          mbar_wait(IFULL+sl*8,(it>>1)&1);
          const int type=idesc[sl*8], rbk=idesc[sl*8+1], a=idesc[sl*8+2], erl=idesc[sl*8+5];
          mbar_arrive(IEMPTY+sl*8);
          if(type==T_END) break;
          if(type==T_RED){ mbar_arrive(REQ); continue; }
          int ma=M_XN,mb,col0=a*192,k0=0,nkb=10,nbox=3; const int row0=rbk*128;
          if(MODE==0||type==T_KV){ mb=a<32?M_WK:M_WV; col0=(a&31)*192; }
          else if(type==T_M1){ ma=M_Y; mb=M_W1; }
          else if(type==T_QA){ mb=M_WQ; }
          else {
            const int nt=a&3; col0=nt<2?nt*192:128+nt*128; nbox=nt<2?3:2;
            if(type==T_M2){ ma=M_H; mb=M_W2; nkb=24; } else { ma=M_OX; mb=M_WO; nkb=96/nsp(rbk); k0=(a>>2)*nkb*64; }
          }
          if(MODE&&erl&&type==T_OP) cnt_wait(C_QA+rbk*16+(a>>2),32/nsp(rbk));
          if(MODE) fence_async_all();
          const CUtensorMap* A=&P.m[ma]; const CUtensorMap* B=&P.m[mb];
          const int trig=(MODE&&type<=T_QA&&rbk>=LATE)?nkb-1:max(nkb-(type==T_QA?TRIG-2:TRIG),0);
          for(int kb=0;kb<nkb;kb++){
            mbar_wait(EMPTY+st*8,ph);
            const uint32_t d=sb+st*STG, fb=FULL+st*8;
            mbar_expect(fb,16384+nbox*8192);
            const int kk=k0+kb*64;
            tma2d(d,A,kk,row0,fb); tma2d(d+8192,A,kk,row0+64,fb);
            if(MODE==0){
              const int r=rbk&1, j=2*r;
              tma2dm(d+16384+j*8192,B,col0+j*64,kk,fb);
              if((kb&1)==r) tma2dm(d+24576,B,col0+64,kk,fb);
            }
            else for(int j=0;j<nbox;j++) tma2d(d+16384+j*8192,B,col0+j*64,kk,fb);
            if(kb==trig) mbar_arrive(REQ);
            if(++st==NST){ st=0; ph^=1; }
          }
          if(MODE&&type==T_QA){
            for(int m=0;m<2;m++){
              mbar_wait(EMPTY+st*8,ph);
              const uint32_t d=sb+st*STG, fb=FULL+st*8;
              mbar_expect(fb,SLOT);
              for(int j=0;j<3;j++) tma2d(d+j*BOXS,&P.m[M_K],col0+j*64,row0+m*64,fb);
              if(erl&&!m) flag_wait(rbk,a);
              for(int j=0;j<3;j++) tma2d(d+j*BOXS+8192,&P.m[M_KM],col0+j*64,rbk*32+m*16,fb);
              if(++st==NST){ st=0; ph^=1; }
            }
          }
        }
      }
      __syncwarp();
    } else if(warp<11){
      const int wg=warp-9;
      const uint32_t S0=sb+W_SLOT, E0=EF+wg*16; int sq=4+2*wg;
      for(uint32_t it=wg;;it+=2){
        mbar_wait(IFULL+wg*8,(it>>1)&1);
        const int type=idesc[wg*8], rbk=idesc[wg*8+1], a=idesc[wg*8+2], erl=idesc[wg*8+5];
        __syncwarp();
        if(lane==0) mbar_arrive(IEMPTY+wg*8);
        if(type==T_END) break;
        if(MODE&&type==T_OP&&nsp(rbk)>1&&lane==0){ mbar_arrive(E0); mbar_arrive(E0+8); }
        const int row0=rbk*128;
        int map=-1,col0=a*192,nbox=3,cnt=-1;
        if(MODE==0||type==T_KV){ map=a<32?M_K:M_V; col0=(a&31)*192; cnt=C_KV+rbk; }
        else if(type==T_M1){ map=M_H; cnt=C_M1+rbk; }
        else if(type==T_QA){ map=M_OX; cnt=C_QA+rbk*16+((a*nsp(rbk))>>5); }
        else if(type!=T_RED){
          const int nt=a&3; col0=nt<2?nt*192:128+nt*128; nbox=nt<2?3:2;
          if(type==T_M2){ map=M_GATE; cnt=C_M2+rbk; } else if(nsp(rbk)==1) map=M_OUT;
        }
        if(MODE&&(type==T_M1||type==T_M2)&&lane==0){ const uint32_t bb=sb+W_BAR+224+wg*8; mbar_expect(bb,nbox*128); bulk_g2s(sb+W_BAR+256+wg*384,(type==T_M1?P.b1:P.b2)+col0,nbox*128,bb); }
        if(it&&lane==0) mbar_wait(TOK,(it&1)^1);
        if(MODE&&map<0){
          if(lane==0) mbar_arrive(TOK);
          if(type==T_RED&&lane==0){ if(erl) cnt_wait(C_OP+rbk,4*nsp(rbk)); mbar_arrive(E0); mbar_arrive(E0+8); }
          if(type==T_OP){ { __syncwarp(); bar_sync(sq,160); sq^=1; } if(lane==0){ fence_gpu(); red_rel(g_cnt+C_OP+rbk); } }
        } else if(MODE&&map==M_OUT){
          if(lane==0){ mbar_arrive(E0); mbar_arrive(E0+8); }
          { __syncwarp(); bar_sync(sq,160); sq^=1; }
          { __syncwarp(); bar_sync(sq,160); sq^=1; }
          if(lane==0) mbar_arrive(TOK);
        } else {
          if(MODE&&type==T_QA){
            if(lane==0){
              fence_async_all();
              for(int m=0;m<2;m++){
                mbar_expect(E0+m*8,SLOT);
                for(int j=0;j<3;j++) tma2d(S0+m*SLOT+j*BOXS,&P.m[M_V],col0+j*64,row0+m*64,E0+m*8);
              }
              if(erl) flag_wait(rbk,a);
              for(int m=0;m<2;m++)
                for(int j=0;j<3;j++) tma2d(S0+m*SLOT+j*BOXS+8192,&P.m[M_VM],col0+j*64,rbk*32+m*16,E0+m*8);
            }
          } else if(lane==0){ mbar_arrive(E0); mbar_arrive(E0+8); }
          for(int m=0;m<2;m++){
            { __syncwarp(); bar_sync(sq,160); sq^=1; }
            if(lane==0){
              for(int j=0;j<nbox;j++) tma_st(&P.m[map],S0+m*SLOT+j*BOXS,col0+j*64,row0+m*64);
              bulk_commit();
            }
          }
          if(lane==0){
            bulk_wait_rd(); mbar_arrive(TOK);
            bulk_wait(); fence_async_all(); red_rel(g_cnt+cnt);
          }
        }
        __syncwarp();
      }
      if(lane==0) bulk_wait();
    }
  } else {
    asm volatile("setmaxnreg.inc.sync.aligned.u32 232;");
    const int wg=warp>>2, wq=warp&3, g=lane>>2, t=lane&3;
    const uint32_t E0=EF+wg*16;
    const uint32_t ra=sb+W_SLOT+(16*wq+(lane&7)+((lane>>3)&1)*8)*128;
    uint32_t e0=0, eb=0; int sq=4+2*wg;
    #pragma unroll 1
    for(uint32_t it=0;;it++){
      mbar_wait(IFULL+wg*8,it&1);
      const int type=idesc[wg*8], rbk=idesc[wg*8+1], a=idesc[wg*8+2]; const uint32_t pos=idesc[wg*8+3];
      __syncwarp();
      if(lane==0) mbar_arrive(IEMPTY+wg*8);
      if(type==T_END) break;
      mbar_wait(sb+W_BAR+144,wg^1);
      if(MODE&&type==T_RED){
        bar_sync(8+wg,128);
        if((tid&127)==0) mbar_arrive(sb+W_BAR+144);
        mbar_wait(E0,e0); mbar_wait(E0+8,e0); e0^=1;
        if(nsp(rbk)==NS1) red_item<32/NS1,NS1>(P,rbk,a,tid); else red_item<32/NS2,NS2>(P,rbk,a,tid);
      } else {
        if(MODE==0||type!=T_QA){
          if(MODE==0||type>=T_M1||(a&3)<2) gemm_item<192,MODE>(P,type,rbk,a,pos,sb,tid,ra,e0,eb,sq); else gemm_item<128,MODE>(P,type,rbk,a,pos,sb,tid,ra,e0,eb,sq);
        } else {
          float acc[192];
          QT(0);
          mainloop<192,0,2>(acc,10,sb,lane,pos);
          QT(1);
          const int sgl=wq>>1, rh=wq&1;
          uint32_t pa[2][20];
          {
            uint32_t q[96];
            float s[2][40];
            QT(2);
            #pragma unroll
            for(int m=0;m<2;m++){
              const uint32_t ks=(pos+10+m)&3;
              const uint32_t dk=((sb+ks*STG)>>4)|(1u<<16);
              #pragma unroll
              for(int i=48*m;i<48*m+48;i++) q[i]=pack_bf16(acc[2*i],acc[2*i+1]);
              mbar_wait(FULL+ks*8,((pos+10+m)>>2)&1);
              #pragma unroll
              for(int i=0;i<40;i++) s[m][i]=0.f;
              wg_arrive();
              #pragma unroll
              for(int T=0;T<12;T++) wgmma_rs<80>(s[m],q+48*m+4*T,dk+(T>>2)*(BOXS/16)+(T&3)*2,T);
              wg_commit();
              wg_wait<0>();
              if(lane==0) mbar_arrive(EMPTY+ks*8);
              QT(3+m);
            }
            const float NEG=rb(-1e9f);
            #pragma unroll
            for(int m=0;m<2;m++){
              float sc[5][4];
              float mx[2]={-3.4e38f,-3.4e38f};
              #pragma unroll
              for(int n=0;n<5;n++)
                #pragma unroll
                for(int i=0;i<4;i+=2){
                  const float u0=n?(sgl?s[m][12+4*n+i]:s[m][4*n-4+i]):(sgl?s[m][36+i]:s[m][32+i]);
                  const float u1=n?(sgl?s[m][13+4*n+i]:s[m][4*n-3+i]):(sgl?s[m][37+i]:s[m][33+i]);
                  const uint32_t r=pack_bf16(u0,u1);
                  const uint32_t w=pack_bf16(__uint_as_float(r<<16)*0.07216878364870322f,__uint_as_float(r&0xffff0000u)*0.07216878364870322f);
                  float v0=__uint_as_float(w<<16), v1=__uint_as_float(w&0xffff0000u);
                  if(n>0){ const int key=8*(n-1)+2*t, row=16*rh+g+4*i; if(key>row) v0=NEG; if(key+1>row) v1=NEG; }
                  sc[n][i]=v0; sc[n][i+1]=v1; mx[i>>1]=fmaxf(mx[i>>1],fmaxf(v0,v1));
                }
              float sum[2]={0.f,0.f};
              #pragma unroll
              for(int r=0;r<2;r++){ mx[r]=fmaxf(mx[r],__shfl_xor_sync(~0u,mx[r],1)); mx[r]=fmaxf(mx[r],__shfl_xor_sync(~0u,mx[r],2)); }
              #pragma unroll
              for(int n=0;n<5;n++)
                #pragma unroll
                for(int i=0;i<4;i++){ const float e=ex2((sc[n][i]-mx[i>>1])*1.4426950408889634f); sc[n][i]=e; sum[i>>1]+=e; }
              #pragma unroll
              for(int r=0;r<2;r++){ sum[r]+=__shfl_xor_sync(~0u,sum[r],1); sum[r]+=__shfl_xor_sync(~0u,sum[r],2); sum[r]=rcp(sum[r]); }
              #pragma unroll
              for(int n=0;n<5;n++){
                const uint32_t p0=pack_bf16(sc[n][0]*sum[0],sc[n][1]*sum[0]), p1=pack_bf16(sc[n][2]*sum[1],sc[n][3]*sum[1]);
                const int o=n?2*(n-1):16, d=n?8:2;
                pa[m][o]=sgl?0u:p0; pa[m][o+1]=sgl?0u:p1; pa[m][o+d]=sgl?p0:0u; pa[m][o+d+1]=sgl?p1:0u;
              }
            }
          }
          QT(5); QT(6);
          const uint32_t dv=((sb+W_SLOT)>>4)|((uint32_t)(BOXS/16)<<16);
          #pragma unroll
          for(int m=0;m<2;m++){
            float o[96];
            #pragma unroll
            for(int i=0;i<96;i++) o[i]=0.f;
            mbar_wait(E0+m*8,e0);
            QT(7+3*m);
            wg_arrive();
            #pragma unroll
            for(int k=0;k<5;k++) wgmma_rs<192>(o,pa[m]+4*k,dv+m*(SLOT/16)+128*k,k);
            wg_commit();
            wg_wait<0>();
            QT(8+3*m);
            bar_sync(8+wg,128);
            { uint32_t p[48];
              #pragma unroll
              for(int i=0;i<48;i++) p[i]=pack_bf16(o[2*i],o[2*i+1]);
              stage_pk<12>(p,ra+m*SLOT,lane); }
            fence_async();
            bar_arrive(sq,160); sq^=1;
            QT(9+3*m);
          }
          e0^=1;
        }
      }
    }
  }
  if(MODE==0) cluster_sync();
}
typedef CUresult (*EncFn)(CUtensorMap*,CUtensorMapDataType,cuuint32_t,void*,const cuuint64_t*,const cuuint64_t*,const cuuint32_t*,const cuuint32_t*,CUtensorMapInterleave,CUtensorMapSwizzle,CUtensorMapL2promotion,CUtensorMapFloatOOBfill);
static CUtensorMap mk2d(const void* base,uint64_t cols,uint64_t rows,uint32_t bc,uint32_t br){
  static EncFn fn=nullptr;
  if(!fn){ void* p=nullptr; cudaDriverEntryPointQueryResult qr; cudaGetDriverEntryPoint("cuTensorMapEncodeTiled",&p,cudaEnableDefault,&qr); fn=(EncFn)p; }
  CUtensorMap m; cuuint64_t gd[2]={cols,rows}; cuuint64_t gs[1]={cols*2}; cuuint32_t bd[2]={bc,br}; cuuint32_t es[2]={1,1};
  fn(&m,CU_TENSOR_MAP_DATA_TYPE_BFLOAT16,2,(void*)base,gd,gs,bd,es,CU_TENSOR_MAP_INTERLEAVE_NONE,CU_TENSOR_MAP_SWIZZLE_128B,CU_TENSOR_MAP_L2_PROMOTION_L2_128B,CU_TENSOR_MAP_FLOAT_OOB_FILL_NONE);
  return m;
}
template<class T> static T* sym(T& s){ void* p; cudaGetSymbolAddress(&p,s); return (T*)p; }
}

int g_reconly=0; int g_kvgrid=132;
extern "C" void kernel_launch(void* const* d_in, const int* in_sizes, int n_in, void* d_out, int out_size) {
  using namespace rk;
  const bf16* x=(const bf16*)d_in[0]; const bf16* mem0=(const bf16*)d_in[1];
  const bf16* Wq=(const bf16*)d_in[2]; const bf16* Wk=(const bf16*)d_in[3]; const bf16* Wv=(const bf16*)d_in[4]; const bf16* Wo=(const bf16*)d_in[5];
  const bf16* w1=(const bf16*)d_in[8]; const bf16* b1=(const bf16*)d_in[9]; const bf16* w2=(const bf16*)d_in[10]; const bf16* b2=(const bf16*)d_in[11];
  cudaStream_t st=cudaStreamPerThread;
  cudaFuncSetAttribute(k_rec,cudaFuncAttributeMaxDynamicSharedMemorySize,SM_TOTAL);
  cudaFuncSetAttribute(k_work<0>,cudaFuncAttributeMaxDynamicSharedMemorySize,W_TOTAL);
  cudaFuncSetAttribute(k_work<1>,cudaFuncAttributeMaxDynamicSharedMemorySize,W_TOTAL);
  bf16* k=(bf16*)sym(g_k); bf16* v=(bf16*)sym(g_v);
  WParams P;
  P.m[M_XN]=mk2d(sym(g_xn),D,S,64,64); P.m[M_Y]=mk2d(sym(g_y),D,S,64,64); P.m[M_H]=mk2d(sym(g_h),F,S,64,64); P.m[M_OX]=mk2d(sym(g_ox),HD,S,64,64);
  P.m[M_K]=mk2d(k,HD,S,64,64); P.m[M_V]=mk2d(v,HD,S,64,64); P.m[M_GATE]=mk2d(sym(g_gate),D,S,64,64);
  P.m[M_WQ]=mk2d(Wq,HD,D,64,64); P.m[M_WK]=mk2d(Wk,HD,D,64,64); P.m[M_WV]=mk2d(Wv,HD,D,64,64);
  P.m[M_W1]=mk2d(w1,F,D,64,64); P.m[M_W2]=mk2d(w2,D,F,64,64); P.m[M_WO]=mk2d(Wo,D,HD,64,64);
  P.m[M_KM]=mk2d(sym(g_km),HD,NSEG*8,64,16); P.m[M_VM]=mk2d(sym(g_vm),HD,NSEG*8,64,16);
  P.x=x; P.b1=b1; P.b2=b2; P.out=(bf16*)d_out;
  k_pre<<<S/8,256,0,st>>>(x,mem0);
  if(!(g_reconly&1)){
    cudaLaunchConfig_t cfg={}; cfg.gridDim=dim3(g_kvgrid); cfg.blockDim=dim3(384); cfg.dynamicSmemBytes=W_TOTAL; cfg.stream=st;
    cudaLaunchAttribute at[2]; at[0].id=cudaLaunchAttributeClusterDimension; at[0].val.clusterDim.x=2; at[0].val.clusterDim.y=1; at[0].val.clusterDim.z=1;
    at[1].id=cudaLaunchAttributeProgrammaticStreamSerialization; at[1].val.programmaticStreamSerializationAllowed=1; cfg.attrs=at; cfg.numAttrs=2;
    cudaLaunchKernelEx(&cfg,k_work<0>,P);
  }
  if(!(g_reconly&4)){
    cudaLaunchConfig_t cfg={}; cfg.gridDim=dim3(NCTA); cfg.blockDim=dim3(256); cfg.dynamicSmemBytes=SM_TOTAL; cfg.stream=st;
    cudaLaunchAttribute at[2]; at[0].id=cudaLaunchAttributeClusterDimension; at[0].val.clusterDim.x=3; at[0].val.clusterDim.y=1; at[0].val.clusterDim.z=1;
    at[1].id=cudaLaunchAttributeProgrammaticStreamSerialization; at[1].val.programmaticStreamSerializationAllowed=1; cfg.attrs=at; cfg.numAttrs=2;
    CUtensorMap tk=mk2d(k,HD,S,64,32), tv=mk2d(v,HD,S,64,32);
    cudaLaunchKernelEx(&cfg,k_rec,tk,tv,Wq,Wk,Wv,Wo,0u);
  }
  if(!(g_reconly&2)){
    cudaLaunchConfig_t cfg={}; cfg.gridDim=dim3(132); cfg.blockDim=dim3(384); cfg.dynamicSmemBytes=W_TOTAL; cfg.stream=st;
    cudaLaunchAttribute at[1]; at[0].id=cudaLaunchAttributeProgrammaticStreamSerialization; at[0].val.programmaticStreamSerializationAllowed=1; cfg.attrs=at; cfg.numAttrs=PDL;
    cudaLaunchKernelEx(&cfg,k_work<1>,P);
  }
}
```

```cpp
#include <cuda_runtime.h>
#include <cuda_bf16.h>
#include <stdint.h>
#include <cuda.h>

namespace rk {
typedef __nv_bfloat16 bf16;
constexpr int S=2048, D=640, H=32, DH=192, HD=6144, NSEG=64, F=1536;
constexpr uint32_t SENT=0xFFFFFFFFu;
#define GUARDN 400000
constexpr int GUARD=GUARDN;
constexpr int NCTA=96;

__device__ __align__(128) bf16 g_xn[S*D];
__device__ __align__(128) bf16 g_y[S*D];
__device__ __align__(128) bf16 g_h[S*F];
__device__ __align__(128) bf16 g_gate[S*D];
__device__ __align__(128) bf16 g_k[(size_t)S*HD];
__device__ __align__(128) bf16 g_v[(size_t)S*HD];
__device__ __align__(128) bf16 g_km[NSEG*8*HD];
__device__ __align__(128) bf16 g_vm[NSEG*8*HD];
__device__ __align__(128) uint32_t g_flag[NCTA*32];
__device__ __align__(128) bf16 g_ox[(size_t)S*HD];
#define NSTAB 0x4332220000000000ull
__host__ __device__ constexpr int nsp(int rb){ return 1<<(int)((NSTAB>>(4*rb))&15); }
__host__ __device__ constexpr int qab(int rb){ int n=0; for(int r=0;r<rb;r++) n+=nsp(r); return n; }
__host__ __device__ constexpr int opp_base(int rb){ int n=0; for(int r=0;r<rb;r++) if(nsp(r)>1) n+=nsp(r); return n*20480; }
__host__ __device__ constexpr bool ns_used(int n){ for(int r=0;r<16;r++) if(nsp(r)==n) return true; return false; }
static_assert(qab(16)<=64&&!ns_used(2),"split table");
__device__ __align__(128) float4 g_opp[(size_t)opp_base(16)];
constexpr int C_NEXT=0, C_KV=256, C_M1=272, C_M2=288, C_OP=304, C_QA=320, C_NUM=384;
__device__ __align__(128) uint32_t g_cnt[C_NUM];
#define PDL 1
__device__ __align__(1024) unsigned long long g_acc[NSEG*2560];
constexpr unsigned long long ACC_INIT=0ull-32ull*((0x5A000000ull<<32)+0xD0000000ull+1ull);
__device__ __align__(128) uint32_t g_nrm[NCTA*2+32];
__device__ int g_err;
__device__ unsigned long long g_gt[128*4];
#define GT(i) do{ if(threadIdx.x==0){ unsigned long long g0; asm volatile("mov.u64 %0, %%globaltimer;":"=l"(g0)); g_gt[blockIdx.x*4+(i)]=g0; } }while(0)

__device__ __forceinline__ float rb(float x){ return __bfloat162float(__float2bfloat16(x)); }
__device__ __forceinline__ uint32_t pack_bf16(float lo,float hi){ uint32_t r; asm("cvt.rn.bf16x2.f32 %0, %1, %2;":"=r"(r):"f"(hi),"f"(lo)); return r; }
__device__ __forceinline__ uint32_t movm(uint32_t a){ uint32_t d; asm volatile("movmatrix.sync.aligned.m8n8.trans.b16 %0, %1;":"=r"(d):"r"(a)); return d; }
__device__ __forceinline__ uint4 ldg_rlx4(const uint32_t* p){ uint4 v; asm volatile("ld.relaxed.gpu.global.v4.u32 {%0,%1,%2,%3}, [%4];":"=r"(v.x),"=r"(v.y),"=r"(v.z),"=r"(v.w):"l"(p):"memory"); return v; }
__device__ __forceinline__ void stg_rlx1(uint32_t* p,uint32_t a){ asm volatile("st.relaxed.gpu.global.u32 [%0], %1;"::"l"(p),"r"(a):"memory"); }
__device__ __forceinline__ void stg_rlx2(uint32_t* p,uint32_t a,uint32_t b){ asm volatile("st.relaxed.gpu.global.v2.u32 [%0], {%1,%2};"::"l"(p),"r"(a),"r"(b):"memory"); }
__device__ __forceinline__ void bar_sync(int id,int n){ asm volatile("bar.sync %0, %1;"::"r"(id),"r"(n):"memory"); }
__device__ __forceinline__ void bar_arrive(int id,int n){ asm volatile("bar.arrive %0, %1;"::"r"(id),"r"(n):"memory"); }
__device__ __forceinline__ void mma16816(float* d,const uint32_t* a,uint32_t b0,uint32_t b1){
  asm volatile("mma.sync.aligned.m16n8k16.row.col.f32.bf16.bf16.f32 {%0,%1,%2,%3},{%4,%5,%6,%7},{%8,%9},{%0,%1,%2,%3};"
   :"+f"(d[0]),"+f"(d[1]),"+f"(d[2]),"+f"(d[3]):"r"(a[0]),"r"(a[1]),"r"(a[2]),"r"(a[3]),"r"(b0),"r"(b1));
}
__device__ __forceinline__ void mma1688(float* d,uint32_t a0,uint32_t a1,uint32_t b0){
  asm volatile("mma.sync.aligned.m16n8k8.row.col.f32.bf16.bf16.f32 {%0,%1,%2,%3},{%4,%5},{%6},{%0,%1,%2,%3};"
   :"+f"(d[0]),"+f"(d[1]),"+f"(d[2]),"+f"(d[3]):"r"(a0),"r"(a1),"r"(b0));
}
__device__ __forceinline__ void ldsm4t(uint32_t* r,uint32_t addr){ asm volatile("ldmatrix.sync.aligned.m8n8.x4.trans.shared.b16 {%0,%1,%2,%3}, [%4];":"=r"(r[0]),"=r"(r[1]),"=r"(r[2]),"=r"(r[3]):"r"(addr):"memory"); }
__device__ __forceinline__ void ldsm4(uint32_t* r,uint32_t addr){ asm volatile("ldmatrix.sync.aligned.m8n8.x4.shared.b16 {%0,%1,%2,%3}, [%4];":"=r"(r[0]),"=r"(r[1]),"=r"(r[2]),"=r"(r[3]):"r"(addr):"memory"); }
__device__ __forceinline__ void stsm4(uint32_t a,uint32_t r0,uint32_t r1,uint32_t r2,uint32_t r3){ asm volatile("stmatrix.sync.aligned.m8n8.x4.shared.b16 [%0], {%1,%2,%3,%4};"::"r"(a),"r"(r0),"r"(r1),"r"(r2),"r"(r3):"memory"); }
__device__ __forceinline__ void stsm2(uint32_t a,uint32_t r0,uint32_t r1){ asm volatile("stmatrix.sync.aligned.m8n8.x2.shared.b16 [%0], {%1,%2};"::"r"(a),"r"(r0),"r"(r1):"memory"); }
__device__ __forceinline__ void cp16(uint32_t dst,const void* src){ asm volatile("cp.async.cg.shared.global [%0], [%1], 16;"::"r"(dst),"l"(src):"memory"); }
__device__ __forceinline__ void cp_wait_all(){ asm volatile("cp.async.wait_all;":::"memory"); }
__device__ __forceinline__ void fence_async(){ asm volatile("fence.proxy.async.shared::cta;":::"memory"); }
__device__ __forceinline__ void sts4f(uint32_t a,const float* v){ asm volatile("st.shared.v4.f32 [%0], {%1,%2,%3,%4};"::"r"(a),"f"(v[0]),"f"(v[1]),"f"(v[2]),"f"(v[3]):"memory"); }
__device__ __forceinline__ void sts4(uint32_t a,uint4 v){ asm volatile("st.shared.v4.u32 [%0], {%1,%2,%3,%4};"::"r"(a),"r"(v.x),"r"(v.y),"r"(v.z),"r"(v.w):"memory"); }
__device__ __forceinline__ void sts4r(uint32_t a,const uint32_t* v){ asm volatile("st.shared.v4.u32 [%0], {%1,%2,%3,%4};"::"r"(a),"r"(v[0]),"r"(v[1]),"r"(v[2]),"r"(v[3]):"memory"); }
__device__ __forceinline__ void sts2(uint32_t a,uint32_t x,uint32_t y){ asm volatile("st.shared.v2.u32 [%0], {%1,%2};"::"r"(a),"r"(x),"r"(y):"memory"); }
__device__ __forceinline__ float4 lds4f(uint32_t a){ float4 v; asm volatile("ld.shared.v4.f32 {%0,%1,%2,%3}, [%4];":"=f"(v.x),"=f"(v.y),"=f"(v.z),"=f"(v.w):"r"(a):"memory"); return v; }
__device__ __forceinline__ float2 lds2f(uint32_t a){ float2 v; asm volatile("ld.shared.v2.f32 {%0,%1}, [%2];":"=f"(v.x),"=f"(v.y):"r"(a):"memory"); return v; }
__device__ __forceinline__ uint4 lds4(uint32_t a){ uint4 v; asm volatile("ld.shared.v4.u32 {%0,%1,%2,%3}, [%4];":"=r"(v.x),"=r"(v.y),"=r"(v.z),"=r"(v.w):"r"(a):"memory"); return v; }
__device__ __forceinline__ void lds4r(uint32_t* r,uint32_t a){ asm volatile("ld.shared.v4.u32 {%0,%1,%2,%3}, [%4];":"=r"(r[0]),"=r"(r[1]),"=r"(r[2]),"=r"(r[3]):"r"(a):"memory"); }
__device__ __forceinline__ uint2 lds2(uint32_t a){ uint2 v; asm volatile("ld.shared.v2.u32 {%0,%1}, [%2];":"=r"(v.x),"=r"(v.y):"r"(a):"memory"); return v; }
__device__ __forceinline__ float ex2(float x){ float r; asm("ex2.approx.ftz.f32 %0, %1;":"=f"(r):"f"(x)); return r; }
__device__ __forceinline__ float rcp(float x){ float r; asm("rcp.approx.ftz.f32 %0, %1;":"=f"(r):"f"(x)); return r; }
__device__ __forceinline__ void mbar_init(uint32_t a,int n){ asm volatile("mbarrier.init.shared.b64 [%0], %1;"::"r"(a),"r"(n):"memory"); }
__device__ __forceinline__ void mbar_expect(uint32_t a,int bytes){ asm volatile("mbarrier.arrive.expect_tx.shared.b64 _, [%0], %1;"::"r"(a),"r"(bytes):"memory"); }
__device__ __forceinline__ void mbar_arrive(uint32_t a){ asm volatile("mbarrier.arrive.shared.b64 _, [%0];"::"r"(a):"memory"); }
__device__ __forceinline__ bool mbar_try(uint32_t a,uint32_t par){ uint32_t ok; asm volatile("{\n.reg .pred p;\nmbarrier.try_wait.parity.shared.b64 p, [%1], %2;\nselp.u32 %0,1,0,p;\n}":"=r"(ok):"r"(a),"r"(par):"memory"); return ok; }
__device__ __forceinline__ bool mbar_try_cl(uint32_t a,uint32_t par){ uint32_t ok; asm volatile("{\n.reg .pred p;\nmbarrier.try_wait.parity.acquire.cluster.shared::cta.b64 p, [%1], %2;\nselp.u32 %0,1,0,p;\n}":"=r"(ok):"r"(a),"r"(par):"memory"); return ok; }
__device__ __forceinline__ void bulk_g2s(uint32_t dst,const void* src,int bytes,uint32_t mb){ asm volatile("cp.async.bulk.shared::cluster.global.mbarrier::complete_tx::bytes [%0], [%1], %2, [%3];"::"r"(dst),"l"(src),"r"(bytes),"r"(mb):"memory"); }
__device__ __forceinline__ uint32_t mapa(uint32_t a,uint32_t r){ uint32_t d; asm("mapa.shared::cluster.u32 %0, %1, %2;":"=r"(d):"r"(a),"r"(r)); return d; }
__device__ __forceinline__ void st_async2(uint32_t ra,uint32_t x,uint32_t y,uint32_t rmb){ asm volatile("st.async.weak.shared::cluster.mbarrier::complete_tx::bytes.v2.b32 [%0], {%1,%2}, [%3];"::"r"(ra),"r"(x),"r"(y),"r"(rmb):"memory"); }
__device__ __forceinline__ void st_async4(uint32_t ra,uint32_t x,uint32_t y,uint32_t z,uint32_t w,uint32_t rmb){ asm volatile("st.async.weak.shared::cluster.mbarrier::complete_tx::bytes.v4.b32 [%0], {%1,%2,%3,%4}, [%5];"::"r"(ra),"r"(x),"r"(y),"r"(z),"r"(w),"r"(rmb):"memory"); }
__device__ __forceinline__ void stg_rlx4(uint32_t* p,uint32_t a,uint32_t b,uint32_t c,uint32_t d){ asm volatile("st.relaxed.gpu.global.v4.u32 [%0], {%1,%2,%3,%4};"::"l"(p),"r"(a),"r"(b),"r"(c),"r"(d):"memory"); }
__device__ __forceinline__ void red64(void* p,uint32_t lo,uint32_t hi){ asm volatile("{\n.reg .b64 v;\nmov.b64 v, {%1,%2};\nred.relaxed.gpu.global.add.u64 [%0], v;\n}"::"l"(p),"r"(lo),"r"(hi):"memory"); }
__device__ __forceinline__ uint32_t amax2(uint32_t a,uint32_t b){ uint32_t r; asm("max.xorsign.abs.bf16x2 %0, %1, %2;":"=r"(r):"r"(a),"r"(b)); return r; }
__device__ __forceinline__ void cluster_sync(){ asm volatile("barrier.cluster.arrive.release.aligned;\nbarrier.cluster.wait.acquire.aligned;":::"memory"); }
__device__ __forceinline__ uint32_t ld_acq(const uint32_t* p){ uint32_t v; asm volatile("ld.acquire.gpu.global.u32 %0, [%1];":"=r"(v):"l"(p):"memory"); return v; }
__device__ __forceinline__ void fence_async_all(){ asm volatile("fence.proxy.async;":::"memory"); }
__device__ __forceinline__ void fence_async_g(){ asm volatile("fence.proxy.async.global;":::"memory"); }
__device__ __forceinline__ void fence_rel(){ asm volatile("fence.release.gpu;":::"memory"); }
__device__ __forceinline__ void fence_acq(){ asm volatile("fence.acquire.gpu;":::"memory"); }
__device__ __forceinline__ void fence_gpu(){ asm volatile("fence.acq_rel.gpu;":::"memory"); }

template<int NL,class V,class LDF,class OKF>
__device__ __forceinline__ int poll1(V* u,LDF ld,OKF ok,bool& dead,int code){
  #pragma unroll
  for(int i=0;i<NL;i++) u[i]=ld(i);
  int guard=0;
  while(true){
    bool f[NL]; bool a=true;
    #pragma unroll
    for(int i=0;i<NL;i++){ f[i]=ok(u[i]); a=a&&f[i]; }
    if(__all_sync(~0u,a)||dead) break;
    #pragma unroll
    for(int i=0;i<NL;i++) if(!f[i]) u[i]=ld(i);
    if(++guard>GUARD){ dead=true; g_err=code; }
  }
  return guard;
}
template<int NL,class V,class LDF,class OKF>
__device__ __forceinline__ int poll2(V* u,LDF ld,OKF ok,bool& dead,int code){
  int guard=0;
  while(true){
    bool f[NL]; bool a=true;
    #pragma unroll
    for(int i=0;i<NL;i++){ f[i]=ok(u[i]); a=a&&f[i]; }
    if(__all_sync(~0u,a)||dead) break;
    #pragma unroll
    for(int i=0;i<NL;i++) if(!f[i]) u[i]=ld(i);
    if(++guard>GUARD){ dead=true; g_err=code; }
  }
  return guard;
}
__device__ __forceinline__ void spin(uint32_t n){ uint32_t t0,t1; asm volatile("mov.u32 %0, %%clock;":"=r"(t0)); do{ asm volatile("mov.u32 %0, %%clock;":"=r"(t1)); }while(t1-t0<n); }
template<int N> __device__ __forceinline__ void wgmma(float* d,uint32_t da,uint32_t db,int sc);
template<int N> __device__ __forceinline__ void wgmma_rs(float* d,const uint32_t* a,uint32_t db,int sc);
template<> __device__ __forceinline__ void wgmma<128>(float* d,uint32_t da,uint32_t db,int sc){
  asm volatile("{\n.reg .pred p;\n.reg .b64 xa, xb;\nmov.b64 xa, {%64, 0x40000040};\nmov.b64 xb, {%65, 0x40000040};\nsetp.ne.b32 p, %66, 0;\nwgmma.mma_async.sync.aligned.m64n128k16.f32.bf16.bf16 {%0,%1,%2,%3,%4,%5,%6,%7,%8,%9,%10,%11,%12,%13,%14,%15,%16,%17,%18,%19,%20,%21,%22,%23,%24,%25,%26,%27,%28,%29,%30,%31,%32,%33,%34,%35,%36,%37,%38,%39,%40,%41,%42,%43,%44,%45,%46,%47,%48,%49,%50,%51,%52,%53,%54,%55,%56,%57,%58,%59,%60,%61,%62,%63}, xa, xb, p, 1, 1, 0, 1;\n}"
   :"+f"(d[0]),"+f"(d[1]),"+f"(d[2]),"+f"(d[3]),"+f"(d[4]),"+f"(d[5]),"+f"(d[6]),"+f"(d[7]),"+f"(d[8]),"+f"(d[9]),"+f"(d[10]),"+f"(d[11]),"+f"(d[12]),"+f"(d[13]),"+f"(d[14]),"+f"(d[15]),"+f"(d[16]),"+f"(d[17]),"+f"(d[18]),"+f"(d[19]),"+f"(d[20]),"+f"(d[21]),"+f"(d[22]),"+f"(d[23]),"+f"(d[24]),"+f"(d[25]),"+f"(d[26]),"+f"(d[27]),"+f"(d[28]),"+f"(d[29]),"+f"(d[30]),"+f"(d[31]),"+f"(d[32]),"+f"(d[33]),"+f"(d[34]),"+f"(d[35]),"+f"(d[36]),"+f"(d[37]),"+f"(d[38]),"+f"(d[39]),"+f"(d[40]),"+f"(d[41]),"+f"(d[42]),"+f"(d[43]),"+f"(d[44]),"+f"(d[45]),"+f"(d[46]),"+f"(d[47]),"+f"(d[48]),"+f"(d[49]),"+f"(d[50]),"+f"(d[51]),"+f"(d[52]),"+f"(d[53]),"+f"(d[54]),"+f"(d[55]),"+f"(d[56]),"+f"(d[57]),"+f"(d[58]),"+f"(d[59]),"+f"(d[60]),"+f"(d[61]),"+f"(d[62]),"+f"(d[63]):"r"(da),"r"(db),"r"(sc));
}
template<> __device__ __forceinline__ void wgmma<192>(float* d,uint32_t da,uint32_t db,int sc){
  asm volatile("{\n.reg .pred p;\n.reg .b64 xa, xb;\nmov.b64 xa, {%96, 0x40000040};\nmov.b64 xb, {%97, 0x40000040};\nsetp.ne.b32 p, %98, 0;\nwgmma.mma_async.sync.aligned.m64n192k16.f32.bf16.bf16 {%0,%1,%2,%3,%4,%5,%6,%7,%8,%9,%10,%11,%12,%13,%14,%15,%16,%17,%18,%19,%20,%21,%22,%23,%24,%25,%26,%27,%28,%29,%30,%31,%32,%33,%34,%35,%36,%37,%38,%39,%40,%41,%42,%43,%44,%45,%46,%47,%48,%49,%50,%51,%52,%53,%54,%55,%56,%57,%58,%59,%60,%61,%62,%63,%64,%65,%66,%67,%68,%69,%70,%71,%72,%73,%74,%75,%76,%77,%78,%79,%80,%81,%82,%83,%84,%85,%86,%87,%88,%89,%90,%91,%92,%93,%94,%95}, xa, xb, p, 1, 1, 0, 1;\n}"
   :"+f"(d[0]),"+f"(d[1]),"+f"(d[2]),"+f"(d[3]),"+f"(d[4]),"+f"(d[5]),"+f"(d[6]),"+f"(d[7]),"+f"(d[8]),"+f"(d[9]),"+f"(d[10]),"+f"(d[11]),"+f"(d[12]),"+f"(d[13]),"+f"(d[14]),"+f"(d[15]),"+f"(d[16]),"+f"(d[17]),"+f"(d[18]),"+f"(d[19]),"+f"(d[20]),"+f"(d[21]),"+f"(d[22]),"+f"(d[23]),"+f"(d[24]),"+f"(d[25]),"+f"(d[26]),"+f"(d[27]),"+f"(d[28]),"+f"(d[29]),"+f"(d[30]),"+f"(d[31]),"+f"(d[32]),"+f"(d[33]),"+f"(d[34]),"+f"(d[35]),"+f"(d[36]),"+f"(d[37]),"+f"(d[38]),"+f"(d[39]),"+f"(d[40]),"+f"(d[41]),"+f"(d[42]),"+f"(d[43]),"+f"(d[44]),"+f"(d[45]),"+f"(d[46]),"+f"(d[47]),"+f"(d[48]),"+f"(d[49]),"+f"(d[50]),"+f"(d[51]),"+f"(d[52]),"+f"(d[53]),"+f"(d[54]),"+f"(d[55]),"+f"(d[56]),"+f"(d[57]),"+f"(d[58]),"+f"(d[59]),"+f"(d[60]),"+f"(d[61]),"+f"(d[62]),"+f"(d[63]),"+f"(d[64]),"+f"(d[65]),"+f"(d[66]),"+f"(d[67]),"+f"(d[68]),"+f"(d[69]),"+f"(d[70]),"+f"(d[71]),"+f"(d[72]),"+f"(d[73]),"+f"(d[74]),"+f"(d[75]),"+f"(d[76]),"+f"(d[77]),"+f"(d[78]),"+f"(d[79]),"+f"(d[80]),"+f"(d[81]),"+f"(d[82]),"+f"(d[83]),"+f"(d[84]),"+f"(d[85]),"+f"(d[86]),"+f"(d[87]),"+f"(d[88]),"+f"(d[89]),"+f"(d[90]),"+f"(d[91]),"+f"(d[92]),"+f"(d[93]),"+f"(d[94]),"+f"(d[95]):"r"(da),"r"(db),"r"(sc));
}
template<> __device__ __forceinline__ void wgmma_rs<80>(float* d,const uint32_t* a,uint32_t db,int sc){
  asm volatile("{\n.reg .pred p;\n.reg .b64 xb;\nmov.b64 xb, {%44, 0x40000040};\nsetp.ne.b32 p, %45, 0;\nwgmma.mma_async.sync.aligned.m64n80k16.f32.bf16.bf16 {%0,%1,%2,%3,%4,%5,%6,%7,%8,%9,%10,%11,%12,%13,%14,%15,%16,%17,%18,%19,%20,%21,%22,%23,%24,%25,%26,%27,%28,%29,%30,%31,%32,%33,%34,%35,%36,%37,%38,%39}, {%40,%41,%42,%43}, xb, p, 1, 1, 0;\n}"
   :"+f"(d[0]),"+f"(d[1]),"+f"(d[2]),"+f"(d[3]),"+f"(d[4]),"+f"(d[5]),"+f"(d[6]),"+f"(d[7]),"+f"(d[8]),"+f"(d[9]),"+f"(d[10]),"+f"(d[11]),"+f"(d[12]),"+f"(d[13]),"+f"(d[14]),"+f"(d[15]),"+f"(d[16]),"+f"(d[17]),"+f"(d[18]),"+f"(d[19]),"+f"(d[20]),"+f"(d[21]),"+f"(d[22]),"+f"(d[23]),"+f"(d[24]),"+f"(d[25]),"+f"(d[26]),"+f"(d[27]),"+f"(d[28]),"+f"(d[29]),"+f"(d[30]),"+f"(d[31]),"+f"(d[32]),"+f"(d[33]),"+f"(d[34]),"+f"(d[35]),"+f"(d[36]),"+f"(d[37]),"+f"(d[38]),"+f"(d[39]):"r"(a[0]),"r"(a[1]),"r"(a[2]),"r"(a[3]),"r"(db),"r"(sc));
}
template<> __device__ __forceinline__ void wgmma_rs<192>(float* d,const uint32_t* a,uint32_t db,int sc){
  asm volatile("{\n.reg .pred p;\n.reg .b64 xb;\nmov.b64 xb, {%100, 0x40000040};\nsetp.ne.b32 p, %101, 0;\nwgmma.mma_async.sync.aligned.m64n192k16.f32.bf16.bf16 {%0,%1,%2,%3,%4,%5,%6,%7,%8,%9,%10,%11,%12,%13,%14,%15,%16,%17,%18,%19,%20,%21,%22,%23,%24,%25,%26,%27,%28,%29,%30,%31,%32,%33,%34,%35,%36,%37,%38,%39,%40,%41,%42,%43,%44,%45,%46,%47,%48,%49,%50,%51,%52,%53,%54,%55,%56,%57,%58,%59,%60,%61,%62,%63,%64,%65,%66,%67,%68,%69,%70,%71,%72,%73,%74,%75,%76,%77,%78,%79,%80,%81,%82,%83,%84,%85,%86,%87,%88,%89,%90,%91,%92,%93,%94,%95}, {%96,%97,%98,%99}, xb, p, 1, 1, 1;\n}"
   :"+f"(d[0]),"+f"(d[1]),"+f"(d[2]),"+f"(d[3]),"+f"(d[4]),"+f"(d[5]),"+f"(d[6]),"+f"(d[7]),"+f"(d[8]),"+f"(d[9]),"+f"(d[10]),"+f"(d[11]),"+f"(d[12]),"+f"(d[13]),"+f"(d[14]),"+f"(d[15]),"+f"(d[16]),"+f"(d[17]),"+f"(d[18]),"+f"(d[19]),"+f"(d[20]),"+f"(d[21]),"+f"(d[22]),"+f"(d[23]),"+f"(d[24]),"+f"(d[25]),"+f"(d[26]),"+f"(d[27]),"+f"(d[28]),"+f"(d[29]),"+f"(d[30]),"+f"(d[31]),"+f"(d[32]),"+f"(d[33]),"+f"(d[34]),"+f"(d[35]),"+f"(d[36]),"+f"(d[37]),"+f"(d[38]),"+f"(d[39]),"+f"(d[40]),"+f"(d[41]),"+f"(d[42]),"+f"(d[43]),"+f"(d[44]),"+f"(d[45]),"+f"(d[46]),"+f"(d[47]),"+f"(d[48]),"+f"(d[49]),"+f"(d[50]),"+f"(d[51]),"+f"(d[52]),"+f"(d[53]),"+f"(d[54]),"+f"(d[55]),"+f"(d[56]),"+f"(d[57]),"+f"(d[58]),"+f"(d[59]),"+f"(d[60]),"+f"(d[61]),"+f"(d[62]),"+f"(d[63]),"+f"(d[64]),"+f"(d[65]),"+f"(d[66]),"+f"(d[67]),"+f"(d[68]),"+f"(d[69]),"+f"(d[70]),"+f"(d[71]),"+f"(d[72]),"+f"(d[73]),"+f"(d[74]),"+f"(d[75]),"+f"(d[76]),"+f"(d[77]),"+f"(d[78]),"+f"(d[79]),"+f"(d[80]),"+f"(d[81]),"+f"(d[82]),"+f"(d[83]),"+f"(d[84]),"+f"(d[85]),"+f"(d[86]),"+f"(d[87]),"+f"(d[88]),"+f"(d[89]),"+f"(d[90]),"+f"(d[91]),"+f"(d[92]),"+f"(d[93]),"+f"(d[94]),"+f"(d[95]):"r"(a[0]),"r"(a[1]),"r"(a[2]),"r"(a[3]),"r"(db),"r"(sc));
}
__global__ void __launch_bounds__(256) k_pre(const bf16* __restrict__ x,const bf16* __restrict__ mem0){
  const int warp=threadIdx.x>>5, lane=threadIdx.x&31;
  const int row=blockIdx.x*8+warp;
  asm volatile("griddepcontrol.launch_dependents;");
  {
    int i=blockIdx.x*256+threadIdx.x; constexpr int n=(S/8)*256;
    if(blockIdx.x==S/8){
      __shared__ uint32_t smx[8];
      uint32_t w[10], mx=0;
      #pragma unroll
      for(int j=0;j<10;j++){ const int k=threadIdx.x+256*j; const uint16_t* mp=(const uint16_t*)mem0+(((k>>3)&3)*2+((k>>5)&1))*D+(k>>6)*16+(k&7);
        w[j]=mp[0]|((uint32_t)mp[8]<<16); mx=max(mx,max(w[j]&0x7fffu,(w[j]>>16)&0x7fffu)); }
      mx=__reduce_max_sync(~0u,mx); if(lane==0) smx[warp]=mx;
      __syncthreads();
      #pragma unroll
      for(int j=0;j<8;j++) mx=max(mx,smx[j]);
      const uint32_t eb=min(max(mx>>7,40u),254u); const float sc=__uint_as_float((280u-eb)<<23);
      #pragma unroll
      for(int j=0;j<10;j++) g_acc[threadIdx.x+256*j]=((unsigned long long)(long long)__float2int_rn(__uint_as_float(w[j]&0xffff0000u)*sc)<<35)+((unsigned long long)(long long)__float2int_rn(__uint_as_float(w[j]<<16)*sc)<<6);
      if(threadIdx.x<NCTA*2) g_nrm[threadIdx.x]=SENT;
      if(threadIdx.x==0) g_nrm[NCTA*2]=(eb-29u)<<23;
      return;
    }
    for(int k=1280+i;k<NSEG*1280;k+=n) ((ulonglong2*)g_acc)[k]=make_ulonglong2(ACC_INIT,ACC_INIT);
    if(i==0) g_err=0;
    if(i<NCTA*32) g_flag[i]=0;
    if(i<C_NUM) g_cnt[i]=0;
  }
  float v[20];
  {
    const uint32_t* p=(const uint32_t*)(x+(size_t)row*D);
    #pragma unroll
    for(int i=0;i<10;i++){ uint32_t u=p[lane+32*i]; v[2*i]=__uint_as_float(u<<16); v[2*i+1]=__uint_as_float(u&0xffff0000u); }
  }
  #pragma unroll
  for(int pass=0;pass<2;pass++){
    float s=0;
    #pragma unroll
    for(int i=0;i<20;i++) s+=v[i];
    #pragma unroll
    for(int o=16;o;o>>=1) s+=__shfl_xor_sync(~0u,s,o);
    float mean=s*(1.f/D);
    float q=0;
    #pragma unroll
    for(int i=0;i<20;i++){ float d=v[i]-mean; q+=d*d; }
    #pragma unroll
    for(int o=16;o;o>>=1) q+=__shfl_xor_sync(~0u,q,o);
    float var=rb(q*(1.f/D)), mb=rb(mean);
    float den=rb(sqrtf(rb(var+1e-5f)));
    uint32_t* o=(uint32_t*)((pass?g_y:g_xn)+(size_t)row*D);
    #pragma unroll
    for(int i=0;i<10;i++){
      float a=rb(rb(v[2*i]-mb)/den), b=rb(rb(v[2*i+1]-mb)/den);
      v[2*i]=a; v[2*i+1]=b;
      o[lane+32*i]=pack_bf16(a,b);
    }
  }
}

#define ADELAY 0
#define KP 4
#define UXP 16
#define OPF 99
#define XGP 0
#define W3O 250
#define FW 3
#define WPA 17
#define WPB 17
#define PD 1000
#define PPOS 2
#define ADP 0
#define ADUP 64
#define ADDN 4
constexpr int SM_QS=0;
constexpr int SM_KS=49152;
constexpr int SM_OS=131072;
constexpr int SM_RED=180224;
constexpr int SM_P=SM_RED+3584;
constexpr int SM_PM=SM_RED+4096+3584;
constexpr int SM_MB=SM_PM+128;
constexpr int SM_MX=SM_PM+192, SM_SCL=SM_PM+224;
constexpr int SM_X5=SM_RED+8192+3584;
constexpr int SM_KX=SM_RED+16384;
constexpr int SM_VX=SM_KX+4096;
constexpr int SM_SCX=SM_VX+14336;
constexpr int SM_KRED=SM_SCX+6144;
constexpr int SM_VMX=SM_KRED+8192;
constexpr int SM_TOTAL=SM_VMX+3072, SM_NR=SM_VMX;
static_assert(SM_TOTAL<=232448,"smem");
__device__ __forceinline__ void wg32_rs(float* d,const uint32_t* a,uint32_t db){
  asm volatile("{\n.reg .b64 xb;\nmov.b64 xb, {%20, 0x40000040};\nwgmma.mma_async.sync.aligned.m64n32k16.f32.bf16.bf16 {%0,%1,%2,%3,%4,%5,%6,%7,%8,%9,%10,%11,%12,%13,%14,%15}, {%16,%17,%18,%19}, xb, 1, 1, 1, 0;\n}"
   :"+f"(d[0]),"+f"(d[1]),"+f"(d[2]),"+f"(d[3]),"+f"(d[4]),"+f"(d[5]),"+f"(d[6]),"+f"(d[7]),"+f"(d[8]),"+f"(d[9]),"+f"(d[10]),"+f"(d[11]),"+f"(d[12]),"+f"(d[13]),"+f"(d[14]),"+f"(d[15])
   :"r"(a[0]),"r"(a[1]),"r"(a[2]),"r"(a[3]),"r"(db));
}
__device__ __forceinline__ void wg32_rs0(float* d,const uint32_t* a,uint32_t db){
  asm volatile("{\n.reg .b64 xb;\nmov.b64 xb, {%20, 0x40000040};\nwgmma.mma_async.sync.aligned.m64n32k16.f32.bf16.bf16 {%0,%1,%2,%3,%4,%5,%6,%7,%8,%9,%10,%11,%12,%13,%14,%15}, {%16,%17,%18,%19}, xb, 0, 1, 1, 0;\n}"
   :"=f"(d[0]),"=f"(d[1]),"=f"(d[2]),"=f"(d[3]),"=f"(d[4]),"=f"(d[5]),"=f"(d[6]),"=f"(d[7]),"=f"(d[8]),"=f"(d[9]),"=f"(d[10]),"=f"(d[11]),"=f"(d[12]),"=f"(d[13]),"=f"(d[14]),"=f"(d[15])
   :"r"(a[0]),"r"(a[1]),"r"(a[2]),"r"(a[3]),"r"(db));
}
__device__ __forceinline__ void wg32_ss(float* d,uint32_t da,uint32_t db){
  asm volatile("{\n.reg .b64 xa, xb;\nmov.b64 xa, {%16, 0x00000180};\nmov.b64 xb, {%17, 0x40000040};\nwgmma.mma_async.sync.aligned.m64n32k16.f32.bf16.bf16 {%0,%1,%2,%3,%4,%5,%6,%7,%8,%9,%10,%11,%12,%13,%14,%15}, xa, xb, 1, 1, 1, 0, 0;\n}"
   :"+f"(d[0]),"+f"(d[1]),"+f"(d[2]),"+f"(d[3]),"+f"(d[4]),"+f"(d[5]),"+f"(d[6]),"+f"(d[7]),"+f"(d[8]),"+f"(d[9]),"+f"(d[10]),"+f"(d[11]),"+f"(d[12]),"+f"(d[13]),"+f"(d[14]),"+f"(d[15])
   :"r"(da),"r"(db));
}
__device__ __forceinline__ void wg32_ss0(float* d,uint32_t da,uint32_t db){
  asm volatile("{\n.reg .b64 xa, xb;\nmov.b64 xa, {%16, 0x00000180};\nmov.b64 xb, {%17, 0x40000040};\nwgmma.mma_async.sync.aligned.m64n32k16.f32.bf16.bf16 {%0,%1,%2,%3,%4,%5,%6,%7,%8,%9,%10,%11,%12,%13,%14,%15}, xa, xb, 0, 1, 1, 0, 0;\n}"
   :"=f"(d[0]),"=f"(d[1]),"=f"(d[2]),"=f"(d[3]),"=f"(d[4]),"=f"(d[5]),"=f"(d[6]),"=f"(d[7]),"=f"(d[8]),"=f"(d[9]),"=f"(d[10]),"=f"(d[11]),"=f"(d[12]),"=f"(d[13]),"=f"(d[14]),"=f"(d[15])
   :"r"(da),"r"(db));
}
template<int V> struct IC{ static constexpr int v=V; };
__device__ __forceinline__ uint32_t lds1(uint32_t a){ uint32_t v; asm volatile("ld.shared.u32 %0, [%1];":"=r"(v):"r"(a):"memory"); return v; }
__device__ __forceinline__ void sts1(uint32_t a,uint32_t x){ asm volatile("st.shared.u32 [%0], %1;"::"r"(a),"r"(x):"memory"); }

#define TS(i)
#define TSB(i)
#define PC(i) (void)np
#define TW(i)
#define TF(i)
#define TFP(i)

__device__ __forceinline__ void cp_commit(){ asm volatile("cp.async.commit_group;":::"memory"); }
template<int N> __device__ __forceinline__ void cp_wait(){ asm volatile("cp.async.wait_group %0;"::"n"(N):"memory"); }
__device__ __forceinline__ void tma2d(uint32_t dst,const CUtensorMap* tm,int c0,int c1,uint32_t mb){
  asm volatile("cp.async.bulk.tensor.2d.shared::cluster.global.mbarrier::complete_tx::bytes [%0], [%1, {%3, %4}], [%2];"::"r"(dst),"l"(tm),"r"(mb),"r"(c0),"r"(c1):"memory"); }
__device__ __forceinline__ void tma2d_pf(const CUtensorMap* tm,int c0,int c1){
  asm volatile("cp.async.bulk.prefetch.tensor.2d.L2.global [%0, {%1, %2}];"::"l"(tm),"r"(c0),"r"(c1):"memory"); }
__global__ void __launch_bounds__(256,1) k_rec(const __grid_constant__ CUtensorMap tmK,const __grid_constant__ CUtensorMap tmV,const bf16* __restrict__ Wq,const bf16* __restrict__ Wk,const bf16* __restrict__ Wv,const bf16* __restrict__ Wo,const uint32_t zero){
  extern __shared__ __align__(1024) uint8_t sm[];
  const int tid=threadIdx.x, warp=__shfl_sync(~0u,tid>>5,0), lane=tid&31, g=lane>>2, t=lane&3;
  const int b=blockIdx.x, h=b/3, c=b-3*h;
  const uint32_t sb=(uint32_t)__cvta_generic_to_shared(sm);
  const int kq=warp&3, mg=warp>>2, wt=warp-mg;
  const uint32_t s16=sb+lane*16;
  const uint32_t qs=lane*16+__shfl_sync(~0u,sb+(mg?SM_KS+kq*20480:SM_QS+kq*12288),0), m5u=__shfl_sync(~0u,sb+SM_X5+(kq>>1)*4096+(kq&1)*256,0), mo=((lane>>3)&1), os=sb+SM_OS+kq*12288+mo*6144+(lane>>4)*128+(lane&7)*16, us=sb+SM_VX+wt*2048+mo*512+(lane>>4)*128+(lane&7)*16;
  const uint32_t XS=sb+SM_MB, KVB=sb+SM_MB+8, XV=sb+SM_MB+16, XL=sb+SM_MB+24;
  GT(0);
  asm volatile("griddepcontrol.launch_dependents;");
  const int ntile=c==0?14:13, tile0=c==0?0:(1+13*c);
  uint32_t pw[40][4];
  auto ldW=[&](int p,uint32_t stg){
    #pragma unroll
    for(int i=0;i<12;i++){
      const int idx=tid+256*i, row=idx>>3, ch=idx&7, m=row>>7, f=160*((row>>5)&3)+32*p+(row&31);
      const bf16* src=(m==0?Wq:(m==1?Wk:Wv))+(size_t)f*HD+h*DH+64*c+ch*8;
      const int sw=(row>>1)&7;
      cp16(stg+row*128+((ch^sw)<<4),src);
    }
    cp_commit();
  };
  auto ldO=[&](int r,uint32_t stg){
    for(int idx=tid;idx<96*28;idx+=256){
      const int row=idx/28, ch=idx-row*28;
      if(ch<2*ntile) cp16(stg+row*464+ch*16,Wo+(size_t)(h*DH+((4*c+6*r+(row>>4))%12)*16+(row&15))*D+tile0*16+ch*8);
    }
    cp_commit();
  };
#define SG(i)
  float nr[2][4]={{0.f,0.f,0.f,0.f},{0.f,0.f,0.f,0.f}};
  auto sq=[&](const uint32_t* r){ mma1688(nr[0],r[0],r[1],r[0]); mma1688(nr[1],r[0],r[1],r[1]); mma1688(nr[0],r[2],r[3],r[2]); mma1688(nr[1],r[2],r[3],r[3]); };
  auto dg=[&](const float* d,int o){ return g==2*t?d[o]:(g==2*t+1?d[o+1]:0.f); };
  SG(0);
  ldW(0,sb+SM_RED);
  SG(1);
  #pragma unroll
  for(int p=0;p<5;p++){
    const uint32_t stg=sb+((p&1)?SM_OS:SM_RED), nstg=sb+((p&1)?SM_RED:SM_OS);
    if(p<4) ldW(p+1,nstg); else ldO(0,nstg);
    SG(2+3*p);
    cp_wait<1>(); __syncthreads();
    SG(3+3*p);
    #pragma unroll
    for(int e=0;e<2;e++){
      const int k=2*p+e, kb=(k+5)%10;
      const int fo=16*e+(lane&6)+(lane>>4)+8*(lane&1);
      const int sw=(fo>>1)&7;
      #pragma unroll
      for(int j=0;j<4;j++){
        const uint32_t a=stg+((mg*4+kq)*32+fo)*128+(((2*j+((lane>>3)&1))^sw)<<4);
        if(!mg){ if(k<6){ uint32_t r[4]; ldsm4t(r,a); sts4r(qs+(k*4+j)*512,r); } else ldsm4t(pw[k>=6?(k-6)*4+j:0],a); }
        else {
          if(kb<10-KP){ uint32_t r[4]; ldsm4t(r,a); sts4r(qs+(kb*4+j)*512,r); } else ldsm4t(pw[kb>=10-KP?(kb-10+KP)*4+j:0],a);
          const int u=kb*4+j;
          const uint32_t av=stg+((8+kq)*32+fo)*128+(((2*((j+kq)&3)+((lane>>3)&1))^sw)<<4);
          if(u<4*KP){ uint32_t r[4]; ldsm4t(r,av); sts4r(qs+(40-4*KP+u)*512,r); sq(r); } else { ldsm4t(pw[u],av); sq(pw[u]); }
        }
      }
    }
    __syncthreads();
    SG(4+3*p);
  }
  float nv=dg(nr[0],0)+dg(nr[1],2);
  #pragma unroll
  for(int o=16;o;o>>=1) nv+=__shfl_xor_sync(~0u,nv,o);
  if(lane==0) sts1(sb+SM_NR+warp*8,__float_as_uint(nv));
  nr[0][0]=nr[0][1]=nr[0][2]=nr[0][3]=0.f; nr[1][0]=nr[1][1]=nr[1][2]=nr[1][3]=0.f;
  #pragma unroll
  for(int r=0;r<2;r++){
    const uint32_t stg=sb+(r?SM_RED:SM_OS);
    if(r==0){ ldO(1,sb+SM_RED); cp_wait<1>(); } else cp_wait<0>();
    __syncthreads();
    SG(17+2*r);
    uint32_t rr[12][4];
    #pragma unroll
    for(int kk=0;kk<6;kk++){
      #pragma unroll
      for(int i=0;i<2;i++){
        int tl=2*wt+i; if(tl>=ntile) tl=0;
        const uint32_t a=stg+(16*kk+(lane&7)+(lane>>4)*8)*464+(2*tl+((lane>>3)&1))*16;
        if(mg){ ldsm4t(rr[kk*2+i],a); sq(rr[kk*2+i]); } else { ldsm4t(pw[16+r*12+kk*2+i],a); sq(pw[16+r*12+kk*2+i]); }
      }
    }
    __syncthreads();
    SG(18+2*r);
    if(mg){
      #pragma unroll
      for(int f=0;f<12;f++) stsm4(os+(r*12+f)*256,rr[f][0],rr[f][1],rr[f][2],rr[f][3]);
    }
  }
  {
    const uint32_t no=__reduce_max_sync(~0u,__float_as_uint(fmaxf(dg(nr[0],0),dg(nr[1],2))));
    if(lane==0) sts1(sb+SM_NR+warp*8+4,no);
  }
  if(tid==96){
    mbar_init(XS,5); mbar_init(KVB,1); mbar_init(XV,1); mbar_init(XL,4);
    asm volatile("fence.mbarrier_init.release.cluster;":::"memory");
    mbar_expect(XS,4096); mbar_expect(XV,2048);
  }
  auto kv_issue=[&](int sn){
    if(lane==0){
      mbar_expect(KVB,32*512);
      tma2d(sb+SM_KX,&tmK,h*DH+64*c,sn*32,KVB);
      #pragma unroll
      for(int i=0;i<3;i++) tma2d(sb+SM_VX+i*4096,&tmV,h*DH+64*i,sn*32,KVB);
    }
    __syncwarp();
  };
  auto kv_chk=[&](int rbk){
    if(lane==0){ int gd=0; while(ld_acq(g_cnt+C_KV+rbk)<64){ if(++gd>GUARD){ g_err=7; break; } } fence_async_g(); }
    __syncwarp();
  };
  auto kv_pf=[&](int sn){
    if(lane==0){ tma2d_pf(&tmK,h*DH+64*c,sn*32); tma2d_pf(&tmV,h*DH+64*c,sn*32); }
    __syncwarp();
  };
  fence_async();
  __syncthreads();
  SG(21);
  if(tid==0){
    float a=0.f; uint32_t o=0;
    #pragma unroll
    for(int w=0;w<8;w++){ const uint2 x=lds2(sb+SM_NR+w*8); a+=__uint_as_float(x.x); o=max(o,x.y); }
    stg_rlx2(g_nrm+b*2,min(__float_as_uint(a),0x7f800000u),min(o,0x7f800000u));
  }
  if(tid==32) sts1(sb+SM_SCL+8,g_nrm[NCTA*2]);
  if(warp==2){
    int gd=0; uint32_t x[6];
    #pragma unroll 1
    while(true){
      bool ok=true;
      #pragma unroll
      for(int i=0;i<6;i++){ asm volatile("ld.relaxed.gpu.global.u32 %0, [%1];":"=r"(x[i]):"l"(g_nrm+lane*6+i):"memory"); ok=ok&&x[i]!=SENT; }
      if(__all_sync(~0u,ok)) break;
      if(++gd>GUARD){ g_err=8; break; }
    }
    const float cw=27.5f*sqrtf((__uint_as_float(x[0])+__uint_as_float(x[2]))+__uint_as_float(x[4]))*sqrtf(__uint_as_float(max(x[1],max(x[3],x[5]))));
    sts1(sb+SM_SCL+4,__reduce_max_sync(~0u,__float_as_uint(cw)&0x7fffffffu));
  }
  if(warp==3){ kv_chk(0); kv_issue(0); kv_pf(1); kv_pf(2); }
  cluster_sync();
  SG(22);
  uint32_t pd=PD;
  bool dead=false;
  const uint32_t qrd=sb+SM_RED+1024+((lane>>3)&1)*4096+(lane>>4)*128+(lane&7)*16+kq*256;
  uint32_t rsc[2];
  rsc[0]=mapa(sb,c==2?0:c+1); rsc[1]=mapa(sb,c==0?2:c-1);
  GT(1);
  auto loop=[&](auto MGc){
  constexpr int MG=decltype(MGc)::v;
  uint32_t buf[8][4];
  uint32_t t0; asm volatile("mov.u32 %0, %%clock;":"=r"(t0)); t0-=4096;
  #define MB0(k) mb[k][0]
  #define MB1(k) mb[k][1]
  #pragma unroll 1
  for(int s=0;s<NSEG;s++){
    const bool last=s==NSEG-1;
    float u[2][16];
    const char* src=(const char*)g_acc+(uint32_t)(s*20480+(kq*10+MG*5)*512+(g&1)*256+(g>>1)*64+t*16);
    uint4 m[5];
    #define SPIN(T,N) { uint32_t t1; do{ asm volatile("mov.u32 %0, %%clock;":"=r"(t1)); }while((int)(t1-(T))<(int)(N)); }
    #define PLD { SPIN(t0,pd) _Pragma("unroll") for(int p=0;p<5;p++) m[p]=ldg_rlx4((const uint32_t*)(src+p*512)); SPIN(t0,pd) TFP(21); }
    #define PL1 { SPIN(t0,kq?0:pd) _Pragma("unroll") for(int p=0;p<5;p++) asm volatile("{\n.reg .pred p;\nsetp.eq.b32 p, %5, 0;\nmov.b32 %0, 0;\nmov.b32 %1, 0;\nmov.b32 %2, 0;\nmov.b32 %3, 0;\n@p ld.relaxed.gpu.global.v4.u32 {%0,%1,%2,%3}, [%4];\n}":"=r"(m[p].x),"=r"(m[p].y),"=r"(m[p].z),"=r"(m[p].w):"l"(src+p*512),"r"(kq):"memory"); \
      asm volatile("wgmma.fence.sync.aligned;":::"memory"); }
    #define PL2 { SPIN(t0,pd) asm volatile("{\n.reg .pred p;\nsetp.eq.b32 p, %21, 0;\n@p bra.uni PLSKIP;\nld.relaxed.gpu.global.v4.u32 {%0,%1,%2,%3}, [%20];\nld.relaxed.gpu.global.v4.u32 {%4,%5,%6,%7}, [%20+512];\nld.relaxed.gpu.global.v4.u32 {%8,%9,%10,%11}, [%20+1024];\nld.relaxed.gpu.global.v4.u32 {%12,%13,%14,%15}, [%20+1536];\nld.relaxed.gpu.global.v4.u32 {%16,%17,%18,%19}, [%20+2048];\nPLSKIP:\n}" \
      :"+r"(m[0].x),"+r"(m[0].y),"+r"(m[0].z),"+r"(m[0].w),"+r"(m[1].x),"+r"(m[1].y),"+r"(m[1].z),"+r"(m[1].w),"+r"(m[2].x),"+r"(m[2].y),"+r"(m[2].z),"+r"(m[2].w),"+r"(m[3].x),"+r"(m[3].y),"+r"(m[3].z),"+r"(m[3].w),"+r"(m[4].x),"+r"(m[4].y),"+r"(m[4].z),"+r"(m[4].w):"l"(src),"r"(kq):"memory"); SPIN(t0,pd) }
    {
      if(ADELAY&&!MG&&warp<3) SPIN(t0,ADELAY)
      { int gd=0; while(!mbar_try(KVB,s&1)){ if(dead||last) break; if(++gd>GUARD){ dead=true; g_err=6; } } }
      TFP(16);
      const uint32_t da=(((sb+SM_OS)>>4)&0x3fff)|(8u<<16);
      const uint32_t dv=(((sb+SM_VX)>>4)&0x3fff)|(1u<<16);
      const uint32_t vb[3]={dv+c*256,dv+(c==2?0:c+1)*256,dv+(c==0?2:c-1)*256};
      asm volatile("wgmma.fence.sync.aligned;":::"memory");
      if constexpr(MG){
        #pragma unroll
        for(int i=0;i<2;i++)
          #pragma unroll
          for(int x=0;x<12;x++){
            if(x==0) wg32_ss0(u[i],da+i*16,vb[0]); else wg32_ss(u[i],da+(x*2+i)*16,vb[x>>2]+(x&3)*2);
            if(PPOS==3&&i*12+x==WPB) PL1
          }
      } else {
        #pragma unroll
        for(int i=0;i<2;i++)
          #pragma unroll
          for(int x=0;x<12;x++){
            if(x==0) wg32_rs0(u[i],pw[16+i],vb[0]); else wg32_rs(u[i],pw[16+x*2+i],vb[x>>2]+(x&3)*2);
            if(PPOS==3&&i*12+x==WPA) PL1
          }
      }
      asm volatile("wgmma.commit_group.sync.aligned;":::"memory");
      TFP(18);
      if(PPOS==2) PLD
      if(PPOS==3) PL2
    }
    const uint32_t mx=s16+SM_RED+kq*4096, m5=m5u+lane*8;
    {
      asm volatile("wgmma.wait_group.sync.aligned 0;":::"memory");
      TFP(19);
      if(MG||warp!=3){
        bar_sync(7,256);
        TFP(20);
        #pragma unroll
        for(int i=0;i<2;i++)
          #pragma unroll
          for(int kk=0;kk<2;kk++)
            stsm4(us+i*1024+kk*256,pack_bf16(u[i][8*kk],u[i][8*kk+1]),pack_bf16(u[i][8*kk+2],u[i][8*kk+3]),pack_bf16(u[i][8*kk+4],u[i][8*kk+5]),pack_bf16(u[i][8*kk+6],u[i][8*kk+7]));
        #pragma unroll
        for(int i=0;i<8;i++) lds4r(buf[i],qs+i*512);
      } else {
        bar_arrive(7,256);
        #pragma unroll
        for(int i=0;i<8;i++) lds4r(buf[i],qs+i*512);
        asm volatile("{\n.reg .pred p, q;\nsetp.eq.u32 p, %0, 0;\nsetp.eq.and.u32 q, %1, 0, p;\n@q fence.release.gpu;\n@p st.relaxed.gpu.global.u32 [%2], %3;\n}"::"r"(lane),"r"(s&3),"l"(g_flag+b*32),"r"(s):"memory");
      }
      SPIN(t0,pd)
      TFP(17);
    }
    uint32_t mb[10][2];
    {
      auto okf=[&](const uint4& v){ return ((v.x|v.z)&63u)==0; };
      const int np=poll2<5>(m,[&](int i){ return ldg_rlx4((const uint32_t*)(src+i*512)); },okf,dead,1);
      TW(0); PC(0); TFP(14);
      if(ADP){ if(np) pd=min(pd+ADUP,2000u); else pd=max(pd-ADDN,(uint32_t)ADP); }
      #pragma unroll
      for(int p=0;p<5;p++){
        mb[p][0]=pack_bf16((float)(int)__funnelshift_r(m[p].x,m[p].y,3),(float)(int)m[p].y);
        mb[p][1]=pack_bf16((float)(int)__funnelshift_r(m[p].z,m[p].w,3),(float)(int)m[p].w);
        if(p==0) sts2(MG?m5:mx-lane*8+3072,mb[0][0],mb[0][1]);
        if(p==2||p==4) sts4(mx+((MG?0:4)+(p>>2))*512,make_uint4(mb[p-1][0],mb[p-1][1],mb[p][0],mb[p][1]));
      }
      bar_arrive((MG?12:8)+kq,64);
    }
    #define XGET { bar_sync((MG?8:12)+kq,64); const uint2 x=lds2(MG?mx-lane*8+3072:m5); mb[5][0]=x.x; mb[5][1]=x.y; \
      _Pragma("unroll") for(int p=0;p<2;p++){ const uint4 y=lds4(mx+((MG?4:0)+p)*512); mb[6+2*p][0]=y.x; mb[6+2*p][1]=y.y; mb[7+2*p][0]=y.z; mb[7+2*p][1]=y.w; } }
    #define XMAX { uint32_t a=amax2(amax2(amax2(mb[0][0],mb[0][1]),amax2(mb[1][0],mb[1][1])),amax2(amax2(amax2(mb[2][0],mb[2][1]),amax2(mb[3][0],mb[3][1])),amax2(mb[4][0],mb[4][1]))); \
      a=__reduce_max_sync(~0u,max(a&0x7fff0000u,(a<<16)&0x7fff0000u)); if(lane==0) sts1(sb+SM_MX+warp*4,a); }
    TS(0); TF(0);
    float acc[4][4]; uint32_t ux[2][2][4];
    #pragma unroll
    for(int i=0;i<4;i++){ acc[i][0]=acc[i][1]=acc[i][2]=acc[i][3]=0.f; }
    #define UXDEP (((ux[0][0][0]^ux[0][1][0])^(ux[1][0][0]^ux[1][1][0]))&zero)
    const uint32_t exo=(uint32_t)(((s*8+g)*HD+h*DH+64*c+16*kq+2*t)*2);
    if constexpr(MG){
      #pragma unroll
      for(int y=0;y<10;y++){
        const int k=KP==4?(y<2?y:(y<4?y+4:(y<6?y-2:(y<8?y+2:y-4)))):(y<2?y:(y<2+KP?y+8-KP:y-KP));
        #pragma unroll
        for(int j=0;j<4;j++){
          if(k<10-KP){ mma16816(acc[j],buf[(k&1)*4+j],MB0(k),MB1(k)); lds4r(buf[(k&1)*4+j],qs+(k*4+j+8)*512); }
          else mma16816(acc[j],pw[k>=10-KP?(k-10+KP)*4+j:0],MB0(k),MB1(k));
        }
        if(y==XGP) XGET
        if(y==5) XMAX
      }
      TF(1);
      {
        const uint32_t ra=s16+SM_KRED+kq*2048;
        #pragma unroll
        for(int i=0;i<4;i++) sts4f(ra+i*512,acc[i]);
      }
      bar_arrive(1,256);
#define VK(u) ((u)>>2)
      #pragma unroll
      for(int i=0;i<4;i++){ acc[i][0]=acc[i][1]=acc[i][2]=acc[i][3]=0.f; }
      #pragma unroll
      for(int y=0;y<40;y++){
        constexpr int NS_=4*KP;
        const int u=y<8?y:(y<20?y-8+NS_:(y<12+NS_?y-12:y));
        const int sl=(u+40-NS_)&7;
        if(u<NS_){ mma16816(acc[u&3],buf[sl],MB0(VK(u)),MB1(VK(u))); if(u+8<NS_) lds4r(buf[sl],qs+(48-NS_+u)*512); }
        else mma16816(acc[u&3],pw[u],MB0(VK(u)),MB1(VK(u)));
        if(y>=OPF&&y<OPF+8) ldsm4(buf[(y-OPF)&7],os+((y-OPF)&7)*256);
        if(y>=UXP&&y<UXP+4) ldsm4(ux[(y-UXP)>>1][(y-UXP)&1],us+((y-UXP)>>1)*1024+((y-UXP)&1)*256);
      }
      TF(2);
      const uint32_t ra=s16+SM_RED+1536;
      #pragma unroll
      for(int i=1;i<4;i++) sts4f(ra+kq*4096+i*512,acc[i]);
      bar_sync(3,128);
      const float cs=__uint_as_float(lds1(sb+SM_SCL+8+(s&1)*4));
      float4 c1=lds4f(ra+((kq+3)&3)*4096+512), d2=lds4f(ra+((kq+2)&3)*4096+1024), e2=lds4f(ra+((kq+1)&3)*4096+1536);
      const uint32_t p0=pack_bf16(((acc[0][0]+c1.x)+(d2.x+e2.x))*cs,((acc[0][1]+c1.y)+(d2.y+e2.y))*cs), p1=pack_bf16(((acc[0][2]+c1.z)+(d2.z+e2.z))*cs,((acc[0][3]+c1.w)+(d2.w+e2.w))*cs);
      if(!last) bar_arrive(2+UXDEP,256);
      const uint32_t v0=movm(p0), v1=movm(p1);
      const uint32_t off=SM_VMX+(kq>>1)*512+lane*16+(kq&1)*8;
      if(!last){
        #pragma unroll
        for(int r=0;r<2;r++) st_async2(rsc[r]+off+(2-r)*1024,v0,v1,rsc[r]+SM_MB+16);
        sts2(sb+off,v0,v1); __syncwarp(); if(lane==0) mbar_arrive(XL);
      }
      TF(5);
      if(OPF>=40){
        #pragma unroll
        for(int i=0;i<8;i++) ldsm4(buf[i],os+i*256);
      }
      stg_rlx1((uint32_t*)((char*)g_vm+exo),v0); stg_rlx1((uint32_t*)((char*)g_vm+exo+16),v1);
      if(last) break;
    } else {
      uint32_t kb[8];
      #pragma unroll
      for(int y=0;y<10;y++){
        const int k=y<2?y:(y<4?y+4:(y<6?y-2:(y<8?y+2:y-4)));
        #pragma unroll
        for(int j=0;j<4;j++){
          if(k<6){ mma16816(acc[j],buf[(k&1)*4+j],MB0(k),MB1(k)); if(k<4) lds4r(buf[(k&1)*4+j],qs+(k*4+j+8)*512); }
          else mma16816(acc[j],pw[k>=6?(k-6)*4+j:0],MB0(k),MB1(k));
        }
        if(y==7){
          const uint32_t ka=sb+SM_KX+(8*kq+(lane&7))*128+((((lane>>3)^(2*kq))^(lane&7))<<4);
          ldsm4(kb,ka); ldsm4(kb+4,ka^64);
        }
        if(y==XGP) XGET
        if(y==5) XMAX
      }
      TF(1);
      {
        const uint32_t qa=s16+SM_RED+kq*4096+1024;
        #pragma unroll
        for(int i=0;i<2;i++) stsm4(qa+i*512,pack_bf16(acc[2*i][0],acc[2*i][1]),pack_bf16(acc[2*i][2],acc[2*i][3]),pack_bf16(acc[2*i+1][0],acc[2*i+1][1]),pack_bf16(acc[2*i+1][2],acc[2*i+1][3]));
      }
      TF(2);
      bar_sync(1,256);
      TS(1); TF(3);
      const uint32_t ra=s16+SM_KRED+kq*512;
      const float cs=__uint_as_float(lds1(sb+SM_SCL+8+(s&1)*4));
      float4 a3=lds4f(ra), c3=lds4f(ra+2048), d3=lds4f(ra+4096), e3=lds4f(ra+6144);
      uint32_t q[4][2][4];
      #pragma unroll
      for(int i=0;i<4;i++){ ldsm4t(q[i][0],qrd^(i*256)); ldsm4t(q[i][1],(qrd^(i*256))+8192); }
      const uint32_t p2=pack_bf16(((a3.x+c3.x)+(d3.x+e3.x))*cs,((a3.y+c3.y)+(d3.y+e3.y))*cs), p3=pack_bf16(((a3.z+c3.z)+(d3.z+e3.z))*cs,((a3.w+c3.w)+(d3.w+e3.w))*cs);
      const uint32_t f2=movm(p2), f3=movm(p3);
      if(last){ stg_rlx1((uint32_t*)((char*)g_km+exo),f2); stg_rlx1((uint32_t*)((char*)g_km+exo+16),f3); break; }
      float sc[6][4];
      #pragma unroll
      for(int i=0;i<6;i++){ sc[i][0]=sc[i][1]=sc[i][2]=sc[i][3]=0.f; }
      #pragma unroll
      for(int i=0;i<4;i++)
        #pragma unroll
        for(int jp=0;jp<2;jp++){
          mma16816(sc[(i&1)*2+jp],q[i][jp],kb[2*i],kb[2*i+1]);
          if(i==1) mma16816(sc[4+jp],q[0][jp],f2,f3);
        }
      const uint32_t w0=__float_as_uint(((sc[0][0]+sc[0][2])+(sc[1][0]+sc[1][2]))+((sc[2][0]+sc[2][2])+(sc[3][0]+sc[3][2]))), w1=__float_as_uint(((sc[0][1]+sc[0][3])+(sc[1][1]+sc[1][3]))+((sc[2][1]+sc[2][3])+(sc[3][1]+sc[3][3])));
      const uint32_t w2=__float_as_uint((sc[4][0]+sc[4][2])+(sc[5][0]+sc[5][2])), w3=__float_as_uint((sc[4][1]+sc[4][3])+(sc[5][1]+sc[5][3]));
      const uint32_t off=SM_SCX+(c*4+kq)*512+lane*16;
      #pragma unroll
      for(int r=0;r<2;r++) st_async4(rsc[r]+off,w0,w1,w2,w3,rsc[r]+SM_MB);
      sts4(sb+off,make_uint4(w0,w1,w2,w3)); __syncwarp(); if(lane==0) mbar_arrive(XS);
      TS(2); TF(5);
      stg_rlx1((uint32_t*)((char*)g_km+exo),f2); stg_rlx1((uint32_t*)((char*)g_km+exo+16),f3);
    }
    if(!MG&&warp==3){
      bar_arrive(2,256);
      const float ssc=0.07216878364870322f*__uint_as_float(lds1(sb+SM_SCL+8+(s&1)*4));
      uint32_t kvc; asm volatile("ld.relaxed.gpu.global.u32 %0, [%1];":"=r"(kvc):"l"(g_cnt+C_KV+(((s>>2)+1)&15)):"memory");
      TF(6);
      { int gd=0; while(!mbar_try(XS,s&1)){ if(dead) break; if(++gd>GUARD){ dead=true; g_err=2; } } }
      TF(7);
      float sv[10];
      {
        float4 u[12];
        #pragma unroll
        for(int n=0;n<12;n++) u[n]=lds4f(s16+SM_SCX+n*512);
        uint32_t r[5];
        #pragma unroll
        for(int n=0;n<4;n++) r[n+1]=pack_bf16((u[n].x+u[4+n].x)+u[8+n].x,(u[n].y+u[4+n].y)+u[8+n].y);
        r[0]=pack_bf16((((u[0].z+u[1].z)+(u[2].z+u[3].z))+((u[4].z+u[5].z)+(u[6].z+u[7].z)))+((u[8].z+u[9].z)+(u[10].z+u[11].z)),
                       (((u[0].w+u[1].w)+(u[2].w+u[3].w))+((u[4].w+u[5].w)+(u[6].w+u[7].w)))+((u[8].w+u[9].w)+(u[10].w+u[11].w)));
        #pragma unroll
        for(int n=0;n<5;n++){
          const uint32_t w=pack_bf16(__uint_as_float(r[n]<<16)*ssc,__uint_as_float(r[n]&0xffff0000u)*ssc);
          sv[2*n]=__uint_as_float(w<<16); sv[2*n+1]=__uint_as_float(w&0xffff0000u);
        }
      }
      TF(8);
      float mx=fmaxf(fmaxf(fmaxf(sv[2],sv[3]),fmaxf(sv[4],sv[5])),fmaxf(fmaxf(fmaxf(sv[6],sv[7]),fmaxf(sv[8],sv[9])),fmaxf(sv[0],sv[1])));
      mx=fmaxf(mx,__shfl_xor_sync(~0u,mx,1)); mx=fmaxf(mx,__shfl_xor_sync(~0u,mx,2));
      mx*=-1.4426950408889634f;
      #pragma unroll
      for(int i=0;i<10;i++) sv[i]=ex2(fmaf(sv[i],1.4426950408889634f,mx));
      sts1(sb+SM_PM+lane*4,pack_bf16(sv[0],sv[1]));
      sts4(s16+SM_P,make_uint4(pack_bf16(sv[2],sv[3]),pack_bf16(sv[4],sv[5]),pack_bf16(sv[6],sv[7]),pack_bf16(sv[8],sv[9])));
      TF(9);
      bar_sync(4,256);
      asm volatile("mov.u32 %0, %%clock;":"=r"(t0)); t0+=W3O;
      TF(11);
      if(lane==0){
        mbar_expect(XS,4096); mbar_expect(XV,2048);
        if((s&3)==2){ int gd=0; while(kvc<64&&s<NSEG-4){ kvc=ld_acq(g_cnt+C_KV+(s>>2)+1); if(++gd>GUARD){ g_err=7; break; } } fence_acq(); fence_async_g(); }
        TF(12);
        if(s+4<NSEG){ tma2d_pf(&tmK,h*DH+64*c,(s+3)*32); tma2d_pf(&tmV,h*DH+64*c,(s+3)*32); }
      }
      __syncwarp();
      if(b<80&&lane<2&&s+3<NSEG) asm volatile("prefetch.global.L2 [%0];"::"l"(g_acc+(size_t)(s+3)*2560+b*32+lane*16));
      TF(13);
    } else {
      if constexpr(!MG){
        #pragma unroll
        for(int i=0;i<2;i++){ ldsm4(ux[i][0],us+i*1024); ldsm4(ux[i][1],us+i*1024+256); }
        {
          const uint4 x=lds4(sb+SM_MX), y=lds4(sb+SM_MX+16); const float cw=__uint_as_float(lds1(sb+SM_SCL+4)), cs=__uint_as_float(lds1(sb+SM_SCL+8+(s&1)*4));
          const float mm=__uint_as_float(max(max(max(x.x,x.y),max(x.z,x.w)),max(max(y.x,y.y),max(y.z,y.w))))*cs;
          const uint32_t eo=min(max((__float_as_uint(cw*fmaxf(mm,1.f))>>23)&255u,37u),254u)-21u;
          if(tid==64){ sts1(sb+SM_SCL,eo*0x00800080u); sts1(sb+SM_SCL+12-(s&1)*4,(eo-3u)<<23); }
        }
        TF(4);
        bar_sync(2+UXDEP,256);
        if(s+2<NSEG&&lane==0){
          tma2d(sb+SM_VX+kq*4096,&tmV,h*DH+64*kq,(s+1)*32,KVB);
          if(kq==0) mbar_expect(KVB,32*512);
          if(kq==1) tma2d(sb+SM_KX,&tmK,h*DH+64*c,(s+1)*32,KVB);
        }
        __syncwarp();
      }
      float ca[2][2][4];
      #pragma unroll
      for(int i=0;i<2;i++)
        #pragma unroll
        for(int j=0;j<2;j++){ ca[i][j][0]=ca[i][j][1]=ca[i][j][2]=ca[i][j][3]=0.f; }
      TF(6);
      { int gd=0; while(!mbar_try(XL,s&1)){ if(dead) break; if(++gd>GUARD){ dead=true; g_err=5; } } }
      TF(7);
      uint4 vm[6];
      vm[0]=lds4(s16+SM_VMX); vm[1]=lds4(s16+SM_VMX+512);
      #define VB0(x) (((x)&1)?vm[(x)>>1].z:vm[(x)>>1].x)
      #define VB1(x) (((x)&1)?vm[(x)>>1].w:vm[(x)>>1].y)
      if constexpr(MG){
        #pragma unroll
        for(int x=0;x<12;x++){
          if(x==4){
            TF(8);
            { int gd=0; while(!mbar_try(XV,s&1)){ if(dead) break; if(++gd>GUARD){ dead=true; g_err=3; } } }
            TF(9);
            #pragma unroll
            for(int i=2;i<6;i++) vm[i]=lds4(s16+SM_VMX+i*512);
          }
          #pragma unroll
          for(int i=0;i<2;i++){
            mma16816(ca[i][x&1],buf[(x*2+i)&7],VB0(x),VB1(x));
            if(x<8) ldsm4(buf[(x*2+i)&7],os+(x*2+i+8)*256);
          }
        }
      } else {
        #pragma unroll
        for(int x=0;x<12;x++){
          if(x==4){
            TF(8);
            { int gd=0; while(!mbar_try(XV,s&1)){ if(dead) break; if(++gd>GUARD){ dead=true; g_err=3; } } }
            TF(9);
            #pragma unroll
            for(int i=2;i<6;i++) vm[i]=lds4(s16+SM_VMX+i*512);
          }
          #pragma unroll
          for(int i=0;i<2;i++) mma16816(ca[i][x&1],pw[16+x*2+i],VB0(x),VB1(x));
        }
      }
      TF(10);
      bar_sync(4,256);
      TS(3); TF(11);
      const uint4 pq=lds4(s16+SM_P); const uint32_t pm=lds1(sb+SM_PM+lane*4), on=lds1(sb+SM_SCL);
      const uint32_t one[4]={on,on,on,on};
      float d[2][4], e[4];
      #pragma unroll
      for(int i=0;i<4;i++){ d[0][i]=0.f; d[1][i]=0.f; e[i]=0.f; }
      mma16816(e,one,pq.x,pq.y); mma16816(d[0],ux[0][0],pq.x,pq.y); mma16816(d[1],ux[1][0],pq.x,pq.y);
      mma16816(e,one,pq.z,pq.w); mma16816(d[0],ux[0][1],pq.z,pq.w); mma16816(d[1],ux[1][1],pq.z,pq.w);
      mma1688(e,one[0],one[0],pm);
      #pragma unroll
      for(int i=0;i<2;i++) mma1688(d[i],pack_bf16(ca[i][0][0]+ca[i][1][0],ca[i][0][1]+ca[i][1][1]),pack_bf16(ca[i][0][2]+ca[i][1][2],ca[i][0][3]+ca[i][1][3]),pm);
      const float i0=rcp(e[0]), i1=rcp(e[1]);
      TF(12);
      char* dst=(char*)g_acc+(uint32_t)((s+1)*20480+(tile0+2*wt)*512+t*64+g*8);
      #pragma unroll
      for(int i=0;i<2;i++){
        if(i==0||2*wt+1<ntile){
          red64(dst+i*512,(__float_as_uint(fmaf(d[i][0],i0,12582912.f))<<6)+1u,__float_as_uint(fmaf(d[i][2],i0,12582912.f))<<3);
          red64(dst+i*512+256,(__float_as_uint(fmaf(d[i][1],i1,12582912.f))<<6)+1u,__float_as_uint(fmaf(d[i][3],i1,12582912.f))<<3);
        }
      }
      asm volatile("mov.u32 %0, %%clock;":"=r"(t0));
      TW(1);
      TS(4); TF(13);
    }
  }
  };
  if(mg) loop(IC<1>{}); else loop(IC<0>{});
  __syncthreads();
  if(tid==FW*32){ fence_rel(); stg_rlx1(g_flag+b*32,NSEG); }
  GT(2);
  cluster_sync();
}

#define FAG fence_async_g
enum { M_XN=0,M_Y,M_H,M_OX,M_K,M_V,M_GATE,M_WQ,M_WK,M_WV,M_W1,M_W2,M_WO,M_KM,M_VM,M_NUM,M_OUT };
struct WParams { CUtensorMap m[M_NUM]; const bf16* x; const bf16* b1; const bf16* b2; bf16* out; const bf16* wq; const bf16* wo; };
#define WPF 99
enum { T_RED=0,T_OP=1,T_QA=2,T_M2=3,T_M1=4,T_KV=5,T_END=6 };
#define KVUP 1024
#define TRIG 10
#define SOV 1
#define LATE 14
#define E15 2
#define OPE 15
#define Q15 5
#define HB 1
#define EARLY 2
constexpr int NRB=16;
constexpr int STG=40960, NST=4, SLOT=30720, BOXS=10240;
constexpr int W_SLOT=NST*STG;
constexpr int W_BAR=W_SLOT+2*SLOT;
constexpr int W_TOTAL=W_BAR+1024;
static_assert(W_TOTAL<=232448,"smem");
#define ST(i)
#define QT(i)
__device__ __forceinline__ void stsm4n(uint32_t a,uint32_t r0,uint32_t r1,uint32_t r2,uint32_t r3){ asm volatile("stmatrix.sync.aligned.m8n8.x4.shared.b16 [%0], {%1,%2,%3,%4};"::"r"(a),"r"(r0),"r"(r1),"r"(r2),"r"(r3)); }
#define WGUARD 2000000
__host__ __device__ constexpr int n_uns(){ int n=0; while(n<16&&nsp(n)==1) n++; return n; }
__host__ __device__ constexpr int n_op(){ int n=0; for(int r=0;r<NRB;r++) n+=4*nsp(r); return n; }
__host__ __device__ constexpr int n_red(){ int n=0; for(int r=0;r<NRB;r++) if(nsp(r)>1) n+=5*nsp(r); return n; }

__device__ __forceinline__ void wg_arrive(){ asm volatile("wgmma.fence.sync.aligned;":::"memory"); }
__device__ __forceinline__ void wg_commit(){ asm volatile("wgmma.commit_group.sync.aligned;":::"memory"); }
template<int N> __device__ __forceinline__ void wg_wait(){ asm volatile("wgmma.wait_group.sync.aligned %0;"::"n"(N):"memory"); }
__device__ __forceinline__ void mbar_wait(uint32_t a,uint32_t par){ int gd=0; while(!mbar_try(a,par)){ if(++gd>WGUARD){ g_err=20; break; } } }
__device__ __forceinline__ uint32_t ld_rlx(const uint32_t* p){ uint32_t v; asm volatile("ld.relaxed.gpu.global.u32 %0, [%1];":"=r"(v):"l"(p):"memory"); return v; }
__device__ __forceinline__ float4 ld_rlx4f(const float4* p){ float4 v; asm volatile("ld.relaxed.gpu.global.v4.f32 {%0,%1,%2,%3}, [%4];":"=f"(v.x),"=f"(v.y),"=f"(v.z),"=f"(v.w):"l"(p):"memory"); return v; }
__device__ __forceinline__ void red_rel(uint32_t* p){ asm volatile("red.release.gpu.global.add.u32 [%0], 1;"::"l"(p):"memory"); }
__device__ __forceinline__ void tma_st(const CUtensorMap* tm,uint32_t src,int c0,int c1){
  asm volatile("cp.async.bulk.tensor.2d.global.shared::cta.bulk_group [%0, {%2, %3}], [%1];"::"l"(tm),"r"(src),"r"(c0),"r"(c1):"memory"); }
__device__ __forceinline__ void bulk_commit(){ asm volatile("cp.async.bulk.commit_group;":::"memory"); }
__device__ __forceinline__ void bulk_wait_rd(){ asm volatile("cp.async.bulk.wait_group.read 0;":::"memory"); }
__device__ __forceinline__ void bulk_wait(){ asm volatile("cp.async.bulk.wait_group 0;":::"memory"); }
__device__ __forceinline__ void mbar_arrive_cl(uint32_t a){ asm volatile("mbarrier.arrive.shared::cluster.b64 _, [%0];"::"r"(a):"memory"); }
__device__ __forceinline__ void tma2dm(uint32_t dst,const CUtensorMap* tm,int c0,int c1,uint32_t mb){
  asm volatile("cp.async.bulk.tensor.2d.shared::cluster.global.mbarrier::complete_tx::bytes.multicast::cluster [%0], [%1, {%3, %4}], [%2], %5;"::"r"(dst),"l"(tm),"r"(mb),"r"(c0),"r"(c1),"h"((uint16_t)3):"memory"); }

template<int N,int CL,int XS> __device__ __forceinline__ void mainloop(float* acc,int nkb,uint32_t sb,int lane,uint32_t pos){
  const uint32_t eb=CL?mapa(sb+W_BAR+32,lane&1):sb+W_BAR+32;
  uint32_t pst=0;
  #pragma unroll
  for(int i=0;i<N/2;i++){ acc[i]=0.f; acc[96+i]=0.f; }
  #pragma unroll 1
  for(int kb=0;kb<nkb;kb++,pos++){
    const uint32_t st=pos&3;
    mbar_wait(sb+W_BAR+st*8,(pos>>2)&1);
    if(!XS&&kb==nkb-1&&(threadIdx.x&127)==0) mbar_arrive(sb+W_BAR+144);
    const uint32_t a=sb+st*STG;
    const uint32_t da=((a>>4)&0x3fff)|(1u<<16);
    const uint32_t db=da+1024+(511u<<16);
    wg_arrive();
    #pragma unroll
    for(int k=0;k<4;k++){ wgmma<N>(acc,da+2*k,db+128*k,kb|k); wgmma<N>(acc+96,da+512+2*k,db+128*k,kb|k); }
    wg_commit();
    if(kb>0){ wg_wait<1>(); if(CL){ if(lane<2) mbar_arrive_cl(eb+pst*8); } else if(lane==0) mbar_arrive(eb+pst*8); }
    pst=st;
  }
  if(XS){
    #pragma unroll
    for(int x=0;x<XS;x++) mbar_wait(sb+W_BAR+((pos+x)&3)*8,((pos+x)>>2)&1);
    if((threadIdx.x&127)==0) mbar_arrive(sb+W_BAR+144);
  }
  wg_wait<0>();
  if(CL){ if(lane<2) mbar_arrive_cl(eb+pst*8); } else if(lane==0) mbar_arrive(eb+pst*8);
}
__device__ __forceinline__ uint32_t act2(uint32_t u,uint32_t bb,float c1,float c3){
  uint32_t s; asm("add.rn.bf16x2 %0, %1, %2;":"=r"(s):"r"(u),"r"(bb));
  float r[2]={__uint_as_float(s<<16), __uint_as_float(s&0xffff0000u)};
  #pragma unroll
  for(int i=0;i<2;i++){
    const float z=r[i]*fmaf(r[i]*r[i],c3,c1);
    r[i]=r[i]*rcp(1.f+ex2(z));
  }
  return pack_bf16(r[0],r[1]);
}
__device__ __forceinline__ uint32_t fin1(uint32_t s,uint32_t x,uint32_t gq){
  const uint32_t p=pack_bf16(__uint_as_float(s<<16)*__uint_as_float(gq<<16),__uint_as_float(s&0xffff0000u)*__uint_as_float(gq&0xffff0000u));
  return pack_bf16(__uint_as_float(x<<16)+__uint_as_float(p<<16),__uint_as_float(x&0xffff0000u)+__uint_as_float(p&0xffff0000u));
}
template<int NT> __device__ __forceinline__ void stage_pk(const uint32_t* p,uint32_t ra,int lane){
  const int sw=lane&7, hi=lane>>4;
  #pragma unroll
  for(int T=0;T<NT;T++) stsm4n(ra+(T>>2)*BOXS+((((2*T+hi)&7)^sw)<<4),p[4*T],p[4*T+1],p[4*T+2],p[4*T+3]);
}
__device__ __noinline__ void post_pass(uint32_t sl,int nbox,int em,uint32_t ba,float c1,float c3,const bf16* x,bf16* out,uint32_t go){
  const int lane=threadIdx.x&31, r=lane>>3, c=lane&7;
  __syncwarp();
  #pragma unroll 1
  for(int j=0;j<nbox;j++){
    uint4 u[4]; uint32_t a[4];
    #pragma unroll
    for(int i=0;i<4;i++){ const int rr=4*i+r; a[i]=sl+j*BOXS+rr*128+((c^(rr&7))<<4); u[i]=lds4(a[i]); }
    if(em==1){
      const uint4 bb=lds4(ba+j*128+c*16);
      #pragma unroll
      for(int i=0;i<4;i++){
        uint4& v=u[i];
        v.x=act2(v.x,bb.x,c1,c3); v.y=act2(v.y,bb.y,c1,c3); v.z=act2(v.z,bb.z,c1,c3); v.w=act2(v.w,bb.w,c1,c3);
        sts4(a[i],v);
      }
    } else {
      uint4 xx[4],gg[4];
      #pragma unroll
      for(int i=0;i<4;i++){ const uint32_t o=go+(4*i+r)*D+j*64+c*8; xx[i]=__ldg((const uint4*)(x+o)); gg[i]=ldg_rlx4((const uint32_t*)(g_gate+o)); }
      #pragma unroll
      for(int i=0;i<4;i++){ const uint32_t o=go+(4*i+r)*D+j*64+c*8;
        *(uint4*)(out+o)=make_uint4(fin1(u[i].x,xx[i].x,gg[i].x),fin1(u[i].y,xx[i].y,gg[i].y),fin1(u[i].z,xx[i].z,gg[i].z),fin1(u[i].w,xx[i].w,gg[i].w)); }
    }
  }
}
template<int Q,int NS> __device__ __forceinline__ void red_item(const WParams& P,int rbk,int r,int tid){
  const int lane=tid&31, g=lane>>2, t=lane&3, wq=(tid>>5)&3;
  const float4* src=g_opp+opp_base(rbk)+(size_t)(r*Q)*128+(tid&127);
  float4 v[Q][NS];
  #pragma unroll
  for(int j=0;j<Q;j++)
    #pragma unroll
    for(int s=0;s<NS;s++) v[j][s]=ld_rlx4f(src+(size_t)s*20480+j*128);
  uint32_t gx[Q][2], xx[Q][2]; uint32_t off[Q];
  #pragma unroll
  for(int j=0;j<Q;j++){
    const int qi=r*Q+j, m=qi>=80, J=qi-80*m;
    off[j]=(uint32_t)((rbk*128+m*64+wq*16+g)*D+8*J+2*t);
    #pragma unroll
    for(int hh=0;hh<2;hh++){ gx[j][hh]=ld_rlx((const uint32_t*)(g_gate+off[j]+hh*8*D)); xx[j][hh]=__ldg((const uint32_t*)(P.x+off[j]+hh*8*D)); }
  }
  #pragma unroll
  for(int j=0;j<Q;j++){
    float4 a=v[j][0];
    #pragma unroll
    for(int s=1;s<NS;s++){ a.x+=v[j][s].x; a.y+=v[j][s].y; a.z+=v[j][s].z; a.w+=v[j][s].w; }
    *(uint32_t*)(P.out+off[j])=fin1(pack_bf16(a.x,a.y),xx[j][0],gx[j][0]);
    *(uint32_t*)(P.out+off[j]+8*D)=fin1(pack_bf16(a.z,a.w),xx[j][1],gx[j][1]);
  }
}
template<int N,int MODE> __device__ __forceinline__ void gemm_item(const WParams& P,int type,int rbk,int a,uint32_t pos,uint32_t sb,int tid,uint32_t ra,uint32_t& e0,uint32_t& eb,int& sq){
  const int lane=tid&31, wg=tid>>7;
  const uint32_t E0=sb+W_BAR+96+wg*16;
  float acc[192];
  const int ns=nsp(rbk), nt=a&3;
  const int nkb=(MODE&&type==T_M2)?24:((MODE&&type==T_OP)?96/ns:10);
  mainloop<N,MODE==0,0>(acc,nkb,sb,lane,pos);
  if(MODE==0||type>=T_M2||ns==1){
    uint32_t p[2][N/4];
    #pragma unroll
    for(int m=0;m<2;m++)
      #pragma unroll
      for(int i=0;i<N/4;i++) p[m][i]=pack_bf16(acc[96*m+2*i],acc[96*m+2*i+1]);
    const float c1=type==T_M1?-2.302208198144325f:-1.4426950408889634f, c3=type==T_M1?-0.10294323958f:0.f;
    const int wq=(tid>>5)&3;
    if(MODE&&(type==T_M1||type==T_M2)){ mbar_wait(sb+W_BAR+224+wg*8,eb); eb^=1; }
    #pragma unroll
    for(int m=0;m<2;m++){
      mbar_wait(E0+m*8,e0);
      stage_pk<N/16>(p[m],ra+m*SLOT,lane);
      if(MODE&&type!=T_KV) post_pass(sb+W_SLOT+m*SLOT+wq*2048,N/64,type==T_OP?2:1,sb+W_BAR+256+wg*384,c1,c3,P.x,P.out,(uint32_t)((rbk*128+m*64+wq*16)*D+(nt<2?nt*192:128+nt*128)));
      fence_async();
      bar_arrive(sq,160); sq^=1;
    }
    e0^=1;
  } else {
    float4* dst=g_opp+opp_base(rbk)+(size_t)(a>>2)*20480+(nt<2?nt*24:16+nt*16)*128+(tid&127);
    #pragma unroll
    for(int m=0;m<2;m++)
      #pragma unroll
      for(int n=0;n<N/8;n++) __stcg(dst+(m*80+n)*128,make_float4(acc[96*m+4*n],acc[96*m+4*n+1],acc[96*m+4*n+2],acc[96*m+4*n+3]));
    mbar_wait(E0,e0); mbar_wait(E0+8,e0); e0^=1;
    bar_arrive(sq,160); sq^=1;
  }
}
__device__ __forceinline__ void decode(int c,int idx,int& rbk,int& a){
  if(c==T_KV){ rbk=2*(idx>>7)+(idx&1); a=(idx>>1)&63; }
  else if(c==T_M1){ rbk=idx>>3; a=idx&7; }
  else if(c==T_M2){ rbk=idx>>2; a=idx&3; }
  else if(c==T_QA){ rbk=idx>>5; a=idx&31; }
  else {
    rbk=0;
    #pragma unroll 1
    while(true){ const int ns=nsp(rbk), n=c==T_OP?4*ns:(ns>1?5*ns:0); if(idx<n) break; idx-=n; rbk++; }
    a=idx;
  }
}
__device__ __forceinline__ void flag_wait(int rbk,int a){
  const uint32_t need=4*rbk+4; const uint32_t* f=g_flag+a*96; int gd=0;
  while(ld_acq(f)<need||ld_acq(f+32)<need||ld_acq(f+64)<need){ __nanosleep(40); if(++gd>WGUARD){ g_err=22; break; } }
  FAG();
}
__device__ __forceinline__ void cnt_wait(int c,uint32_t thr){
  int gd=0;
  while(ld_acq(g_cnt+c)<thr){ __nanosleep(40); if(++gd>WGUARD){ g_err=23; break; } }
}
template<int MODE>
__global__ void __launch_bounds__(384,1) k_work(const __grid_constant__ WParams P){
  extern __shared__ __align__(1024) uint8_t sm[];
  const uint32_t sb=(uint32_t)__cvta_generic_to_shared(sm);
  const int tid=threadIdx.x, warp=__shfl_sync(~0u,tid>>5,0), lane=tid&31;
  const uint32_t FULL=sb+W_BAR, EMPTY=sb+W_BAR+32, IFULL=sb+W_BAR+64, IEMPTY=sb+W_BAR+80, EF=sb+W_BAR+96, REQ=sb+W_BAR+128, TOK=sb+W_BAR+136;
  volatile int* idesc=(volatile int*)(sm+W_BAR+160);
  if(tid==352) ST(0);
  if(tid==0){
    for(int i=0;i<NST;i++){ mbar_init(FULL+i*8,1); mbar_init(EMPTY+i*8,MODE?4:8); mbar_init(EF+i*8,1); }
    for(int i=0;i<2;i++){ mbar_init(IFULL+i*8,1); mbar_init(IEMPTY+i*8,6); mbar_init(sb+W_BAR+224+i*8,1); }
    mbar_init(REQ,1); mbar_init(TOK,1); mbar_init(sb+W_BAR+144,1);
    asm volatile("fence.mbarrier_init.release.cluster;":::"memory");
  }
  __syncthreads();
  if(MODE==0){ cluster_sync(); asm volatile("griddepcontrol.wait;":::"memory"); asm volatile("griddepcontrol.launch_dependents;"); }
  if(warp>=8){
    asm volatile("setmaxnreg.dec.sync.aligned.u32 40;");
    if(warp==11){
      uint32_t it=0, pos=0;
      int held=-1; int guard=0; bool fin=false;
      const int cl=lane>>2, cj=lane&3;
      const int ncls=cl==T_RED?n_red():(cl==T_OP?n_op():(cl==T_QA?NRB*32:(cl==T_M2?NRB*4:(cl==T_M1?NRB*8:(cl==T_KV?NRB*64-KVUP:0)))));
      const int cofs=cl==T_KV?KVUP:0;
      int sidx=blockIdx.x; int nit=0;
      if(lane==0) ST(1);
      while(true){
        int type=T_END, idx=0, erl=0;
        if(!fin){
          if(it) mbar_wait(REQ,(it&1)^1);
          if(MODE==0){
            if(sidx<KVUP){ type=T_KV; idx=sidx; sidx+=gridDim.x; }
            if(it==WPF){
              const int ci=blockIdx.x*32+lane;
              if(ci<3840) asm volatile("cp.async.bulk.prefetch.L2.global [%0], 4096;"::"l"((const char*)(ci<1920?P.wq:P.wo)+(size_t)(ci<1920?ci:ci-1920)*4096):"memory");
            }
          }
          else {
            while(true){
              int cand=held;
              if(cand<0&&ncls){ cand=(int)ld_rlx(g_cnt+C_NEXT+cl*32); if(cand>=ncls) cand=-1; }
              if(lane==0&&nit==0) ST(5+(cand&0));
              const uint32_t* fp=nullptr; uint32_t thr=0, sl1=0; bool only1=false, no1=cl>=T_M2;
              if(cand>=0&&cl<=T_M2){
                int rbk,a; decode(cl,cand,rbk,a); const int ns=nsp(rbk);
                if(cl==T_QA){ if(cj<3){ fp=g_flag+a*96+cj*32; thr=4*rbk+4; sl1=rbk==NRB-1?E15:EARLY; } else { fp=g_cnt+C_KV+min(rbk+1,NRB-1); thr=64; only1=true; } }
                else if(cj==0){ fp=g_cnt+(cl==T_RED?C_OP+rbk:(cl==T_OP?C_QA+qab(rbk)+(a>>2):C_M1+rbk)); thr=cl==T_RED?4*ns:(cl==T_OP?32/ns:8); sl1=thr; }
                else if(cj==1){ if(cl==T_RED||(cl==T_OP&&ns==1)){ fp=g_cnt+C_M2+rbk; thr=4; } if(rbk<OPE) no1=true; }
                else if(cj==2&&cl<T_QA&&ns>1){ fp=g_cnt+C_NEXT+(cl+1)*32; thr=cl==T_OP?(rbk+1)*32:4*qab(rbk+1); only1=true; }
              }
              __syncwarp();
              if(lane==0&&nit==0) ST(2);
              uint32_t v=0; if(fp) v=ld_acq(fp);
              __syncwarp();
              if(lane==0&&nit==0) ST(3+(v&0));
              nit++;
              uint32_t b2=__ballot_sync(~0u,cand>=0&&(v>=thr||only1)), b1=__ballot_sync(~0u,cand>=0&&!no1&&v+sl1>=thr);
              const uint32_t ba=__ballot_sync(~0u,cand>=0), bh=__ballot_sync(~0u,held>=0);
              b2&=b2>>1; b2&=b2>>2; b1&=b1>>1; b1&=b1>>2;
              const bool opf=__ballot_sync(~0u,cl==T_OP&&cand<4*n_uns())!=0;
              if(opf&&(bh&~(15u<<(4*T_OP)))) b2&=~(1u<<(4*T_OP));
              b2&=0x111111u; b1&=0x111u; if(bh) b1&=(__popc(bh)==4)?bh:0u;
              if(!EARLY) b1=0;
              if(!ba) break;
              if(b2|b1){
                uint32_t bb=b2?b2:b1;
                if(HB&&(b2&bh)) bb=b2&bh;
                if(Q15&&(((b1|b2)>>(4*T_QA))&1)&&__ballot_sync(~0u,cl==T_QA&&cand>=(NRB-Q15)*32)) bb=1u<<(4*T_QA);
                #define RD(c) ((bb>>(4*(c)))&1)
                const int w=RD(T_KV)?T_KV:(RD(T_M2)?T_M2:(RD(T_M1)?T_M1:((opf&&RD(T_OP))?T_OP:(RD(T_QA)?T_QA:(RD(T_OP)?T_OP:T_RED)))));
                int got=-1;
                if(cl==w){
                  if(held>=0){ got=held; held=-1; }
                  else {
                    int tk=0; if(cj==0) tk=(int)atomicAdd(g_cnt+C_NEXT+cl*32,1u);
                    tk=__shfl_sync(15u<<(4*cl),tk,4*cl);
                    if(tk<ncls){ if(tk==cand||cl>T_M2) got=tk; else held=tk; }
                  }
                  if(got>=0) got+=cofs;
                }
                got=__shfl_sync(~0u,got,4*w);
                if(got>=0){ type=w; idx=got; erl=!((b2>>(4*w))&1); break; }
              } else {
                __nanosleep(100);
                if(++guard>WGUARD){ g_err=21; break; }
              }
            }
          }
        }
        __syncwarp();
        if(lane==0){
          const uint32_t sl=it&1;
          int rbk=0,a=0; if(type!=T_END) decode(type,idx,rbk,a);
          mbar_wait(IEMPTY+sl*8,((it>>1)&1)^1);
          idesc[sl*8]=type; idesc[sl*8+1]=rbk; idesc[sl*8+2]=a; idesc[sl*8+3]=pos; idesc[sl*8+4]=idx; idesc[sl*8+5]=erl;
          mbar_arrive(IFULL+sl*8);
          pos+=type==T_RED?0:(type==T_M2?24:(type==T_OP?96/nsp(rbk):(type==T_QA?12:10)));
        }
        __syncwarp();
        it++;
        if(type==T_END){ if(fin) break; fin=true; }
      }
    } else if(warp==8){
      if(lane==0){
        uint32_t st=0, ph=1;
        for(uint32_t it=0;;it++){
          const uint32_t sl=it&1;
          mbar_wait(IFULL+sl*8,(it>>1)&1);
          const int type=idesc[sl*8], rbk=idesc[sl*8+1], a=idesc[sl*8+2], erl=idesc[sl*8+5];
          mbar_arrive(IEMPTY+sl*8);
          if(type==T_END) break;
          if(type==T_RED){ mbar_arrive(REQ); continue; }
          int ma=M_XN,mb,col0=a*192,k0=0,nkb=10,nbox=3; const int row0=rbk*128;
          if(MODE==0||type==T_KV){ mb=a<32?M_WK:M_WV; col0=(a&31)*192; }
          else if(type==T_M1){ ma=M_Y; mb=M_W1; }
          else if(type==T_QA){ mb=M_WQ; }
          else {
            const int nt=a&3; col0=nt<2?nt*192:128+nt*128; nbox=nt<2?3:2;
            if(type==T_M2){ ma=M_H; mb=M_W2; nkb=24; } else { ma=M_OX; mb=M_WO; nkb=96/nsp(rbk); k0=(a>>2)*nkb*64; }
          }
          if(MODE&&erl&&type==T_OP) cnt_wait(C_QA+qab(rbk)+(a>>2),32/nsp(rbk));
          if(MODE) FAG();
          const CUtensorMap* A=&P.m[ma]; const CUtensorMap* B=&P.m[mb];
          const int trig=(MODE&&type<=T_QA&&rbk>=LATE)?nkb-1:max(nkb-(type==T_QA?TRIG-2:TRIG),0);
          for(int kb=0;kb<nkb;kb++){
            mbar_wait(EMPTY+st*8,ph);
            const uint32_t d=sb+st*STG, fb=FULL+st*8;
            mbar_expect(fb,16384+nbox*8192);
            const int kk=k0+kb*64;
            tma2d(d,A,kk,row0,fb); tma2d(d+8192,A,kk,row0+64,fb);
            if(MODE==0){
              const int r=rbk&1, j=2*r;
              tma2dm(d+16384+j*8192,B,col0+j*64,kk,fb);
              if((kb&1)==r) tma2dm(d+24576,B,col0+64,kk,fb);
            }
            else for(int j=0;j<nbox;j++) tma2d(d+16384+j*8192,B,col0+j*64,kk,fb);
            if(kb==trig) mbar_arrive(REQ);
            if(++st==NST){ st=0; ph^=1; }
          }
          if(MODE&&type==T_QA){
            for(int m=0;m<2;m++){
              mbar_wait(EMPTY+st*8,ph);
              const uint32_t d=sb+st*STG, fb=FULL+st*8;
              mbar_expect(fb,SLOT);
              for(int j=0;j<3;j++) tma2d(d+j*BOXS,&P.m[M_K],col0+j*64,row0+m*64,fb);
              if(erl&&!m) flag_wait(rbk,a);
              for(int j=0;j<3;j++) tma2d(d+j*BOXS+8192,&P.m[M_KM],col0+j*64,rbk*32+m*16,fb);
              if(++st==NST){ st=0; ph^=1; }
            }
          }
        }
      }
      __syncwarp();
    } else if(warp<11){
      const int wg=warp-9;
      const uint32_t S0=sb+W_SLOT, E0=EF+wg*16; int sq=4+2*wg;
      for(uint32_t it=wg;;it+=2){
        mbar_wait(IFULL+wg*8,(it>>1)&1);
        const int type=idesc[wg*8], rbk=idesc[wg*8+1], a=idesc[wg*8+2], erl=idesc[wg*8+5];
        __syncwarp();
        if(lane==0) mbar_arrive(IEMPTY+wg*8);
        if(type==T_END) break;
        if(MODE&&type==T_OP&&nsp(rbk)>1&&lane==0){ mbar_arrive(E0); mbar_arrive(E0+8); }
        const int row0=rbk*128;
        int map=-1,col0=a*192,nbox=3,cnt=-1;
        if(MODE==0||type==T_KV){ map=a<32?M_K:M_V; col0=(a&31)*192; cnt=C_KV+rbk; }
        else if(type==T_M1){ map=M_H; cnt=C_M1+rbk; }
        else if(type==T_QA){ map=M_OX; cnt=C_QA+qab(rbk)+((a*nsp(rbk))>>5); }
        else if(type!=T_RED){
          const int nt=a&3; col0=nt<2?nt*192:128+nt*128; nbox=nt<2?3:2;
          if(type==T_M2){ map=M_GATE; cnt=C_M2+rbk; } else if(nsp(rbk)==1) map=M_OUT;
        }
        if(MODE&&(type==T_M1||type==T_M2)&&lane==0){ const uint32_t bb=sb+W_BAR+224+wg*8; mbar_expect(bb,nbox*128); bulk_g2s(sb+W_BAR+256+wg*384,(type==T_M1?P.b1:P.b2)+col0,nbox*128,bb); }
        if(it&&lane==0) mbar_wait(TOK,(it&1)^1);
        if(MODE&&map<0){
          if(lane==0) mbar_arrive(TOK);
          if(type==T_RED&&lane==0){ if(erl) cnt_wait(C_OP+rbk,4*nsp(rbk)); mbar_arrive(E0); mbar_arrive(E0+8); }
          if(type==T_OP){ { __syncwarp(); bar_sync(sq,160); sq^=1; } if(lane==0) red_rel(g_cnt+C_OP+rbk); }
        } else if(MODE&&map==M_OUT){
          if(lane==0){ mbar_arrive(E0); mbar_arrive(E0+8); }
          { __syncwarp(); bar_sync(sq,160); sq^=1; }
          { __syncwarp(); bar_sync(sq,160); sq^=1; }
          if(lane==0) mbar_arrive(TOK);
        } else {
          if(MODE&&type==T_QA){
            if(lane==0){
              FAG();
              for(int m=0;m<2;m++){
                mbar_expect(E0+m*8,SLOT);
                for(int j=0;j<3;j++) tma2d(S0+m*SLOT+j*BOXS,&P.m[M_V],col0+j*64,row0+m*64,E0+m*8);
              }
              if(erl) flag_wait(rbk,a);
              for(int m=0;m<2;m++)
                for(int j=0;j<3;j++) tma2d(S0+m*SLOT+j*BOXS+8192,&P.m[M_VM],col0+j*64,rbk*32+m*16,E0+m*8);
            }
          } else if(lane==0){ mbar_arrive(E0); mbar_arrive(E0+8); }
          for(int m=0;m<2;m++){
            { __syncwarp(); bar_sync(sq,160); sq^=1; }
            if(lane==0){
              for(int j=0;j<nbox;j++) tma_st(&P.m[map],S0+m*SLOT+j*BOXS,col0+j*64,row0+m*64);
              bulk_commit();
            }
          }
          if(lane==0){
            bulk_wait_rd(); mbar_arrive(TOK);
            bulk_wait(); FAG(); red_rel(g_cnt+cnt);
          }
        }
        __syncwarp();
      }
      if(lane==0) bulk_wait();
    }
  } else {
    asm volatile("setmaxnreg.inc.sync.aligned.u32 232;");
    const int wg=warp>>2, wq=warp&3, g=lane>>2, t=lane&3;
    const uint32_t E0=EF+wg*16;
    const uint32_t ra=sb+W_SLOT+(16*wq+(lane&7)+((lane>>3)&1)*8)*128;
    uint32_t e0=0, eb=0; int sq=4+2*wg;
    #pragma unroll 1
    for(uint32_t it=0;;it++){
      mbar_wait(IFULL+wg*8,it&1);
      const int type=idesc[wg*8], rbk=idesc[wg*8+1], a=idesc[wg*8+2]; const uint32_t pos=idesc[wg*8+3];
      __syncwarp();
      if(lane==0) mbar_arrive(IEMPTY+wg*8);
      if(type==T_END) break;
      mbar_wait(sb+W_BAR+144,wg^1);
      if(MODE&&type==T_RED){
        bar_sync(8+wg,128);
        if((tid&127)==0) mbar_arrive(sb+W_BAR+144);
        mbar_wait(E0,e0); mbar_wait(E0+8,e0); e0^=1;
        { const int ns=nsp(rbk);
          if(ns_used(4)&&ns==4) red_item<8,4>(P,rbk,a,tid);
          if(ns_used(8)&&ns==8) red_item<4,8>(P,rbk,a,tid);
          if(ns_used(16)&&ns==16) red_item<2,16>(P,rbk,a,tid); }
      } else {
        if(MODE==0||type!=T_QA){
          if(MODE==0||type>=T_M1||(a&3)<2) gemm_item<192,MODE>(P,type,rbk,a,pos,sb,tid,ra,e0,eb,sq); else gemm_item<128,MODE>(P,type,rbk,a,pos,sb,tid,ra,e0,eb,sq);
        } else {
          float acc[192];
          QT(0);
          mainloop<192,0,2>(acc,10,sb,lane,pos);
          QT(1);
          const int sgl=wq>>1, rh=wq&1;
          uint32_t pa[2][20];
          {
            uint32_t q[96];
            float s[2][40];
            QT(2);
            #pragma unroll
            for(int m=0;m<2;m++){
              const uint32_t ks=(pos+10+m)&3;
              const uint32_t dk=((sb+ks*STG)>>4)|(1u<<16);
              #pragma unroll
              for(int i=48*m;i<48*m+48;i++) q[i]=pack_bf16(acc[2*i],acc[2*i+1]);
              mbar_wait(FULL+ks*8,((pos+10+m)>>2)&1);
              #pragma unroll
              for(int i=0;i<40;i++) s[m][i]=0.f;
              wg_arrive();
              #pragma unroll
              for(int T=0;T<12;T++) wgmma_rs<80>(s[m],q+48*m+4*T,dk+(T>>2)*(BOXS/16)+(T&3)*2,T);
              wg_commit();
              wg_wait<0>();
              if(lane==0) mbar_arrive(EMPTY+ks*8);
              QT(3+m);
            }
            const float NEG=rb(-1e9f);
            #pragma unroll
            for(int m=0;m<2;m++){
              float sc[5][4];
              float mx[2]={-3.4e38f,-3.4e38f};
              #pragma unroll
              for(int n=0;n<5;n++)
                #pragma unroll
                for(int i=0;i<4;i+=2){
                  const float u0=n?(sgl?s[m][12+4*n+i]:s[m][4*n-4+i]):(sgl?s[m][36+i]:s[m][32+i]);
                  const float u1=n?(sgl?s[m][13+4*n+i]:s[m][4*n-3+i]):(sgl?s[m][37+i]:s[m][33+i]);
                  const uint32_t r=pack_bf16(u0,u1);
                  const uint32_t w=pack_bf16(__uint_as_float(r<<16)*0.07216878364870322f,__uint_as_float(r&0xffff0000u)*0.07216878364870322f);
                  float v0=__uint_as_float(w<<16), v1=__uint_as_float(w&0xffff0000u);
                  if(n>0){ const int key=8*(n-1)+2*t, row=16*rh+g+4*i; if(key>row) v0=NEG; if(key+1>row) v1=NEG; }
                  sc[n][i]=v0; sc[n][i+1]=v1; mx[i>>1]=fmaxf(mx[i>>1],fmaxf(v0,v1));
                }
              float sum[2]={0.f,0.f};
              #pragma unroll
              for(int r=0;r<2;r++){ mx[r]=fmaxf(mx[r],__shfl_xor_sync(~0u,mx[r],1)); mx[r]=fmaxf(mx[r],__shfl_xor_sync(~0u,mx[r],2)); }
              #pragma unroll
              for(int n=0;n<5;n++)
                #pragma unroll
                for(int i=0;i<4;i++){ const float e=ex2((sc[n][i]-mx[i>>1])*1.4426950408889634f); sc[n][i]=e; sum[i>>1]+=e; }
              #pragma unroll
              for(int r=0;r<2;r++){ sum[r]+=__shfl_xor_sync(~0u,sum[r],1); sum[r]+=__shfl_xor_sync(~0u,sum[r],2); sum[r]=rcp(sum[r]); }
              #pragma unroll
              for(int n=0;n<5;n++){
                const uint32_t p0=pack_bf16(sc[n][0]*sum[0],sc[n][1]*sum[0]), p1=pack_bf16(sc[n][2]*sum[1],sc[n][3]*sum[1]);
                const int o=n?2*(n-1):16, d=n?8:2;
                pa[m][o]=sgl?0u:p0; pa[m][o+1]=sgl?0u:p1; pa[m][o+d]=sgl?p0:0u; pa[m][o+d+1]=sgl?p1:0u;
              }
            }
          }
          QT(5); QT(6);
          const uint32_t dv=((sb+W_SLOT)>>4)|((uint32_t)(BOXS/16)<<16);
          #pragma unroll
          for(int m=0;m<2;m++){
            float o[96];
            #pragma unroll
            for(int i=0;i<96;i++) o[i]=0.f;
            mbar_wait(E0+m*8,e0);
            QT(7+3*m);
            wg_arrive();
            #pragma unroll
            for(int k=0;k<5;k++) wgmma_rs<192>(o,pa[m]+4*k,dv+m*(SLOT/16)+128*k,k);
            wg_commit();
            wg_wait<0>();
            QT(8+3*m);
            bar_sync(8+wg,128);
            { uint32_t p[48];
              #pragma unroll
              for(int i=0;i<48;i++) p[i]=pack_bf16(o[2*i],o[2*i+1]);
              stage_pk<12>(p,ra+m*SLOT,lane); }
            fence_async();
            bar_arrive(sq,160); sq^=1;
            QT(9+3*m);
          }
          e0^=1;
        }
      }
    }
  }
  if(MODE==0) cluster_sync();
}
typedef CUresult (*EncFn)(CUtensorMap*,CUtensorMapDataType,cuuint32_t,void*,const cuuint64_t*,const cuuint64_t*,const cuuint32_t*,const cuuint32_t*,CUtensorMapInterleave,CUtensorMapSwizzle,CUtensorMapL2promotion,CUtensorMapFloatOOBfill);
static CUtensorMap mk2d(const void* base,uint64_t cols,uint64_t rows,uint32_t bc,uint32_t br){
  static EncFn fn=nullptr;
  if(!fn){ void* p=nullptr; cudaDriverEntryPointQueryResult qr; cudaGetDriverEntryPoint("cuTensorMapEncodeTiled",&p,cudaEnableDefault,&qr); fn=(EncFn)p; }
  CUtensorMap m; cuuint64_t gd[2]={cols,rows}; cuuint64_t gs[1]={cols*2}; cuuint32_t bd[2]={bc,br}; cuuint32_t es[2]={1,1};
  fn(&m,CU_TENSOR_MAP_DATA_TYPE_BFLOAT16,2,(void*)base,gd,gs,bd,es,CU_TENSOR_MAP_INTERLEAVE_NONE,CU_TENSOR_MAP_SWIZZLE_128B,CU_TENSOR_MAP_L2_PROMOTION_L2_128B,CU_TENSOR_MAP_FLOAT_OOB_FILL_NONE);
  return m;
}
template<class T> static T* sym(T& s){ void* p; cudaGetSymbolAddress(&p,s); return (T*)p; }
}

int g_reconly=0; int g_kvgrid=132;
extern "C" void kernel_launch(void* const* d_in, const int* in_sizes, int n_in, void* d_out, int out_size) {
  using namespace rk;
  const bf16* x=(const bf16*)d_in[0]; const bf16* mem0=(const bf16*)d_in[1];
  const bf16* Wq=(const bf16*)d_in[2]; const bf16* Wk=(const bf16*)d_in[3]; const bf16* Wv=(const bf16*)d_in[4]; const bf16* Wo=(const bf16*)d_in[5];
  const bf16* w1=(const bf16*)d_in[8]; const bf16* b1=(const bf16*)d_in[9]; const bf16* w2=(const bf16*)d_in[10]; const bf16* b2=(const bf16*)d_in[11];
  cudaStream_t st=cudaStreamPerThread;
  cudaFuncSetAttribute(k_rec,cudaFuncAttributeMaxDynamicSharedMemorySize,SM_TOTAL);
  cudaFuncSetAttribute(k_work<0>,cudaFuncAttributeMaxDynamicSharedMemorySize,W_TOTAL);
  cudaFuncSetAttribute(k_work<1>,cudaFuncAttributeMaxDynamicSharedMemorySize,W_TOTAL);
  bf16* k=(bf16*)sym(g_k); bf16* v=(bf16*)sym(g_v);
  WParams P;
  P.m[M_XN]=mk2d(sym(g_xn),D,S,64,64); P.m[M_Y]=mk2d(sym(g_y),D,S,64,64); P.m[M_H]=mk2d(sym(g_h),F,S,64,64); P.m[M_OX]=mk2d(sym(g_ox),HD,S,64,64);
  P.m[M_K]=mk2d(k,HD,S,64,64); P.m[M_V]=mk2d(v,HD,S,64,64); P.m[M_GATE]=mk2d(sym(g_gate),D,S,64,64);
  P.m[M_WQ]=mk2d(Wq,HD,D,64,64); P.m[M_WK]=mk2d(Wk,HD,D,64,64); P.m[M_WV]=mk2d(Wv,HD,D,64,64);
  P.m[M_W1]=mk2d(w1,F,D,64,64); P.m[M_W2]=mk2d(w2,D,F,64,64); P.m[M_WO]=mk2d(Wo,D,HD,64,64);
  P.m[M_KM]=mk2d(sym(g_km),HD,NSEG*8,64,16); P.m[M_VM]=mk2d(sym(g_vm),HD,NSEG*8,64,16);
  P.x=x; P.b1=b1; P.b2=b2; P.out=(bf16*)d_out; P.wq=Wq; P.wo=Wo;
  k_pre<<<S/8+1,256,0,st>>>(x,mem0);
  if(!(g_reconly&1)){
    cudaLaunchConfig_t cfg={}; cfg.gridDim=dim3(g_kvgrid); cfg.blockDim=dim3(384); cfg.dynamicSmemBytes=W_TOTAL; cfg.stream=st;
    cudaLaunchAttribute at[2]; at[0].id=cudaLaunchAttributeClusterDimension; at[0].val.clusterDim.x=2; at[0].val.clusterDim.y=1; at[0].val.clusterDim.z=1;
    at[1].id=cudaLaunchAttributeProgrammaticStreamSerialization; at[1].val.programmaticStreamSerializationAllowed=1; cfg.attrs=at; cfg.numAttrs=2;
    cudaLaunchKernelEx(&cfg,k_work<0>,P);
  }
  if(!(g_reconly&4)){
    cudaLaunchConfig_t cfg={}; cfg.gridDim=dim3(NCTA); cfg.blockDim=dim3(256); cfg.dynamicSmemBytes=SM_TOTAL; cfg.stream=st;
    cudaLaunchAttribute at[2]; at[0].id=cudaLaunchAttributeClusterDimension; at[0].val.clusterDim.x=3; at[0].val.clusterDim.y=1; at[0].val.clusterDim.z=1;
    at[1].id=cudaLaunchAttributeProgrammaticStreamSerialization; at[1].val.programmaticStreamSerializationAllowed=1; cfg.attrs=at; cfg.numAttrs=2;
    CUtensorMap tk=mk2d(k,HD,S,64,32), tv=mk2d(v,HD,S,64,32);
    cudaLaunchKernelEx(&cfg,k_rec,tk,tv,Wq,Wk,Wv,Wo,0u);
  }
  if(!(g_reconly&2)){
    cudaLaunchConfig_t cfg={}; cfg.gridDim=dim3(132); cfg.blockDim=dim3(384); cfg.dynamicSmemBytes=W_TOTAL; cfg.stream=st;
    cudaLaunchAttribute at[1]; at[0].id=cudaLaunchAttributeProgrammaticStreamSerialization; at[0].val.programmaticStreamSerializationAllowed=1; cfg.attrs=at; cfg.numAttrs=PDL;
    cudaLaunchKernelEx(&cfg,k_work<1>,P);
  }
}
```

```cpp
#include <cuda_runtime.h>
#include <cuda_bf16.h>
#include <stdint.h>
#include <cuda.h>

namespace rk {
typedef __nv_bfloat16 bf16;
constexpr int S=2048, D=640, H=32, DH=192, HD=6144, NSEG=64, F=1536;
constexpr uint32_t SENT=0xFFFFFFFFu;
#define GUARDN 400000
constexpr int GUARD=GUARDN;
constexpr int NCTA=96;

__device__ __align__(128) bf16 g_xn[S*D];
__device__ __align__(128) bf16 g_y[S*D];
__device__ __align__(128) bf16 g_h[S*F];
__device__ __align__(128) bf16 g_gate[S*D];
__device__ __align__(128) bf16 g_k[(size_t)S*HD];
__device__ __align__(128) bf16 g_v[(size_t)S*HD];
__device__ __align__(128) bf16 g_km[NSEG*8*HD];
__device__ __align__(128) uint32_t g_flag[NCTA*32];
__device__ __align__(1024) uint8_t g_u[(size_t)NSEG*40*40960];
__device__ __align__(1024) uint8_t g_p[(size_t)NSEG*40*2048];
#define NSTAB 0xA555522222222222ull
__host__ __device__ constexpr int nsp(int rb){ return (int)((NSTAB>>(4*rb))&15); }
__host__ __device__ constexpr bool ns_used(int n){ for(int r=0;r<16;r++) if(nsp(r)==n) return true; return false; }
constexpr int C_NEXT=0, C_KV=256, C_M1=272, C_M2=288, C_OP=304, C_QA=320, C_NUM=384;
__device__ __align__(128) uint32_t g_cnt[C_NUM];
#define PDL 1
__device__ __align__(1024) unsigned long long g_acc[NSEG*2560];
constexpr unsigned long long ACC_INIT=0ull-32ull*((0x5A000000ull<<32)+0xD0000000ull+1ull);
__device__ __align__(128) uint32_t g_nrm[NCTA*2+32];
__device__ int g_err;
__device__ unsigned long long g_gt[128*4];
#define GT(i) do{ if(threadIdx.x==0){ unsigned long long g0; asm volatile("mov.u64 %0, %%globaltimer;":"=l"(g0)); g_gt[blockIdx.x*4+(i)]=g0; } }while(0)

__device__ __forceinline__ float rb(float x){ return __bfloat162float(__float2bfloat16(x)); }
__device__ __forceinline__ uint32_t pack_bf16(float lo,float hi){ uint32_t r; asm("cvt.rn.bf16x2.f32 %0, %1, %2;":"=r"(r):"f"(hi),"f"(lo)); return r; }
__device__ __forceinline__ uint32_t movm(uint32_t a){ uint32_t d; asm volatile("movmatrix.sync.aligned.m8n8.trans.b16 %0, %1;":"=r"(d):"r"(a)); return d; }
__device__ __forceinline__ uint4 ldg_rlx4(const uint32_t* p){ uint4 v; asm volatile("ld.relaxed.gpu.global.v4.u32 {%0,%1,%2,%3}, [%4];":"=r"(v.x),"=r"(v.y),"=r"(v.z),"=r"(v.w):"l"(p):"memory"); return v; }
__device__ __forceinline__ void stg_rlx1(uint32_t* p,uint32_t a){ asm volatile("st.relaxed.gpu.global.u32 [%0], %1;"::"l"(p),"r"(a):"memory"); }
__device__ __forceinline__ void stg_rlx2(uint32_t* p,uint32_t a,uint32_t b){ asm volatile("st.relaxed.gpu.global.v2.u32 [%0], {%1,%2};"::"l"(p),"r"(a),"r"(b):"memory"); }
__device__ __forceinline__ void stg1(void* p,uint32_t a){ asm volatile("st.global.u32 [%0], %1;"::"l"(p),"r"(a):"memory"); }
__device__ __forceinline__ void stg4(void* p,uint32_t a,uint32_t b,uint32_t c,uint32_t d){ asm volatile("st.global.v4.u32 [%0], {%1,%2,%3,%4};"::"l"(p),"r"(a),"r"(b),"r"(c),"r"(d):"memory"); }
__device__ __forceinline__ void bar_sync(int id,int n){ asm volatile("bar.sync %0, %1;"::"r"(id),"r"(n):"memory"); }
__device__ __forceinline__ void bar_arrive(int id,int n){ asm volatile("bar.arrive %0, %1;"::"r"(id),"r"(n):"memory"); }
__device__ __forceinline__ void mma16816(float* d,const uint32_t* a,uint32_t b0,uint32_t b1){
  asm volatile("mma.sync.aligned.m16n8k16.row.col.f32.bf16.bf16.f32 {%0,%1,%2,%3},{%4,%5,%6,%7},{%8,%9},{%0,%1,%2,%3};"
   :"+f"(d[0]),"+f"(d[1]),"+f"(d[2]),"+f"(d[3]):"r"(a[0]),"r"(a[1]),"r"(a[2]),"r"(a[3]),"r"(b0),"r"(b1));
}
__device__ __forceinline__ void mma1688(float* d,uint32_t a0,uint32_t a1,uint32_t b0){
  asm volatile("mma.sync.aligned.m16n8k8.row.col.f32.bf16.bf16.f32 {%0,%1,%2,%3},{%4,%5},{%6},{%0,%1,%2,%3};"
   :"+f"(d[0]),"+f"(d[1]),"+f"(d[2]),"+f"(d[3]):"r"(a0),"r"(a1),"r"(b0));
}
__device__ __forceinline__ void ldsm4t(uint32_t* r,uint32_t addr){ asm volatile("ldmatrix.sync.aligned.m8n8.x4.trans.shared.b16 {%0,%1,%2,%3}, [%4];":"=r"(r[0]),"=r"(r[1]),"=r"(r[2]),"=r"(r[3]):"r"(addr):"memory"); }
__device__ __forceinline__ void ldsm4(uint32_t* r,uint32_t addr){ asm volatile("ldmatrix.sync.aligned.m8n8.x4.shared.b16 {%0,%1,%2,%3}, [%4];":"=r"(r[0]),"=r"(r[1]),"=r"(r[2]),"=r"(r[3]):"r"(addr):"memory"); }
__device__ __forceinline__ void stsm4(uint32_t a,uint32_t r0,uint32_t r1,uint32_t r2,uint32_t r3){ asm volatile("stmatrix.sync.aligned.m8n8.x4.shared.b16 [%0], {%1,%2,%3,%4};"::"r"(a),"r"(r0),"r"(r1),"r"(r2),"r"(r3):"memory"); }
__device__ __forceinline__ void stsm2(uint32_t a,uint32_t r0,uint32_t r1){ asm volatile("stmatrix.sync.aligned.m8n8.x2.shared.b16 [%0], {%1,%2};"::"r"(a),"r"(r0),"r"(r1):"memory"); }
__device__ __forceinline__ void cp16(uint32_t dst,const void* src){ asm volatile("cp.async.cg.shared.global [%0], [%1], 16;"::"r"(dst),"l"(src):"memory"); }
__device__ __forceinline__ void cp_wait_all(){ asm volatile("cp.async.wait_all;":::"memory"); }
__device__ __forceinline__ void fence_async(){ asm volatile("fence.proxy.async.shared::cta;":::"memory"); }
__device__ __forceinline__ void sts4f(uint32_t a,const float* v){ asm volatile("st.shared.v4.f32 [%0], {%1,%2,%3,%4};"::"r"(a),"f"(v[0]),"f"(v[1]),"f"(v[2]),"f"(v[3]):"memory"); }
__device__ __forceinline__ void sts4(uint32_t a,uint4 v){ asm volatile("st.shared.v4.u32 [%0], {%1,%2,%3,%4};"::"r"(a),"r"(v.x),"r"(v.y),"r"(v.z),"r"(v.w):"memory"); }
__device__ __forceinline__ void sts4r(uint32_t a,const uint32_t* v){ asm volatile("st.shared.v4.u32 [%0], {%1,%2,%3,%4};"::"r"(a),"r"(v[0]),"r"(v[1]),"r"(v[2]),"r"(v[3]):"memory"); }
__device__ __forceinline__ void sts2(uint32_t a,uint32_t x,uint32_t y){ asm volatile("st.shared.v2.u32 [%0], {%1,%2};"::"r"(a),"r"(x),"r"(y):"memory"); }
__device__ __forceinline__ float4 lds4f(uint32_t a){ float4 v; asm volatile("ld.shared.v4.f32 {%0,%1,%2,%3}, [%4];":"=f"(v.x),"=f"(v.y),"=f"(v.z),"=f"(v.w):"r"(a):"memory"); return v; }
__device__ __forceinline__ float2 lds2f(uint32_t a){ float2 v; asm volatile("ld.shared.v2.f32 {%0,%1}, [%2];":"=f"(v.x),"=f"(v.y):"r"(a):"memory"); return v; }
__device__ __forceinline__ uint4 lds4(uint32_t a){ uint4 v; asm volatile("ld.shared.v4.u32 {%0,%1,%2,%3}, [%4];":"=r"(v.x),"=r"(v.y),"=r"(v.z),"=r"(v.w):"r"(a):"memory"); return v; }
__device__ __forceinline__ void lds4r(uint32_t* r,uint32_t a){ asm volatile("ld.shared.v4.u32 {%0,%1,%2,%3}, [%4];":"=r"(r[0]),"=r"(r[1]),"=r"(r[2]),"=r"(r[3]):"r"(a):"memory"); }
__device__ __forceinline__ uint2 lds2(uint32_t a){ uint2 v; asm volatile("ld.shared.v2.u32 {%0,%1}, [%2];":"=r"(v.x),"=r"(v.y):"r"(a):"memory"); return v; }
__device__ __forceinline__ float ex2(float x){ float r; asm("ex2.approx.ftz.f32 %0, %1;":"=f"(r):"f"(x)); return r; }
__device__ __forceinline__ float rcp(float x){ float r; asm("rcp.approx.ftz.f32 %0, %1;":"=f"(r):"f"(x)); return r; }
__device__ __forceinline__ void mbar_init(uint32_t a,int n){ asm volatile("mbarrier.init.shared.b64 [%0], %1;"::"r"(a),"r"(n):"memory"); }
__device__ __forceinline__ void mbar_expect(uint32_t a,int bytes){ asm volatile("mbarrier.arrive.expect_tx.shared.b64 _, [%0], %1;"::"r"(a),"r"(bytes):"memory"); }
__device__ __forceinline__ void mbar_arrive(uint32_t a){ asm volatile("mbarrier.arrive.shared.b64 _, [%0];"::"r"(a):"memory"); }
__device__ __forceinline__ bool mbar_try(uint32_t a,uint32_t par){ uint32_t ok; asm volatile("{\n.reg .pred p;\nmbarrier.try_wait.parity.shared.b64 p, [%1], %2;\nselp.u32 %0,1,0,p;\n}":"=r"(ok):"r"(a),"r"(par):"memory"); return ok; }
__device__ __forceinline__ bool mbar_test(uint32_t a,uint32_t par){ uint32_t ok; asm volatile("{\n.reg .pred p;\nmbarrier.test_wait.parity.shared.b64 p, [%1], %2;\nselp.u32 %0,1,0,p;\n}":"=r"(ok):"r"(a),"r"(par):"memory"); return ok; }
__device__ __forceinline__ bool mbar_try_cl(uint32_t a,uint32_t par){ uint32_t ok; asm volatile("{\n.reg .pred p;\nmbarrier.try_wait.parity.acquire.cluster.shared::cta.b64 p, [%1], %2;\nselp.u32 %0,1,0,p;\n}":"=r"(ok):"r"(a),"r"(par):"memory"); return ok; }
__device__ __forceinline__ void bulk_g2s(uint32_t dst,const void* src,int bytes,uint32_t mb){ asm volatile("cp.async.bulk.shared::cluster.global.mbarrier::complete_tx::bytes [%0], [%1], %2, [%3];"::"r"(dst),"l"(src),"r"(bytes),"r"(mb):"memory"); }
__device__ __forceinline__ uint32_t mapa(uint32_t a,uint32_t r){ uint32_t d; asm("mapa.shared::cluster.u32 %0, %1, %2;":"=r"(d):"r"(a),"r"(r)); return d; }
__device__ __forceinline__ void st_async2(uint32_t ra,uint32_t x,uint32_t y,uint32_t rmb){ asm volatile("st.async.weak.shared::cluster.mbarrier::complete_tx::bytes.v2.b32 [%0], {%1,%2}, [%3];"::"r"(ra),"r"(x),"r"(y),"r"(rmb):"memory"); }
__device__ __forceinline__ void st_async4(uint32_t ra,uint32_t x,uint32_t y,uint32_t z,uint32_t w,uint32_t rmb){ asm volatile("st.async.weak.shared::cluster.mbarrier::complete_tx::bytes.v4.b32 [%0], {%1,%2,%3,%4}, [%5];"::"r"(ra),"r"(x),"r"(y),"r"(z),"r"(w),"r"(rmb):"memory"); }
__device__ __forceinline__ void stg_rlx4(uint32_t* p,uint32_t a,uint32_t b,uint32_t c,uint32_t d){ asm volatile("st.relaxed.gpu.global.v4.u32 [%0], {%1,%2,%3,%4};"::"l"(p),"r"(a),"r"(b),"r"(c),"r"(d):"memory"); }
__device__ __forceinline__ void red64(void* p,uint32_t lo,uint32_t hi){ asm volatile("{\n.reg .b64 v;\nmov.b64 v, {%1,%2};\nred.relaxed.gpu.global.add.u64 [%0], v;\n}"::"l"(p),"r"(lo),"r"(hi):"memory"); }
__device__ __forceinline__ uint32_t amax2(uint32_t a,uint32_t b){ uint32_t r; asm("max.xorsign.abs.bf16x2 %0, %1, %2;":"=r"(r):"r"(a),"r"(b)); return r; }
__device__ __forceinline__ void cluster_sync(){ asm volatile("barrier.cluster.arrive.release.aligned;\nbarrier.cluster.wait.acquire.aligned;":::"memory"); }
__device__ __forceinline__ uint32_t ld_acq(const uint32_t* p){ uint32_t v; asm volatile("ld.acquire.gpu.global.u32 %0, [%1];":"=r"(v):"l"(p):"memory"); return v; }
__device__ __forceinline__ void fence_async_all(){ asm volatile("fence.proxy.async;":::"memory"); }
__device__ __forceinline__ void fence_async_g(){ asm volatile("fence.proxy.async.global;":::"memory"); }
__device__ __forceinline__ void fence_rel(){ asm volatile("fence.release.gpu;":::"memory"); }
__device__ __forceinline__ void fence_acq(){ asm volatile("fence.acquire.gpu;":::"memory"); }
__device__ __forceinline__ void fence_gpu(){ asm volatile("fence.acq_rel.gpu;":::"memory"); }

template<int NL,class V,class LDF,class OKF>
__device__ __forceinline__ int poll1(V* u,LDF ld,OKF ok,bool& dead,int code){
  #pragma unroll
  for(int i=0;i<NL;i++) u[i]=ld(i);
  int guard=0;
  while(true){
    bool f[NL]; bool a=true;
    #pragma unroll
    for(int i=0;i<NL;i++){ f[i]=ok(u[i]); a=a&&f[i]; }
    if(__all_sync(~0u,a)||dead) break;
    #pragma unroll
    for(int i=0;i<NL;i++) if(!f[i]) u[i]=ld(i);
    if(++guard>GUARD){ dead=true; g_err=code; }
  }
  return guard;
}
template<int NL,class V,class LDF,class OKF>
__device__ __forceinline__ int poll2(V* u,LDF ld,OKF ok,bool& dead,int code){
  int guard=0;
  while(true){
    bool f[NL]; bool a=true;
    #pragma unroll
    for(int i=0;i<NL;i++){ f[i]=ok(u[i]); a=a&&f[i]; }
    if(__all_sync(~0u,a)||dead) break;
    #pragma unroll
    for(int i=0;i<NL;i++) if(!f[i]) u[i]=ld(i);
    if(++guard>GUARD){ dead=true; g_err=code; }
  }
  return guard;
}
__device__ __forceinline__ void spin(uint32_t n){ uint32_t t0,t1; asm volatile("mov.u32 %0, %%clock;":"=r"(t0)); do{ asm volatile("mov.u32 %0, %%clock;":"=r"(t1)); }while(t1-t0<n); }
template<int N> __device__ __forceinline__ void wgmma(float* d,uint32_t da,uint32_t db,int sc);
template<int N> __device__ __forceinline__ void wgmma_rs(float* d,const uint32_t* a,uint32_t db,int sc);
template<> __device__ __forceinline__ void wgmma<128>(float* d,uint32_t da,uint32_t db,int sc){
  asm volatile("{\n.reg .pred p;\n.reg .b64 xa, xb;\nmov.b64 xa, {%64, 0x40000040};\nmov.b64 xb, {%65, 0x40000040};\nsetp.ne.b32 p, %66, 0;\nwgmma.mma_async.sync.aligned.m64n128k16.f32.bf16.bf16 {%0,%1,%2,%3,%4,%5,%6,%7,%8,%9,%10,%11,%12,%13,%14,%15,%16,%17,%18,%19,%20,%21,%22,%23,%24,%25,%26,%27,%28,%29,%30,%31,%32,%33,%34,%35,%36,%37,%38,%39,%40,%41,%42,%43,%44,%45,%46,%47,%48,%49,%50,%51,%52,%53,%54,%55,%56,%57,%58,%59,%60,%61,%62,%63}, xa, xb, p, 1, 1, 0, 1;\n}"
   :"+f"(d[0]),"+f"(d[1]),"+f"(d[2]),"+f"(d[3]),"+f"(d[4]),"+f"(d[5]),"+f"(d[6]),"+f"(d[7]),"+f"(d[8]),"+f"(d[9]),"+f"(d[10]),"+f"(d[11]),"+f"(d[12]),"+f"(d[13]),"+f"(d[14]),"+f"(d[15]),"+f"(d[16]),"+f"(d[17]),"+f"(d[18]),"+f"(d[19]),"+f"(d[20]),"+f"(d[21]),"+f"(d[22]),"+f"(d[23]),"+f"(d[24]),"+f"(d[25]),"+f"(d[26]),"+f"(d[27]),"+f"(d[28]),"+f"(d[29]),"+f"(d[30]),"+f"(d[31]),"+f"(d[32]),"+f"(d[33]),"+f"(d[34]),"+f"(d[35]),"+f"(d[36]),"+f"(d[37]),"+f"(d[38]),"+f"(d[39]),"+f"(d[40]),"+f"(d[41]),"+f"(d[42]),"+f"(d[43]),"+f"(d[44]),"+f"(d[45]),"+f"(d[46]),"+f"(d[47]),"+f"(d[48]),"+f"(d[49]),"+f"(d[50]),"+f"(d[51]),"+f"(d[52]),"+f"(d[53]),"+f"(d[54]),"+f"(d[55]),"+f"(d[56]),"+f"(d[57]),"+f"(d[58]),"+f"(d[59]),"+f"(d[60]),"+f"(d[61]),"+f"(d[62]),"+f"(d[63]):"r"(da),"r"(db),"r"(sc));
}
template<> __device__ __forceinline__ void wgmma<192>(float* d,uint32_t da,uint32_t db,int sc){
  asm volatile("{\n.reg .pred p;\n.reg .b64 xa, xb;\nmov.b64 xa, {%96, 0x40000040};\nmov.b64 xb, {%97, 0x40000040};\nsetp.ne.b32 p, %98, 0;\nwgmma.mma_async.sync.aligned.m64n192k16.f32.bf16.bf16 {%0,%1,%2,%3,%4,%5,%6,%7,%8,%9,%10,%11,%12,%13,%14,%15,%16,%17,%18,%19,%20,%21,%22,%23,%24,%25,%26,%27,%28,%29,%30,%31,%32,%33,%34,%35,%36,%37,%38,%39,%40,%41,%42,%43,%44,%45,%46,%47,%48,%49,%50,%51,%52,%53,%54,%55,%56,%57,%58,%59,%60,%61,%62,%63,%64,%65,%66,%67,%68,%69,%70,%71,%72,%73,%74,%75,%76,%77,%78,%79,%80,%81,%82,%83,%84,%85,%86,%87,%88,%89,%90,%91,%92,%93,%94,%95}, xa, xb, p, 1, 1, 0, 1;\n}"
   :"+f"(d[0]),"+f"(d[1]),"+f"(d[2]),"+f"(d[3]),"+f"(d[4]),"+f"(d[5]),"+f"(d[6]),"+f"(d[7]),"+f"(d[8]),"+f"(d[9]),"+f"(d[10]),"+f"(d[11]),"+f"(d[12]),"+f"(d[13]),"+f"(d[14]),"+f"(d[15]),"+f"(d[16]),"+f"(d[17]),"+f"(d[18]),"+f"(d[19]),"+f"(d[20]),"+f"(d[21]),"+f"(d[22]),"+f"(d[23]),"+f"(d[24]),"+f"(d[25]),"+f"(d[26]),"+f"(d[27]),"+f"(d[28]),"+f"(d[29]),"+f"(d[30]),"+f"(d[31]),"+f"(d[32]),"+f"(d[33]),"+f"(d[34]),"+f"(d[35]),"+f"(d[36]),"+f"(d[37]),"+f"(d[38]),"+f"(d[39]),"+f"(d[40]),"+f"(d[41]),"+f"(d[42]),"+f"(d[43]),"+f"(d[44]),"+f"(d[45]),"+f"(d[46]),"+f"(d[47]),"+f"(d[48]),"+f"(d[49]),"+f"(d[50]),"+f"(d[51]),"+f"(d[52]),"+f"(d[53]),"+f"(d[54]),"+f"(d[55]),"+f"(d[56]),"+f"(d[57]),"+f"(d[58]),"+f"(d[59]),"+f"(d[60]),"+f"(d[61]),"+f"(d[62]),"+f"(d[63]),"+f"(d[64]),"+f"(d[65]),"+f"(d[66]),"+f"(d[67]),"+f"(d[68]),"+f"(d[69]),"+f"(d[70]),"+f"(d[71]),"+f"(d[72]),"+f"(d[73]),"+f"(d[74]),"+f"(d[75]),"+f"(d[76]),"+f"(d[77]),"+f"(d[78]),"+f"(d[79]),"+f"(d[80]),"+f"(d[81]),"+f"(d[82]),"+f"(d[83]),"+f"(d[84]),"+f"(d[85]),"+f"(d[86]),"+f"(d[87]),"+f"(d[88]),"+f"(d[89]),"+f"(d[90]),"+f"(d[91]),"+f"(d[92]),"+f"(d[93]),"+f"(d[94]),"+f"(d[95]):"r"(da),"r"(db),"r"(sc));
}
template<> __device__ __forceinline__ void wgmma_rs<80>(float* d,const uint32_t* a,uint32_t db,int sc){
  asm volatile("{\n.reg .pred p;\n.reg .b64 xb;\nmov.b64 xb, {%44, 0x40000040};\nsetp.ne.b32 p, %45, 0;\nwgmma.mma_async.sync.aligned.m64n80k16.f32.bf16.bf16 {%0,%1,%2,%3,%4,%5,%6,%7,%8,%9,%10,%11,%12,%13,%14,%15,%16,%17,%18,%19,%20,%21,%22,%23,%24,%25,%26,%27,%28,%29,%30,%31,%32,%33,%34,%35,%36,%37,%38,%39}, {%40,%41,%42,%43}, xb, p, 1, 1, 0;\n}"
   :"+f"(d[0]),"+f"(d[1]),"+f"(d[2]),"+f"(d[3]),"+f"(d[4]),"+f"(d[5]),"+f"(d[6]),"+f"(d[7]),"+f"(d[8]),"+f"(d[9]),"+f"(d[10]),"+f"(d[11]),"+f"(d[12]),"+f"(d[13]),"+f"(d[14]),"+f"(d[15]),"+f"(d[16]),"+f"(d[17]),"+f"(d[18]),"+f"(d[19]),"+f"(d[20]),"+f"(d[21]),"+f"(d[22]),"+f"(d[23]),"+f"(d[24]),"+f"(d[25]),"+f"(d[26]),"+f"(d[27]),"+f"(d[28]),"+f"(d[29]),"+f"(d[30]),"+f"(d[31]),"+f"(d[32]),"+f"(d[33]),"+f"(d[34]),"+f"(d[35]),"+f"(d[36]),"+f"(d[37]),"+f"(d[38]),"+f"(d[39]):"r"(a[0]),"r"(a[1]),"r"(a[2]),"r"(a[3]),"r"(db),"r"(sc));
}
template<> __device__ __forceinline__ void wgmma_rs<192>(float* d,const uint32_t* a,uint32_t db,int sc){
  asm volatile("{\n.reg .pred p;\n.reg .b64 xb;\nmov.b64 xb, {%100, 0x40000040};\nsetp.ne.b32 p, %101, 0;\nwgmma.mma_async.sync.aligned.m64n192k16.f32.bf16.bf16 {%0,%1,%2,%3,%4,%5,%6,%7,%8,%9,%10,%11,%12,%13,%14,%15,%16,%17,%18,%19,%20,%21,%22,%23,%24,%25,%26,%27,%28,%29,%30,%31,%32,%33,%34,%35,%36,%37,%38,%39,%40,%41,%42,%43,%44,%45,%46,%47,%48,%49,%50,%51,%52,%53,%54,%55,%56,%57,%58,%59,%60,%61,%62,%63,%64,%65,%66,%67,%68,%69,%70,%71,%72,%73,%74,%75,%76,%77,%78,%79,%80,%81,%82,%83,%84,%85,%86,%87,%88,%89,%90,%91,%92,%93,%94,%95}, {%96,%97,%98,%99}, xb, p, 1, 1, 1;\n}"
   :"+f"(d[0]),"+f"(d[1]),"+f"(d[2]),"+f"(d[3]),"+f"(d[4]),"+f"(d[5]),"+f"(d[6]),"+f"(d[7]),"+f"(d[8]),"+f"(d[9]),"+f"(d[10]),"+f"(d[11]),"+f"(d[12]),"+f"(d[13]),"+f"(d[14]),"+f"(d[15]),"+f"(d[16]),"+f"(d[17]),"+f"(d[18]),"+f"(d[19]),"+f"(d[20]),"+f"(d[21]),"+f"(d[22]),"+f"(d[23]),"+f"(d[24]),"+f"(d[25]),"+f"(d[26]),"+f"(d[27]),"+f"(d[28]),"+f"(d[29]),"+f"(d[30]),"+f"(d[31]),"+f"(d[32]),"+f"(d[33]),"+f"(d[34]),"+f"(d[35]),"+f"(d[36]),"+f"(d[37]),"+f"(d[38]),"+f"(d[39]),"+f"(d[40]),"+f"(d[41]),"+f"(d[42]),"+f"(d[43]),"+f"(d[44]),"+f"(d[45]),"+f"(d[46]),"+f"(d[47]),"+f"(d[48]),"+f"(d[49]),"+f"(d[50]),"+f"(d[51]),"+f"(d[52]),"+f"(d[53]),"+f"(d[54]),"+f"(d[55]),"+f"(d[56]),"+f"(d[57]),"+f"(d[58]),"+f"(d[59]),"+f"(d[60]),"+f"(d[61]),"+f"(d[62]),"+f"(d[63]),"+f"(d[64]),"+f"(d[65]),"+f"(d[66]),"+f"(d[67]),"+f"(d[68]),"+f"(d[69]),"+f"(d[70]),"+f"(d[71]),"+f"(d[72]),"+f"(d[73]),"+f"(d[74]),"+f"(d[75]),"+f"(d[76]),"+f"(d[77]),"+f"(d[78]),"+f"(d[79]),"+f"(d[80]),"+f"(d[81]),"+f"(d[82]),"+f"(d[83]),"+f"(d[84]),"+f"(d[85]),"+f"(d[86]),"+f"(d[87]),"+f"(d[88]),"+f"(d[89]),"+f"(d[90]),"+f"(d[91]),"+f"(d[92]),"+f"(d[93]),"+f"(d[94]),"+f"(d[95]):"r"(a[0]),"r"(a[1]),"r"(a[2]),"r"(a[3]),"r"(db),"r"(sc));
}
__global__ void __launch_bounds__(256) k_pre(const bf16* __restrict__ x,const bf16* __restrict__ mem0){
  const int warp=threadIdx.x>>5, lane=threadIdx.x&31;
  const int row=blockIdx.x*8+warp;
  asm volatile("griddepcontrol.launch_dependents;");
  {
    int i=blockIdx.x*256+threadIdx.x; constexpr int n=(S/8)*256;
    if(blockIdx.x==S/8){
      __shared__ uint32_t smx[8];
      uint32_t w[10], mx=0;
      #pragma unroll
      for(int j=0;j<10;j++){ const int k=threadIdx.x+256*j; const uint16_t* mp=(const uint16_t*)mem0+(((k>>3)&3)*2+((k>>5)&1))*D+(k>>6)*16+(k&7);
        w[j]=mp[0]|((uint32_t)mp[8]<<16); mx=max(mx,max(w[j]&0x7fffu,(w[j]>>16)&0x7fffu)); }
      mx=__reduce_max_sync(~0u,mx); if(lane==0) smx[warp]=mx;
      __syncthreads();
      #pragma unroll
      for(int j=0;j<8;j++) mx=max(mx,smx[j]);
      const uint32_t eb=min(max(mx>>7,40u),254u); const float sc=__uint_as_float((280u-eb)<<23);
      #pragma unroll
      for(int j=0;j<10;j++) g_acc[threadIdx.x+256*j]=((unsigned long long)(long long)__float2int_rn(__uint_as_float(w[j]&0xffff0000u)*sc)<<35)+((unsigned long long)(long long)__float2int_rn(__uint_as_float(w[j]<<16)*sc)<<6);
      if(threadIdx.x<NCTA*2) g_nrm[threadIdx.x]=SENT;
      if(threadIdx.x==0) g_nrm[NCTA*2]=(eb-29u)<<23;
      return;
    }
    for(int k=1280+i;k<NSEG*1280;k+=n) ((ulonglong2*)g_acc)[k]=make_ulonglong2(ACC_INIT,ACC_INIT);
    if(i==0) g_err=0;
    if(i<NCTA*32) g_flag[i]=0;
    if(i<C_NUM) g_cnt[i]=0;
  }
  float v[20];
  {
    const uint32_t* p=(const uint32_t*)(x+(size_t)row*D);
    #pragma unroll
    for(int i=0;i<10;i++){ uint32_t u=p[lane+32*i]; v[2*i]=__uint_as_float(u<<16); v[2*i+1]=__uint_as_float(u&0xffff0000u); }
  }
  #pragma unroll
  for(int pass=0;pass<2;pass++){
    float s=0;
    #pragma unroll
    for(int i=0;i<20;i++) s+=v[i];
    #pragma unroll
    for(int o=16;o;o>>=1) s+=__shfl_xor_sync(~0u,s,o);
    float mean=s*(1.f/D);
    float q=0;
    #pragma unroll
    for(int i=0;i<20;i++){ float d=v[i]-mean; q+=d*d; }
    #pragma unroll
    for(int o=16;o;o>>=1) q+=__shfl_xor_sync(~0u,q,o);
    float var=rb(q*(1.f/D)), mb=rb(mean);
    float den=rb(sqrtf(rb(var+1e-5f)));
    uint32_t* o=(uint32_t*)((pass?g_y:g_xn)+(size_t)row*D);
    #pragma unroll
    for(int i=0;i<10;i++){
      float a=rb(rb(v[2*i]-mb)/den), b=rb(rb(v[2*i+1]-mb)/den);
      v[2*i]=a; v[2*i+1]=b;
      o[lane+32*i]=pack_bf16(a,b);
    }
  }
}

#define ULAY 0
#define WGO 1
#define UBP 4
#define URM 63
#define UEB 24
#define NOF 0
#define EXD 0
#define UEX 1
#define ADELAY 0
#define KP 4
#define UXP 16
#define OPF 99
#define XGP 0
#define W3O 250
#define FW 3
#define WPA 1
#define WPB 1
#define PD 1000
#define PPOS 2
#define ADP 0
#define ADUP 64
#define ADDN 4
constexpr int SM_QS=0;
constexpr int SM_KS=49152;
constexpr int SM_OS=131072;
constexpr int SM_RED=180224;
constexpr int SM_P=SM_RED+3584;
constexpr int SM_PM=SM_RED+4096+3584;
constexpr int SM_MB=SM_PM+128;
constexpr int SM_MX=SM_PM+192, SM_SCL=SM_PM+224;
constexpr int SM_X5=SM_RED+8192+3584;
constexpr int SM_KX=SM_RED+16384;
constexpr int SM_VX=SM_KX+4096;
constexpr int SM_SCX=SM_VX+14336;
constexpr int SM_KRED=SM_SCX+6144;
constexpr int SM_VMX=SM_KRED+8192;
constexpr int SM_TOTAL=SM_VMX+3072, SM_NR=SM_VMX;
static_assert(SM_TOTAL<=232448,"smem");
__device__ __forceinline__ void wg32_rs(float* d,const uint32_t* a,uint32_t db){
  asm volatile("{\n.reg .b64 xb;\nmov.b64 xb, {%20, 0x40000040};\nwgmma.mma_async.sync.aligned.m64n32k16.f32.bf16.bf16 {%0,%1,%2,%3,%4,%5,%6,%7,%8,%9,%10,%11,%12,%13,%14,%15}, {%16,%17,%18,%19}, xb, 1, 1, 1, 0;\n}"
   :"+f"(d[0]),"+f"(d[1]),"+f"(d[2]),"+f"(d[3]),"+f"(d[4]),"+f"(d[5]),"+f"(d[6]),"+f"(d[7]),"+f"(d[8]),"+f"(d[9]),"+f"(d[10]),"+f"(d[11]),"+f"(d[12]),"+f"(d[13]),"+f"(d[14]),"+f"(d[15])
   :"r"(a[0]),"r"(a[1]),"r"(a[2]),"r"(a[3]),"r"(db));
}
__device__ __forceinline__ void wg32_rs0(float* d,const uint32_t* a,uint32_t db){
  asm volatile("{\n.reg .b64 xb;\nmov.b64 xb, {%20, 0x40000040};\nwgmma.mma_async.sync.aligned.m64n32k16.f32.bf16.bf16 {%0,%1,%2,%3,%4,%5,%6,%7,%8,%9,%10,%11,%12,%13,%14,%15}, {%16,%17,%18,%19}, xb, 0, 1, 1, 0;\n}"
   :"=f"(d[0]),"=f"(d[1]),"=f"(d[2]),"=f"(d[3]),"=f"(d[4]),"=f"(d[5]),"=f"(d[6]),"=f"(d[7]),"=f"(d[8]),"=f"(d[9]),"=f"(d[10]),"=f"(d[11]),"=f"(d[12]),"=f"(d[13]),"=f"(d[14]),"=f"(d[15])
   :"r"(a[0]),"r"(a[1]),"r"(a[2]),"r"(a[3]),"r"(db));
}
__device__ __forceinline__ void wg32_ss(float* d,uint32_t da,uint32_t db){
  asm volatile("{\n.reg .b64 xa, xb;\nmov.b64 xa, {%16, 0x00000180};\nmov.b64 xb, {%17, 0x40000040};\nwgmma.mma_async.sync.aligned.m64n32k16.f32.bf16.bf16 {%0,%1,%2,%3,%4,%5,%6,%7,%8,%9,%10,%11,%12,%13,%14,%15}, xa, xb, 1, 1, 1, 0, 0;\n}"
   :"+f"(d[0]),"+f"(d[1]),"+f"(d[2]),"+f"(d[3]),"+f"(d[4]),"+f"(d[5]),"+f"(d[6]),"+f"(d[7]),"+f"(d[8]),"+f"(d[9]),"+f"(d[10]),"+f"(d[11]),"+f"(d[12]),"+f"(d[13]),"+f"(d[14]),"+f"(d[15])
   :"r"(da),"r"(db));
}
__device__ __forceinline__ void wg32_ss0(float* d,uint32_t da,uint32_t db){
  asm volatile("{\n.reg .b64 xa, xb;\nmov.b64 xa, {%16, 0x00000180};\nmov.b64 xb, {%17, 0x40000040};\nwgmma.mma_async.sync.aligned.m64n32k16.f32.bf16.bf16 {%0,%1,%2,%3,%4,%5,%6,%7,%8,%9,%10,%11,%12,%13,%14,%15}, xa, xb, 0, 1, 1, 0, 0;\n}"
   :"=f"(d[0]),"=f"(d[1]),"=f"(d[2]),"=f"(d[3]),"=f"(d[4]),"=f"(d[5]),"=f"(d[6]),"=f"(d[7]),"=f"(d[8]),"=f"(d[9]),"=f"(d[10]),"=f"(d[11]),"=f"(d[12]),"=f"(d[13]),"=f"(d[14]),"=f"(d[15])
   :"r"(da),"r"(db));
}
template<int V> struct IC{ static constexpr int v=V; };
__device__ __forceinline__ uint32_t lds1(uint32_t a){ uint32_t v; asm volatile("ld.shared.u32 %0, [%1];":"=r"(v):"r"(a):"memory"); return v; }
__device__ __forceinline__ void sts1(uint32_t a,uint32_t x){ asm volatile("st.shared.u32 [%0], %1;"::"r"(a),"r"(x):"memory"); }

#define TS(i)
#define TSB(i)
#define PC(i) (void)np
#define TW(i)
#define TF(i)
#define TFP(i)

__device__ __forceinline__ void cp_commit(){ asm volatile("cp.async.commit_group;":::"memory"); }
template<int N> __device__ __forceinline__ void cp_wait(){ asm volatile("cp.async.wait_group %0;"::"n"(N):"memory"); }
__device__ __forceinline__ void tma2d(uint32_t dst,const CUtensorMap* tm,int c0,int c1,uint32_t mb){
  asm volatile("cp.async.bulk.tensor.2d.shared::cluster.global.mbarrier::complete_tx::bytes [%0], [%1, {%3, %4}], [%2];"::"r"(dst),"l"(tm),"r"(mb),"r"(c0),"r"(c1):"memory"); }
__device__ __forceinline__ void tma2d_pf(const CUtensorMap* tm,int c0,int c1){
  asm volatile("cp.async.bulk.prefetch.tensor.2d.L2.global [%0, {%1, %2}];"::"l"(tm),"r"(c0),"r"(c1):"memory"); }
__global__ void __launch_bounds__(256,1) k_rec(const __grid_constant__ CUtensorMap tmK,const __grid_constant__ CUtensorMap tmV,const bf16* __restrict__ Wq,const bf16* __restrict__ Wk,const bf16* __restrict__ Wv,const bf16* __restrict__ Wo,const uint32_t zero){
  extern __shared__ __align__(1024) uint8_t sm[];
  const int tid=threadIdx.x, warp=__shfl_sync(~0u,tid>>5,0), lane=tid&31, g=lane>>2, t=lane&3;
  const int b=blockIdx.x, h=b/3, c=b-3*h;
  const uint32_t sb=(uint32_t)__cvta_generic_to_shared(sm);
  const int kq=warp&3, mg=warp>>2, wt=warp-mg;
  const uint32_t s16=sb+lane*16;
  const uint32_t qs=lane*16+__shfl_sync(~0u,sb+(mg?SM_KS+kq*20480:SM_QS+kq*12288),0), m5u=__shfl_sync(~0u,sb+SM_X5+(kq>>1)*4096+(kq&1)*256,0), mo=((lane>>3)&1), os=sb+SM_OS+kq*12288+mo*6144+(lane>>4)*128+(lane&7)*16, us=sb+SM_VX+wt*2048+mo*512+(lane>>4)*128+(lane&7)*16;
  const uint32_t XS=sb+SM_MB, KVB=sb+SM_MB+8, XV=sb+SM_MB+16, XL=sb+SM_MB+24;
  GT(0);
  asm volatile("griddepcontrol.launch_dependents;");
  const int ntile=c==0?14:13, tile0=c==0?0:(1+13*c);
  uint32_t pw[40][4];
  auto ldW=[&](int p,uint32_t stg){
    #pragma unroll
    for(int i=0;i<12;i++){
      const int idx=tid+256*i, row=idx>>3, ch=idx&7, m=row>>7, f=160*((row>>5)&3)+32*p+(row&31);
      const bf16* src=(m==0?Wq:(m==1?Wk:Wv))+(size_t)f*HD+h*DH+64*c+ch*8;
      const int sw=(row>>1)&7;
      cp16(stg+row*128+((ch^sw)<<4),src);
    }
    cp_commit();
  };
  auto ldO=[&](int r,uint32_t stg){
    for(int idx=tid;idx<96*28;idx+=256){
      const int row=idx/28, ch=idx-row*28;
      if(ch<2*ntile) cp16(stg+row*464+ch*16,Wo+(size_t)(h*DH+((4*c+6*r+(row>>4))%12)*16+(row&15))*D+tile0*16+ch*8);
    }
    cp_commit();
  };
#define SG(i)
  float nr[2][4]={{0.f,0.f,0.f,0.f},{0.f,0.f,0.f,0.f}};
  auto sq=[&](const uint32_t* r){ mma1688(nr[0],r[0],r[1],r[0]); mma1688(nr[1],r[0],r[1],r[1]); mma1688(nr[0],r[2],r[3],r[2]); mma1688(nr[1],r[2],r[3],r[3]); };
  auto dg=[&](const float* d,int o){ return g==2*t?d[o]:(g==2*t+1?d[o+1]:0.f); };
  SG(0);
  ldW(0,sb+SM_RED);
  SG(1);
  #pragma unroll
  for(int p=0;p<5;p++){
    const uint32_t stg=sb+((p&1)?SM_OS:SM_RED), nstg=sb+((p&1)?SM_RED:SM_OS);
    if(p<4) ldW(p+1,nstg); else ldO(0,nstg);
    SG(2+3*p);
    cp_wait<1>(); __syncthreads();
    SG(3+3*p);
    #pragma unroll
    for(int e=0;e<2;e++){
      const int k=2*p+e, kb=(k+5)%10;
      const int fo=16*e+(lane&6)+(lane>>4)+8*(lane&1);
      const int sw=(fo>>1)&7;
      #pragma unroll
      for(int j=0;j<4;j++){
        const uint32_t a=stg+((mg*4+kq)*32+fo)*128+(((2*j+((lane>>3)&1))^sw)<<4);
        if(!mg){ if(k<6){ uint32_t r[4]; ldsm4t(r,a); sts4r(qs+(k*4+j)*512,r); } else ldsm4t(pw[k>=6?(k-6)*4+j:0],a); }
        else {
          if(kb<10-KP){ uint32_t r[4]; ldsm4t(r,a); sts4r(qs+(kb*4+j)*512,r); } else ldsm4t(pw[kb>=10-KP?(kb-10+KP)*4+j:0],a);
          const int u=kb*4+j;
          const uint32_t av=stg+((8+kq)*32+fo)*128+(((2*((j+kq)&3)+((lane>>3)&1))^sw)<<4);
          if(u<4*KP){ uint32_t r[4]; ldsm4t(r,av); sts4r(qs+(40-4*KP+u)*512,r); sq(r); } else { ldsm4t(pw[u],av); sq(pw[u]); }
        }
      }
    }
    __syncthreads();
    SG(4+3*p);
  }
  float nv=dg(nr[0],0)+dg(nr[1],2);
  #pragma unroll
  for(int o=16;o;o>>=1) nv+=__shfl_xor_sync(~0u,nv,o);
  if(lane==0) sts1(sb+SM_NR+warp*8,__float_as_uint(nv));
  nr[0][0]=nr[0][1]=nr[0][2]=nr[0][3]=0.f; nr[1][0]=nr[1][1]=nr[1][2]=nr[1][3]=0.f;
  #pragma unroll
  for(int r=0;r<2;r++){
    const uint32_t stg=sb+(r?SM_RED:SM_OS);
    if(r==0){ ldO(1,sb+SM_RED); cp_wait<1>(); } else cp_wait<0>();
    __syncthreads();
    SG(17+2*r);
    uint32_t rr[12][4];
    #pragma unroll
    for(int kk=0;kk<6;kk++){
      #pragma unroll
      for(int i=0;i<2;i++){
        int tl=2*wt+i; if(tl>=ntile) tl=0;
        const uint32_t a=stg+(16*kk+(lane&7)+(lane>>4)*8)*464+(2*tl+((lane>>3)&1))*16;
        if(mg){ ldsm4t(rr[kk*2+i],a); sq(rr[kk*2+i]); } else { ldsm4t(pw[16+r*12+kk*2+i],a); sq(pw[16+r*12+kk*2+i]); }
      }
    }
    __syncthreads();
    SG(18+2*r);
    if(mg){
      #pragma unroll
      for(int f=0;f<12;f++) stsm4(os+(r*12+f)*256,rr[f][0],rr[f][1],rr[f][2],rr[f][3]);
    }
  }
  {
    const uint32_t no=__reduce_max_sync(~0u,__float_as_uint(fmaxf(dg(nr[0],0),dg(nr[1],2))));
    if(lane==0) sts1(sb+SM_NR+warp*8+4,no);
  }
  if(tid==96){
    mbar_init(XS,5); mbar_init(KVB,1); mbar_init(XV,1); mbar_init(XL,4);
    asm volatile("fence.mbarrier_init.release.cluster;":::"memory");
    mbar_expect(XS,4096); mbar_expect(XV,2048);
  }
  auto kv_issue=[&](int sn){
    if(lane==0){
      mbar_expect(KVB,32*512);
      tma2d(sb+SM_KX,&tmK,h*DH+64*c,sn*32,KVB);
      #pragma unroll
      for(int i=0;i<3;i++) tma2d(sb+SM_VX+i*4096,&tmV,h*DH+64*i,sn*32,KVB);
    }
    __syncwarp();
  };
  auto kv_chk=[&](int rbk){
    if(lane==0){ int gd=0; while(ld_acq(g_cnt+C_KV+rbk)<64){ if(++gd>GUARD){ g_err=7; break; } } fence_async_g(); }
    __syncwarp();
  };
  auto kv_pf=[&](int sn){
    if(lane==0){ tma2d_pf(&tmK,h*DH+64*c,sn*32); tma2d_pf(&tmV,h*DH+64*c,sn*32); }
    __syncwarp();
  };
  fence_async();
  __syncthreads();
  SG(21);
  if(tid==0){
    float a=0.f; uint32_t o=0;
    #pragma unroll
    for(int w=0;w<8;w++){ const uint2 x=lds2(sb+SM_NR+w*8); a+=__uint_as_float(x.x); o=max(o,x.y); }
    stg_rlx2(g_nrm+b*2,min(__float_as_uint(a),0x7f800000u),min(o,0x7f800000u));
  }
  if(tid==32) sts1(sb+SM_SCL+8,g_nrm[NCTA*2]);
  if(warp==2){
    int gd=0; uint32_t x[6];
    #pragma unroll 1
    while(true){
      bool ok=true;
      #pragma unroll
      for(int i=0;i<6;i++){ asm volatile("ld.relaxed.gpu.global.u32 %0, [%1];":"=r"(x[i]):"l"(g_nrm+lane*6+i):"memory"); ok=ok&&x[i]!=SENT; }
      if(__all_sync(~0u,ok)) break;
      if(++gd>GUARD){ g_err=8; break; }
    }
    const float cw=27.5f*sqrtf((__uint_as_float(x[0])+__uint_as_float(x[2]))+__uint_as_float(x[4]))*sqrtf(__uint_as_float(max(x[1],max(x[3],x[5]))));
    sts1(sb+SM_SCL+4,__reduce_max_sync(~0u,__float_as_uint(cw)&0x7fffffffu));
  }
  if(warp==3){ kv_chk(0); kv_issue(0); kv_pf(1); }
  cluster_sync();
  SG(22);
  uint32_t pd=PD;
  bool dead=false;
  const uint32_t qrd=sb+SM_RED+1024+((lane>>3)&1)*4096+(lane>>4)*128+(lane&7)*16+kq*256;
  uint32_t rsc[2];
  rsc[0]=mapa(sb,c==2?0:c+1); rsc[1]=mapa(sb,c==0?2:c-1);
  GT(1);
  auto loop=[&](auto MGc){
  constexpr int MG=decltype(MGc)::v;
  uint32_t buf[8][4], um[2][2]={{0,0},{0,0}}, ex0=0, ex1=0;
  uint32_t eo1=(uint32_t)((32+(h>>2))*40960+(tile0+2*wt)*1024+(h&3)*128+lane*4), eo2=(uint32_t)((g*HD+h*DH+64*c+16*kq+2*t)*2);
  uint32_t so=(uint32_t)((kq*10+MG*5)*512+(g&1)*256+(g>>1)*64+t*16)^zero;
  bool kvok=false;
  #define EXPU { char* um_=(char*)g_u+eo1; _Pragma("unroll") for(int i=0;i<2;i++) if(i==0||2*wt+1<ntile){ stg1(um_+i*1024,um[i][0]); stg1(um_+i*1024+512,um[i][1]); } }
  #define EXPK { uint32_t* ep=(uint32_t*)((char*)g_km+eo2); stg1(ep,ex0); stg1(ep+4,ex1); }
  #define UBULK { const uint32_t o_=(us-sb)&~2047u; asm volatile("{\n.reg .pred p;\nelect.sync _|p, 0xffffffff;\n@p cp.async.bulk.global.shared::cta.bulk_group [%0], [%1], %2;\n@p cp.async.bulk.commit_group;\n}" \
      ::"l"((char*)g_u+(uint32_t)(s*1638400+h*40960+tile0*1024-SM_VX+o_)),"r"(sb+o_),"r"(2*wt+1<ntile?2048:1024):"memory"); }
  uint32_t t0; asm volatile("mov.u32 %0, %%clock;":"=r"(t0)); t0-=4096;
  #define MB0(k) mb[k][0]
  #define MB1(k) mb[k][1]
  #pragma unroll 1
  for(int s=0;s<NSEG;s++){
    const bool last=s==NSEG-1;
    float u[2][16];
    const char* src=(const char*)g_acc+so;
    uint4 m[5];
    #define SPIN(T,N) { uint32_t t1; do{ asm volatile("mov.u32 %0, %%clock;":"=r"(t1)); }while((int)(t1-(T))<(int)(N)); }
    #define PLD { SPIN(t0,pd) _Pragma("unroll") for(int p=0;p<5;p++) m[p]=ldg_rlx4((const uint32_t*)(src+p*512)); SPIN(t0,pd) TFP(21); }
    {
      if(!kvok){ int gd=0; while(!mbar_try(KVB,s&1)){ if(dead) break; if(++gd>GUARD){ dead=true; g_err=6; } } }
      TFP(16);
      const uint32_t da=(((sb+SM_OS)>>4)&0x3fff)|(8u<<16);
      const uint32_t dv=(((sb+SM_VX)>>4)&0x3fff)|(1u<<16);
      const uint32_t vb[3]={dv+c*256,dv+(c==2?0:c+1)*256,dv+(c==0?2:c-1)*256};
      asm volatile("wgmma.fence.sync.aligned;":::"memory");
      if constexpr(MG){
        #pragma unroll
        for(int y=0;y<24;y++){
          const int i=WGO?(y&1):(y>=12), x=WGO?(y>>1):(y%12);
          if(x==0) wg32_ss0(u[i],da+i*16,vb[0]); else wg32_ss(u[i],da+(x*2+i)*16,vb[x>>2]+(x&3)*2);
          if(y==WPB){ EXPU SPIN(t0,0) }
        }
      } else {
        #pragma unroll
        for(int y=0;y<24;y++){
          const int i=WGO?(y&1):(y>=12), x=WGO?(y>>1):(y%12);
          if(x==0) wg32_rs0(u[i],pw[16+i],vb[0]); else wg32_rs(u[i],pw[16+x*2+i],vb[x>>2]+(x&3)*2);
          if(y==WPA&&warp!=3){ EXPU EXPK }
        }
      }
      asm volatile("wgmma.commit_group.sync.aligned;":::"memory");
      TFP(18);
      if(!MG&&warp==3){
        EXPK
        if(lane==0&&s+2<NSEG){ tma2d_pf(&tmK,h*DH+64*c,(s+2)*32); tma2d_pf(&tmV,h*DH+64*c,(s+2)*32); }
        __syncwarp();
        if(b<80&&lane<2&&s+2<NSEG) asm volatile("prefetch.global.L2 [%0];"::"l"(g_acc+(size_t)(s+2)*2560+b*32+lane*16));
      }
      PLD
    }
    const uint32_t mx=s16+SM_RED+kq*4096, m5=m5u+lane*8;
    {
      asm volatile("wgmma.wait_group.sync.aligned 0;":::"memory");
      TFP(19);
      if(MG||warp!=3){
        if(UEX) asm volatile("cp.async.bulk.wait_group 0;":::"memory");
        bar_sync(7,256);
        TFP(20);
        #pragma unroll
        for(int i=0;i<2;i++)
          #pragma unroll
          for(int kk=0;kk<2;kk++)
            stsm4(us+i*1024+kk*256,pack_bf16(u[i][8*kk],u[i][8*kk+1]),pack_bf16(u[i][8*kk+2],u[i][8*kk+3]),pack_bf16(u[i][8*kk+4],u[i][8*kk+5]),pack_bf16(u[i][8*kk+6],u[i][8*kk+7]));
        if(UEX){ fence_async(); if(UBP==0) UBULK }
        #pragma unroll
        for(int i=0;i<8;i++) lds4r(buf[i],qs+i*512);
      } else {
        #pragma unroll
        for(int i=0;i<8;i++) lds4r(buf[i],qs+i*512);
        bar_sync(7,256);
        asm volatile("{\n.reg .pred p, q;\nsetp.eq.u32 p, %0, 0;\nsetp.eq.and.u32 q, %1, 0, p;\n@q fence.release.gpu;\n@p st.relaxed.gpu.global.u32 [%2], %3;\n}"::"r"(lane),"r"((s&3)|NOF),"l"(g_flag+b*32),"r"(s):"memory");
      }
      SPIN(t0,pd)
      TFP(17);
    }
    uint32_t mb[10][2];
    {
      auto okf=[&](const uint4& v){ return ((v.x|v.z)&63u)==0; };
      const int np=poll2<5>(m,[&](int i){ return ldg_rlx4((const uint32_t*)(src+i*512)); },okf,dead,1);
      TW(0); PC(0); TFP(14);
      if(ADP){ if(np) pd=min(pd+ADUP,2000u); else pd=max(pd-ADDN,(uint32_t)ADP); }
      #pragma unroll
      for(int p=0;p<5;p++){
        mb[p][0]=pack_bf16((float)(int)__funnelshift_r(m[p].x,m[p].y,3),(float)(int)m[p].y);
        mb[p][1]=pack_bf16((float)(int)__funnelshift_r(m[p].z,m[p].w,3),(float)(int)m[p].w);
        if(p==0) sts2(MG?m5:mx-lane*8+3072,mb[0][0],mb[0][1]);
        if(p==2||p==4) sts4(mx+((MG?0:4)+(p>>2))*512,make_uint4(mb[p-1][0],mb[p-1][1],mb[p][0],mb[p][1]));
      }
      bar_arrive((MG?12:8)+kq,64);
      if(UEX&&UBP==1&&(MG||warp!=3)) UBULK
    }
    #define XGET { bar_sync((MG?8:12)+kq,64); const uint2 x=lds2(MG?mx-lane*8+3072:m5); mb[5][0]=x.x; mb[5][1]=x.y; \
      _Pragma("unroll") for(int p=0;p<2;p++){ const uint4 y=lds4(mx+((MG?4:0)+p)*512); mb[6+2*p][0]=y.x; mb[6+2*p][1]=y.y; mb[7+2*p][0]=y.z; mb[7+2*p][1]=y.w; } }
    #define XMAX { uint32_t a=amax2(amax2(amax2(mb[0][0],mb[0][1]),amax2(mb[1][0],mb[1][1])),amax2(amax2(amax2(mb[2][0],mb[2][1]),amax2(mb[3][0],mb[3][1])),amax2(mb[4][0],mb[4][1]))); \
      a=__reduce_max_sync(~0u,max(a&0x7fff0000u,(a<<16)&0x7fff0000u)); if(lane==0) sts1(sb+SM_MX+warp*4,a); }
    TS(0); TF(0);
    float acc[4][4]; uint32_t ux[2][2][4];
    #pragma unroll
    for(int i=0;i<4;i++){ acc[i][0]=acc[i][1]=acc[i][2]=acc[i][3]=0.f; }
    #define UXDEP (((ux[0][0][0]^ux[0][1][0])^(ux[1][0][0]^ux[1][1][0]))&zero)
    if constexpr(MG){
      #pragma unroll
      for(int y=0;y<10;y++){
        const int k=KP==4?(y<2?y:(y<4?y+4:(y<6?y-2:(y<8?y+2:y-4)))):(y<2?y:(y<2+KP?y+8-KP:y-KP));
        #pragma unroll
        for(int j=0;j<4;j++){
          if(k<10-KP){ mma16816(acc[j],buf[(k&1)*4+j],MB0(k),MB1(k)); lds4r(buf[(k&1)*4+j],qs+(k*4+j+8)*512); }
          else mma16816(acc[j],pw[k>=10-KP?(k-10+KP)*4+j:0],MB0(k),MB1(k));
        }
        if(y==XGP) XGET
        if(y==5) XMAX
        if(UEX&&UBP==y+2) UBULK
      }
      TF(1);
      {
        const uint32_t ra=s16+SM_KRED+kq*2048;
        #pragma unroll
        for(int i=0;i<4;i++) sts4f(ra+i*512,acc[i]);
      }
      bar_arrive(1,256);
#define VK(u) ((u)>>2)
      #pragma unroll
      for(int i=0;i<4;i++){ acc[i][0]=acc[i][1]=acc[i][2]=acc[i][3]=0.f; }
      #pragma unroll
      for(int y=0;y<40;y++){
        constexpr int NS_=4*KP;
        const int u=y<8?y:(y<20?y-8+NS_:(y<12+NS_?y-12:y));
        const int sl=(u+40-NS_)&7;
        if(u<NS_){ mma16816(acc[u&3],buf[sl],MB0(VK(u)),MB1(VK(u))); if(u+8<NS_) lds4r(buf[sl],qs+(48-NS_+u)*512); }
        else mma16816(acc[u&3],pw[u],MB0(VK(u)),MB1(VK(u)));
        if(y>=OPF&&y<OPF+8) ldsm4(buf[(y-OPF)&7],os+((y-OPF)&7)*256);
        if(y>=UXP&&y<UXP+4) ldsm4(ux[(y-UXP)>>1][(y-UXP)&1],us+((y-UXP)>>1)*1024+((y-UXP)&1)*256);
      }
      TF(2);
      const uint32_t ra=s16+SM_RED+1536;
      #pragma unroll
      for(int i=1;i<4;i++) sts4f(ra+kq*4096+i*512,acc[i]);
      bar_sync(3,128);
      const float cs=__uint_as_float(lds1(sb+SM_SCL+8+(s&1)*4));
      float4 c1=lds4f(ra+((kq+3)&3)*4096+512), d2=lds4f(ra+((kq+2)&3)*4096+1024), e2=lds4f(ra+((kq+1)&3)*4096+1536);
      const uint32_t p0=pack_bf16(((acc[0][0]+c1.x)+(d2.x+e2.x))*cs,((acc[0][1]+c1.y)+(d2.y+e2.y))*cs), p1=pack_bf16(((acc[0][2]+c1.z)+(d2.z+e2.z))*cs,((acc[0][3]+c1.w)+(d2.w+e2.w))*cs);
      if(UEX) asm volatile("cp.async.bulk.wait_group.read 0;":::"memory");
      bar_arrive(2+UXDEP,256);
      const uint32_t v0=movm(p0), v1=movm(p1);
      const uint32_t off=SM_VMX+(kq>>1)*512+lane*16+(kq&1)*8;
      #pragma unroll
      for(int r=0;r<2;r++) st_async2(rsc[r]+off+(2-r)*1024,v0,v1,rsc[r]+SM_MB+16);
      sts2(sb+off,v0,v1); __syncwarp(); if(lane==0) mbar_arrive(XL);
      TF(5);
      if(OPF>=40){
        #pragma unroll
        for(int i=0;i<8;i++) ldsm4(buf[i],os+i*256);
      }
    } else {
      uint32_t kb[8];
      #pragma unroll
      for(int y=0;y<10;y++){
        const int k=y<2?y:(y<4?y+4:(y<6?y-2:(y<8?y+2:y-4)));
        #pragma unroll
        for(int j=0;j<4;j++){
          if(k<6){ mma16816(acc[j],buf[(k&1)*4+j],MB0(k),MB1(k)); if(k<4) lds4r(buf[(k&1)*4+j],qs+(k*4+j+8)*512); }
          else mma16816(acc[j],pw[k>=6?(k-6)*4+j:0],MB0(k),MB1(k));
        }
        if(y==7){
          const uint32_t ka=sb+SM_KX+(8*kq+(lane&7))*128+((((lane>>3)^(2*kq))^(lane&7))<<4);
          ldsm4(kb,ka); ldsm4(kb+4,ka^64);
        }
        if(y==XGP) XGET
        if(y==5) XMAX
        if(UEX&&UBP==y+2&&warp!=3) UBULK
      }
      TF(1);
      {
        const uint32_t qa=s16+SM_RED+kq*4096+1024;
        #pragma unroll
        for(int i=0;i<2;i++) stsm4(qa+i*512,pack_bf16(acc[2*i][0],acc[2*i][1]),pack_bf16(acc[2*i][2],acc[2*i][3]),pack_bf16(acc[2*i+1][0],acc[2*i+1][1]),pack_bf16(acc[2*i+1][2],acc[2*i+1][3]));
      }
      TF(2);
      bar_sync(1,256);
      TS(1); TF(3);
      const uint32_t ra=s16+SM_KRED+kq*512;
      const float cs=__uint_as_float(lds1(sb+SM_SCL+8+(s&1)*4));
      float4 a3=lds4f(ra), c3=lds4f(ra+2048), d3=lds4f(ra+4096), e3=lds4f(ra+6144);
      uint32_t q[4][2][4];
      #pragma unroll
      for(int i=0;i<4;i++){ ldsm4t(q[i][0],qrd^(i*256)); ldsm4t(q[i][1],(qrd^(i*256))+8192); }
      const uint32_t p2=pack_bf16(((a3.x+c3.x)+(d3.x+e3.x))*cs,((a3.y+c3.y)+(d3.y+e3.y))*cs), p3=pack_bf16(((a3.z+c3.z)+(d3.z+e3.z))*cs,((a3.w+c3.w)+(d3.w+e3.w))*cs);
      const uint32_t f2=movm(p2), f3=movm(p3);
      ex0=f2; ex1=f3;
      float sc[6][4];
      #pragma unroll
      for(int i=0;i<6;i++){ sc[i][0]=sc[i][1]=sc[i][2]=sc[i][3]=0.f; }
      #pragma unroll
      for(int i=0;i<4;i++)
        #pragma unroll
        for(int jp=0;jp<2;jp++){
          mma16816(sc[(i&1)*2+jp],q[i][jp],kb[2*i],kb[2*i+1]);
          if(i==1) mma16816(sc[4+jp],q[0][jp],f2,f3);
        }
      const uint32_t w0=__float_as_uint(((sc[0][0]+sc[0][2])+(sc[1][0]+sc[1][2]))+((sc[2][0]+sc[2][2])+(sc[3][0]+sc[3][2]))), w1=__float_as_uint(((sc[0][1]+sc[0][3])+(sc[1][1]+sc[1][3]))+((sc[2][1]+sc[2][3])+(sc[3][1]+sc[3][3])));
      const uint32_t w2=__float_as_uint((sc[4][0]+sc[4][2])+(sc[5][0]+sc[5][2])), w3=__float_as_uint((sc[4][1]+sc[4][3])+(sc[5][1]+sc[5][3]));
      const uint32_t off=SM_SCX+(c*4+kq)*512+lane*16;
      #pragma unroll
      for(int r=0;r<2;r++) st_async4(rsc[r]+off,w0,w1,w2,w3,rsc[r]+SM_MB);
      sts4(sb+off,make_uint4(w0,w1,w2,w3)); __syncwarp(); if(lane==0) mbar_arrive(XS);
      TS(2); TF(5);
    }
    if(!MG&&warp==3){
      bar_arrive(2,256);
      const float ssc=0.07216878364870322f*__uint_as_float(lds1(sb+SM_SCL+8+(s&1)*4));
      uint32_t kvc; asm volatile("ld.relaxed.gpu.global.u32 %0, [%1];":"=r"(kvc):"l"(g_cnt+C_KV+(((s>>2)+1)&15)):"memory");
      TF(6);
      { int gd=0; while(!mbar_try(XS,s&1)){ if(dead) break; if(++gd>GUARD){ dead=true; g_err=2; } } }
      TF(7);
      float sv[10];
      {
        float4 u[12];
        #pragma unroll
        for(int n=0;n<12;n++) u[n]=lds4f(s16+SM_SCX+n*512);
        uint32_t r[5];
        #pragma unroll
        for(int n=0;n<4;n++) r[n+1]=pack_bf16((u[n].x+u[4+n].x)+u[8+n].x,(u[n].y+u[4+n].y)+u[8+n].y);
        r[0]=pack_bf16((((u[0].z+u[1].z)+(u[2].z+u[3].z))+((u[4].z+u[5].z)+(u[6].z+u[7].z)))+((u[8].z+u[9].z)+(u[10].z+u[11].z)),
                       (((u[0].w+u[1].w)+(u[2].w+u[3].w))+((u[4].w+u[5].w)+(u[6].w+u[7].w)))+((u[8].w+u[9].w)+(u[10].w+u[11].w)));
        #pragma unroll
        for(int n=0;n<5;n++){
          const uint32_t w=pack_bf16(__uint_as_float(r[n]<<16)*ssc,__uint_as_float(r[n]&0xffff0000u)*ssc);
          sv[2*n]=__uint_as_float(w<<16); sv[2*n+1]=__uint_as_float(w&0xffff0000u);
        }
      }
      TF(8);
      float mx=fmaxf(fmaxf(fmaxf(sv[2],sv[3]),fmaxf(sv[4],sv[5])),fmaxf(fmaxf(fmaxf(sv[6],sv[7]),fmaxf(sv[8],sv[9])),fmaxf(sv[0],sv[1])));
      mx=fmaxf(mx,__shfl_xor_sync(~0u,mx,1)); mx=fmaxf(mx,__shfl_xor_sync(~0u,mx,2));
      mx*=-1.4426950408889634f;
      #pragma unroll
      for(int i=0;i<10;i++) sv[i]=ex2(fmaf(sv[i],1.4426950408889634f,mx));
      sts1(sb+SM_PM+lane*4,pack_bf16(sv[0],sv[1]));
      sts4(s16+SM_P,make_uint4(pack_bf16(sv[2],sv[3]),pack_bf16(sv[4],sv[5]),pack_bf16(sv[6],sv[7]),pack_bf16(sv[8],sv[9])));
      TF(9);
      bar_sync(4,256);
      asm volatile("mov.u32 %0, %%clock;":"=r"(t0)); t0+=W3O;
      TF(11);
      if(lane==0){
        mbar_expect(XS,4096); mbar_expect(XV,2048);
        if((s&3)==2){ int gd=0; while(kvc<64&&s<NSEG-4){ kvc=ld_acq(g_cnt+C_KV+(s>>2)+1); if(++gd>GUARD){ g_err=7; break; } } fence_acq(); fence_async_g(); }
      }
      __syncwarp();
      eo2=(uint32_t)(((s*8+g)*HD+h*DH+64*c+16*kq+2*t)*2)^zero;
      TF(13);
    } else {
      if constexpr(!MG){
        #pragma unroll
        for(int i=0;i<2;i++){ ldsm4(ux[i][0],us+i*1024); ldsm4(ux[i][1],us+i*1024+256); }
        {
          const uint4 x=lds4(sb+SM_MX), y=lds4(sb+SM_MX+16); const float cw=__uint_as_float(lds1(sb+SM_SCL+4)), cs=__uint_as_float(lds1(sb+SM_SCL+8+(s&1)*4));
          const float mm=__uint_as_float(max(max(max(x.x,x.y),max(x.z,x.w)),max(max(y.x,y.y),max(y.z,y.w))))*cs;
          const uint32_t eo=min(max((__float_as_uint(cw*fmaxf(mm,1.f))>>23)&255u,37u),254u)-21u;
          if(tid==64){ sts1(sb+SM_SCL,eo*0x00800080u); sts1(sb+SM_SCL+12-(s&1)*4,(eo-3u)<<23); }
        }
        TF(4);
        if(UEX) asm volatile("cp.async.bulk.wait_group.read 0;":::"memory");
        bar_sync(2+UXDEP,256);
        if(!last&&lane==0){
          tma2d(sb+SM_VX+kq*4096,&tmV,h*DH+64*kq,(s+1)*32,KVB);
          if(kq==0) mbar_expect(KVB,32*512);
          if(kq==1) tma2d(sb+SM_KX,&tmK,h*DH+64*c,(s+1)*32,KVB);
        }
        __syncwarp();
      }
      float ca[2][2][4];
      #pragma unroll
      for(int i=0;i<2;i++)
        #pragma unroll
        for(int j=0;j<2;j++){ ca[i][j][0]=ca[i][j][1]=ca[i][j][2]=ca[i][j][3]=0.f; }
      TF(6);
      { int gd=0; while(!mbar_try(XL,s&1)){ if(dead) break; if(++gd>GUARD){ dead=true; g_err=5; } } }
      TF(7);
      uint4 vm[6];
      vm[0]=lds4(s16+SM_VMX); vm[1]=lds4(s16+SM_VMX+512);
      #define VB0(x) (((x)&1)?vm[(x)>>1].z:vm[(x)>>1].x)
      #define VB1(x) (((x)&1)?vm[(x)>>1].w:vm[(x)>>1].y)
      if constexpr(MG){
        #pragma unroll
        for(int x=0;x<12;x++){
          if(x==4){
            TF(8);
            { int gd=0; while(!mbar_try(XV,s&1)){ if(dead) break; if(++gd>GUARD){ dead=true; g_err=3; } } }
            TF(9);
            #pragma unroll
            for(int i=2;i<6;i++) vm[i]=lds4(s16+SM_VMX+i*512);
          }
          #pragma unroll
          for(int i=0;i<2;i++){
            mma16816(ca[i][x&1],buf[(x*2+i)&7],VB0(x),VB1(x));
            if(x<8) ldsm4(buf[(x*2+i)&7],os+(x*2+i+8)*256);
          }
        }
      } else {
        #pragma unroll
        for(int x=0;x<12;x++){
          if(x==4){
            TF(8);
            { int gd=0; while(!mbar_try(XV,s&1)){ if(dead) break; if(++gd>GUARD){ dead=true; g_err=3; } } }
            TF(9);
            #pragma unroll
            for(int i=2;i<6;i++) vm[i]=lds4(s16+SM_VMX+i*512);
          }
          #pragma unroll
          for(int i=0;i<2;i++) mma16816(ca[i][x&1],pw[16+x*2+i],VB0(x),VB1(x));
        }
      }
      TF(10);
      bar_sync(4,256);
      TS(3); TF(11);
      const uint4 pq=lds4(s16+SM_P); const uint32_t pm=lds1(sb+SM_PM+lane*4), on=lds1(sb+SM_SCL);
      kvok=mbar_test(KVB,(s&1)^1);
      const uint32_t one[4]={on,on,on,on};
      float d[2][4], e[4];
      #pragma unroll
      for(int i=0;i<4;i++){ d[0][i]=0.f; d[1][i]=0.f; e[i]=0.f; }
      mma16816(e,one,pq.x,pq.y); mma16816(d[0],ux[0][0],pq.x,pq.y); mma16816(d[1],ux[1][0],pq.x,pq.y);
      mma16816(e,one,pq.z,pq.w); mma16816(d[0],ux[0][1],pq.z,pq.w); mma16816(d[1],ux[1][1],pq.z,pq.w);
      mma1688(e,one[0],one[0],pm);
      #pragma unroll
      for(int i=0;i<2;i++){ um[i][0]=pack_bf16(ca[i][0][0]+ca[i][1][0],ca[i][0][1]+ca[i][1][1]); um[i][1]=pack_bf16(ca[i][0][2]+ca[i][1][2],ca[i][0][3]+ca[i][1][3]); mma1688(d[i],um[i][0],um[i][1],pm); }
      const float i0=rcp(e[0]), i1=rcp(e[1]);
      TF(12);
      const uint32_t ro=(tile0+2*wt)*512+t*64+g*8;
      char* dst=(char*)g_acc+(uint32_t)((s+1)*20480+ro);
      #pragma unroll
      for(int i=0;i<2;i++){
        if(!last&&(i==0||2*wt+1<ntile)){
          red64(dst+i*512,(__float_as_uint(fmaf(d[i][0],i0,12582912.f))<<6)+1u,__float_as_uint(fmaf(d[i][2],i0,12582912.f))<<3);
          red64(dst+i*512+256,(__float_as_uint(fmaf(d[i][1],i1,12582912.f))<<6)+1u,__float_as_uint(fmaf(d[i][3],i1,12582912.f))<<3);
        }
      }
      asm volatile("mov.u32 %0, %%clock;":"=r"(t0));
      {
        const uint32_t z=t0&zero;
        eo1=(uint32_t)(s*1638400+(32+(h>>2))*40960+(tile0+2*wt)*1024+(h&3)*128+((s16-sb)>>2))^z;
        if(!MG) eo2=(uint32_t)(((s*8+g)*HD+h*DH+64*c+16*kq+2*t)*2)^z;
      }
      TW(1);
      TS(4); TF(13);
    }
    so+=20480;
  }
  if(MG||warp!=3) EXPU
  if(!MG) EXPK
  };
  if(mg) loop(IC<1>{}); else loop(IC<0>{});
  asm volatile("cp.async.bulk.wait_group 0;":::"memory");
  __syncthreads();
  if(tid==FW*32){ fence_rel(); stg_rlx1(g_flag+b*32,NSEG); }
  GT(2);
  cluster_sync();
}

#define UTM 0
#define UPF 0
#define KLEAD 16
#define MLEAD 16
#define QPK 1
#define FAG fence_async_g
enum { M_XN=0,M_Y,M_H,M_K,M_V,M_GATE,M_WQ,M_WK,M_WV,M_W1,M_W2,M_KM,M_U1,M_U2,M_U5,M_U10,M_NUM,M_OUT };
struct WParams { CUtensorMap m[M_NUM]; const bf16* x; const bf16* b1; const bf16* b2; bf16* out; const bf16* wq; const bf16* wo; };
#define WPF 99
enum { T_RED=0,T_OP=1,T_QA=2,T_M2=3,T_M1=4,T_KV=5,T_END=6 };
#define KVUP 824
#define TRIG 10
#define SOV 1
#define LATE 14
#define E15 3
#define OPE 15
#define Q15 3
#define HB 1
#define EARLY 2
constexpr int NRB=16;
constexpr int STG=45056, NST=4, SLOT=24576, BOXS=8192, BOXK=10240;
constexpr int W_SLOT=NST*STG;
constexpr int W_BAR=W_SLOT+2*SLOT;
constexpr int W_TOTAL=W_BAR+1024;
static_assert(W_TOTAL<=232448,"smem");
#define ST(i)
#define QT(i)
__device__ __forceinline__ void stsm4n(uint32_t a,uint32_t r0,uint32_t r1,uint32_t r2,uint32_t r3){ asm volatile("stmatrix.sync.aligned.m8n8.x4.shared.b16 [%0], {%1,%2,%3,%4};"::"r"(a),"r"(r0),"r"(r1),"r"(r2),"r"(r3)); }
#define WGUARD 2000000
__host__ __device__ constexpr int n_uns(){ int n=0; while(n<16&&nsp(n)==1) n++; return n; }
__host__ __device__ constexpr int n_op(){ int n=0; for(int r=0;r<NRB;r++) n+=4*nsp(r); return n; }
__host__ __device__ constexpr int n_red(){ return 0; }
__host__ __device__ constexpr int pu_st(int ns){ return ns==1?40:(ns==2?20:(ns==5?10:8)); }

__device__ __forceinline__ void wg_arrive(){ asm volatile("wgmma.fence.sync.aligned;":::"memory"); }
__device__ __forceinline__ void wg_commit(){ asm volatile("wgmma.commit_group.sync.aligned;":::"memory"); }
template<int N> __device__ __forceinline__ void wg_wait(){ asm volatile("wgmma.wait_group.sync.aligned %0;"::"n"(N):"memory"); }
__device__ __forceinline__ void mbar_wait(uint32_t a,uint32_t par){ int gd=0; while(!mbar_try(a,par)){ if(++gd>WGUARD){ g_err=20; break; } } }
__device__ __forceinline__ uint32_t ld_rlx(const uint32_t* p){ uint32_t v; asm volatile("ld.relaxed.gpu.global.u32 %0, [%1];":"=r"(v):"l"(p):"memory"); return v; }
__device__ __forceinline__ float4 ld_rlx4f(const float4* p){ float4 v; asm volatile("ld.relaxed.gpu.global.v4.f32 {%0,%1,%2,%3}, [%4];":"=f"(v.x),"=f"(v.y),"=f"(v.z),"=f"(v.w):"l"(p):"memory"); return v; }
__device__ __forceinline__ void red_rel(uint32_t* p){ asm volatile("red.release.gpu.global.add.u32 [%0], 1;"::"l"(p):"memory"); }
__device__ __forceinline__ void tma_st(const CUtensorMap* tm,uint32_t src,int c0,int c1){
  asm volatile("cp.async.bulk.tensor.2d.global.shared::cta.bulk_group [%0, {%2, %3}], [%1];"::"l"(tm),"r"(src),"r"(c0),"r"(c1):"memory"); }
__device__ __forceinline__ void bulk_commit(){ asm volatile("cp.async.bulk.commit_group;":::"memory"); }
__device__ __forceinline__ void bulk_wait_rd(){ asm volatile("cp.async.bulk.wait_group.read 0;":::"memory"); }
__device__ __forceinline__ void bulk_wait(){ asm volatile("cp.async.bulk.wait_group 0;":::"memory"); }
__device__ __forceinline__ void mbar_arrive_cl(uint32_t a){ asm volatile("mbarrier.arrive.shared::cluster.b64 _, [%0];"::"r"(a):"memory"); }
__device__ __forceinline__ void tma2dm(uint32_t dst,const CUtensorMap* tm,int c0,int c1,uint32_t mb){
  asm volatile("cp.async.bulk.tensor.2d.shared::cluster.global.mbarrier::complete_tx::bytes.multicast::cluster [%0], [%1, {%3, %4}], [%2], %5;"::"r"(dst),"l"(tm),"r"(mb),"r"(c0),"r"(c1),"h"((uint16_t)3):"memory"); }

template<int N,int CL,int XS> __device__ __forceinline__ void mainloop(float* acc,int nkb,uint32_t sb,int lane,uint32_t pos){
  const uint32_t eb=CL?mapa(sb+W_BAR+32,lane&1):sb+W_BAR+32;
  uint32_t pst=0;
  #pragma unroll
  for(int i=0;i<N/2;i++){ acc[i]=0.f; acc[96+i]=0.f; }
  #pragma unroll 1
  for(int kb=0;kb<nkb;kb++,pos++){
    const uint32_t st=pos&3;
    mbar_wait(sb+W_BAR+st*8,(pos>>2)&1);
    if(!XS&&kb==nkb-1&&(threadIdx.x&127)==0) mbar_arrive(sb+W_BAR+144);
    const uint32_t a=sb+st*STG;
    const uint32_t da=((a>>4)&0x3fff)|(1u<<16);
    const uint32_t db=da+1024+(511u<<16);
    wg_arrive();
    #pragma unroll
    for(int k=0;k<4;k++){ wgmma<N>(acc,da+2*k,db+128*k,kb|k); wgmma<N>(acc+96,da+512+2*k,db+128*k,kb|k); }
    wg_commit();
    if(kb>0){ wg_wait<1>(); if(CL){ if(lane<2) mbar_arrive_cl(eb+pst*8); } else if(lane==0) mbar_arrive(eb+pst*8); }
    pst=st;
  }
  if(XS){
    #pragma unroll
    for(int x=0;x<XS;x++) mbar_wait(sb+W_BAR+((pos+x)&3)*8,((pos+x)>>2)&1);
    if((threadIdx.x&127)==0) mbar_arrive(sb+W_BAR+144);
  }
  wg_wait<0>();
  if(CL){ if(lane<2) mbar_arrive_cl(eb+pst*8); } else if(lane==0) mbar_arrive(eb+pst*8);
}
__device__ __forceinline__ uint32_t act2(uint32_t u,uint32_t bb,float c1,float c3){
  uint32_t s; asm("add.rn.bf16x2 %0, %1, %2;":"=r"(s):"r"(u),"r"(bb));
  float r[2]={__uint_as_float(s<<16), __uint_as_float(s&0xffff0000u)};
  #pragma unroll
  for(int i=0;i<2;i++){
    const float z=r[i]*fmaf(r[i]*r[i],c3,c1);
    r[i]=r[i]*rcp(1.f+ex2(z));
  }
  return pack_bf16(r[0],r[1]);
}
__device__ __forceinline__ uint32_t fin1(uint32_t s,uint32_t x,uint32_t gq){
  const uint32_t p=pack_bf16(__uint_as_float(s<<16)*__uint_as_float(gq<<16),__uint_as_float(s&0xffff0000u)*__uint_as_float(gq&0xffff0000u));
  return pack_bf16(__uint_as_float(x<<16)+__uint_as_float(p<<16),__uint_as_float(x&0xffff0000u)+__uint_as_float(p&0xffff0000u));
}
template<int NT> __device__ __forceinline__ void stage_pk(const uint32_t* p,uint32_t ra,int lane){
  const int sw=lane&7, hi=lane>>4;
  #pragma unroll
  for(int T=0;T<NT;T++) stsm4n(ra+(T>>2)*BOXS+((((2*T+hi)&7)^sw)<<4),p[4*T],p[4*T+1],p[4*T+2],p[4*T+3]);
}
__device__ __noinline__ void post_pass(uint32_t sl,int nbox,uint32_t ba,float c1,float c3){
  const int lane=threadIdx.x&31, r=lane>>3, c=lane&7;
  __syncwarp();
  #pragma unroll 1
  for(int j=0;j<nbox;j++){
    uint4 u[4]; uint32_t a[4];
    #pragma unroll
    for(int i=0;i<4;i++){ const int rr=4*i+r; a[i]=sl+j*BOXS+rr*128+((c^(rr&7))<<4); u[i]=lds4(a[i]); }
    const uint4 bb=lds4(ba+j*128+c*16);
    #pragma unroll
    for(int i=0;i<4;i++){
      uint4& v=u[i];
      v.x=act2(v.x,bb.x,c1,c3); v.y=act2(v.y,bb.y,c1,c3); v.z=act2(v.z,bb.z,c1,c3); v.w=act2(v.w,bb.w,c1,c3);
      sts4(a[i],v);
    }
  }
}
__device__ __forceinline__ void wg32_pu(float* d,uint32_t da,uint32_t db,int sc){
  asm volatile("{\n.reg .pred p;\n.reg .b64 xa, xb;\nmov.b64 xa, {%16, 32};\nmov.b64 xb, {%17, 8};\nsetp.ne.b32 p, %18, 0;\nwgmma.mma_async.sync.aligned.m64n32k16.f32.bf16.bf16 {%0,%1,%2,%3,%4,%5,%6,%7,%8,%9,%10,%11,%12,%13,%14,%15}, xa, xb, p, 1, 1, 0, 0;\n}"
   :"+f"(d[0]),"+f"(d[1]),"+f"(d[2]),"+f"(d[3]),"+f"(d[4]),"+f"(d[5]),"+f"(d[6]),"+f"(d[7]),"+f"(d[8]),"+f"(d[9]),"+f"(d[10]),"+f"(d[11]),"+f"(d[12]),"+f"(d[13]),"+f"(d[14]),"+f"(d[15])
   :"r"(da),"r"(db),"r"(sc));
}
__device__ __forceinline__ void stsm4t(uint32_t a,uint32_t r0,uint32_t r1,uint32_t r2,uint32_t r3){ asm volatile("stmatrix.sync.aligned.m8n8.x4.trans.shared.b16 [%0], {%1,%2,%3,%4};"::"r"(a),"r"(r0),"r"(r1),"r"(r2),"r"(r3):"memory"); }
template<int NS> __device__ __forceinline__ void pu_item(const WParams& P,int rbk,int a,uint32_t pos,uint32_t sb,int tid,uint32_t& e0,int& sq){
  constexpr int MT=10/NS, NKB=pu_st(NS), BPS=40/NKB, H0=(MT+1)/2;
  const int lane=tid&31, wg=tid>>7, wq=(tid>>5)&3;
  const int seg=rbk*4+a/NS, part=a%NS;
  const uint32_t go=(uint32_t)((seg*32+wq*8+(lane>>3))*D+part*MT*64+(lane&7)*8);
  uint4 xx[MT][2], gg[MT][2];
  auto ldx=[&](int m){
    #pragma unroll
    for(int j=m*H0;j<m*H0+H0&&j<MT;j++)
      #pragma unroll
      for(int i=0;i<2;i++){ const uint32_t o=go+i*4*D+j*64; xx[j][i]=ldg_rlx4((const uint32_t*)(P.x+o)); gg[j][i]=ldg_rlx4((const uint32_t*)(g_gate+o)); }
  };
  if(NS>1){ ldx(0); ldx(1); }
  float acc[MT][16];
  #pragma unroll
  for(int i=0;i<MT*16;i++) acc[i>>4][i&15]=0.f;
  uint32_t pst=0;
  #pragma unroll 1
  for(int kb=0;kb<NKB;kb++,pos++){
    const uint32_t st=pos&3;
    mbar_wait(sb+W_BAR+st*8,(pos>>2)&1);
    if(kb==NKB-1&&(tid&127)==0) mbar_arrive(sb+W_BAR+144);
    const uint32_t sa=((sb+st*STG)>>4)&0x3fff, da=sa|(8u<<16), db=(sa+BPS*MT*256)|(32u<<16);
    wg_arrive();
    #pragma unroll
    for(int j=0;j<BPS;j++)
      #pragma unroll
      for(int k=0;k<2;k++)
        #pragma unroll
        for(int m=0;m<MT;m++) wg32_pu(acc[m],da+(j*MT+m)*256+k*16,db+j*128+k*64,kb|j|k);
    wg_commit();
    if(kb>0){ wg_wait<1>(); if(lane==0) mbar_arrive(sb+W_BAR+32+pst*8); }
    pst=st;
  }
  wg_wait<0>();
  if(lane==0) mbar_arrive(sb+W_BAR+32+pst*8);
  const uint32_t wa=sb+W_SLOT+((lane>>4)*8+(lane&7))*128+(((2*wq+((lane>>3)&1))^(lane&7))<<4);
  const uint32_t rd=sb+W_SLOT+(wq*8+(lane>>3))*128+(((lane&7)^(lane>>3))<<4);
  #pragma unroll
  for(int m=0;m<2;m++){
    mbar_wait(sb+W_BAR+96+wg*16+m*8,e0);
    if(m*H0<MT){
      #pragma unroll
      for(int j=0;j<H0&&m*H0+j<MT;j++){ const float* q=acc[m*H0+j<MT?m*H0+j:0];
        #pragma unroll
        for(int i=0;i<2;i++) stsm4t(wa+m*SLOT+j*4096+i*2048,pack_bf16(q[8*i],q[8*i+1]),pack_bf16(q[8*i+2],q[8*i+3]),pack_bf16(q[8*i+4],q[8*i+5]),pack_bf16(q[8*i+6],q[8*i+7])); }
      if(NS==1) ldx(m);
      bar_sync(8+wg,128);
      #pragma unroll
      for(int j=0;j<H0&&m*H0+j<MT;j++)
        #pragma unroll
        for(int i=0;i<2;i++){
          const uint4 u=lds4((rd^(i*64))+m*SLOT+j*4096+i*512), x=xx[m*H0+j<MT?m*H0+j:0][i], g=gg[m*H0+j<MT?m*H0+j:0][i];
          *(uint4*)(P.out+go+i*4*D+(m*H0+j)*64)=make_uint4(fin1(u.x,x.x,g.x),fin1(u.y,x.y,g.y),fin1(u.z,x.z,g.z),fin1(u.w,x.w,g.w));
        }
    }
    bar_arrive(sq,160); sq^=1;
  }
  e0^=1;
}
template<int N,int MODE> __device__ __forceinline__ void gemm_item(const WParams& P,int type,int rbk,int a,uint32_t pos,uint32_t sb,int tid,uint32_t ra,uint32_t& e0,uint32_t& eb,int& sq){
  const int lane=tid&31, wg=tid>>7;
  const uint32_t E0=sb+W_BAR+96+wg*16;
  float acc[192];
  mainloop<N,MODE==0,0>(acc,(MODE&&type==T_M2)?24:10,sb,lane,pos);
  uint32_t p[2][N/4];
  #pragma unroll
  for(int m=0;m<2;m++)
    #pragma unroll
    for(int i=0;i<N/4;i++) p[m][i]=pack_bf16(acc[96*m+2*i],acc[96*m+2*i+1]);
  const float c1=type==T_M1?-2.302208198144325f:-1.4426950408889634f, c3=type==T_M1?-0.10294323958f:0.f;
  const int wq=(tid>>5)&3;
  if(MODE&&type!=T_KV){ mbar_wait(sb+W_BAR+224+wg*8,eb); eb^=1; }
  #pragma unroll
  for(int m=0;m<2;m++){
    mbar_wait(E0+m*8,e0);
    stage_pk<N/16>(p[m],ra+m*SLOT,lane);
    if(MODE&&type!=T_KV) post_pass(sb+W_SLOT+m*SLOT+wq*2048,N/64,sb+W_BAR+256+wg*384,c1,c3);
    fence_async();
    bar_arrive(sq,160); sq^=1;
  }
  e0^=1;
}
__device__ __forceinline__ int n_it(int c,int r){ return c==T_OP?4*nsp(r):(c==T_QA?32:(c==T_M2?4:(r?0:(c==T_M1?128:(c==T_KV?1024-KVUP:0))))); }
__device__ __forceinline__ void flag_wait(int rbk,int a){
  const uint32_t need=4*rbk+4; const uint32_t* f=g_flag+a*96; int gd=0;
  while(ld_acq(f)<need||ld_acq(f+32)<need||ld_acq(f+64)<need){ __nanosleep(40); if(++gd>WGUARD){ g_err=22; break; } }
  FAG();
}
__device__ __forceinline__ void cnt_wait(int c,uint32_t thr){
  int gd=0;
  while(ld_acq(g_cnt+c)<thr){ __nanosleep(40); if(++gd>WGUARD){ g_err=23; break; } }
}
template<int MODE>
__global__ void __launch_bounds__(384,1) k_work(const __grid_constant__ WParams P){
  extern __shared__ __align__(1024) uint8_t sm[];
  const uint32_t sb=(uint32_t)__cvta_generic_to_shared(sm);
  const int tid=threadIdx.x, warp=__shfl_sync(~0u,tid>>5,0), lane=tid&31;
  const uint32_t FULL=sb+W_BAR, EMPTY=sb+W_BAR+32, IFULL=sb+W_BAR+64, IEMPTY=sb+W_BAR+80, EF=sb+W_BAR+96, REQ=sb+W_BAR+128, TOK=sb+W_BAR+136;
  volatile int* idesc=(volatile int*)(sm+W_BAR+160);
  if(tid==352) ST(0);
  if(tid==0){
    for(int i=0;i<NST;i++){ mbar_init(FULL+i*8,1); mbar_init(EMPTY+i*8,MODE?4:8); mbar_init(EF+i*8,1); }
    for(int i=0;i<2;i++){ mbar_init(IFULL+i*8,1); mbar_init(IEMPTY+i*8,6); mbar_init(sb+W_BAR+224+i*8,1); }
    mbar_init(REQ,1); mbar_init(TOK,1); mbar_init(sb+W_BAR+144,1);
    asm volatile("fence.mbarrier_init.release.cluster;":::"memory");
  }
  __syncthreads();
  if(MODE==0){ cluster_sync(); asm volatile("griddepcontrol.wait;":::"memory"); asm volatile("griddepcontrol.launch_dependents;"); }
  if(warp>=8){
    asm volatile("setmaxnreg.dec.sync.aligned.u32 40;");
    if(warp==11){
      uint32_t it=0, pos=0;
      int guard=0; bool fin=false;
      const int cl=lane>>2, cj=lane&3;
      int sidx=blockIdx.x; int nit=0;
      if(lane==0) ST(1);
      while(true){
        int type=T_END, rbk=0, a=0, erl=0;
        if(!fin){
          if(it) mbar_wait(REQ,(it&1)^1);
          if(MODE==0){
            if(sidx<KVUP){ type=T_KV; a=sidx; sidx+=gridDim.x; }
            if(it==WPF){
              const int ci=blockIdx.x*32+lane;
              if(ci<3840) asm volatile("cp.async.bulk.prefetch.L2.global [%0], 4096;"::"l"((const char*)(ci<1920?P.wq:P.wo)+(size_t)(ci<1920?ci:ci-1920)*4096):"memory");
            }
          }
          else {
            while(true){
              const uint4 nx=ldg_rlx4(g_cnt+C_NEXT+cl*32+cj*4);
              int cand=(int)nx.x<n_it(cl,4*cj)?4*cj*4096+nx.x:((int)nx.y<n_it(cl,4*cj+1)?(4*cj+1)*4096+nx.y:((int)nx.z<n_it(cl,4*cj+2)?(4*cj+2)*4096+nx.z:((int)nx.w<n_it(cl,4*cj+3)?(4*cj+3)*4096+nx.w:65536)));
              cand=min(cand,__shfl_xor_sync(~0u,cand,1)); cand=min(cand,__shfl_xor_sync(~0u,cand,2));
              const int cr=cand>>12, ca=cand&4095, qr=__shfl_sync(~0u,cr,4*T_QA);
              const bool has=cr<NRB;
              if(lane==0&&nit==0) ST(5);
              const uint32_t* fp=nullptr; uint32_t thr=0, sl1=0; bool only1=false, no1=cl>=T_M2;
              if(has&&cl<=T_M2){
                if(cl==T_QA){ if(cj<3){ fp=g_flag+ca*96+cj*32; thr=4*cr+4; sl1=cr==NRB-1?E15:EARLY; } else { fp=g_cnt+C_KV+min(cr+1,NRB-1); thr=64; only1=true; } }
                else if(cj==0){ fp=g_cnt+(cl==T_OP?C_QA:C_M1)+cr; thr=cl==T_OP?32:8; sl1=thr; }
                else if(cj==1){ if(cl==T_OP){ fp=g_cnt+C_M2+cr; thr=4; } if(cr<OPE||qr<=cr) no1=true; }
              }
              __syncwarp();
              if(lane==0&&nit==0) ST(2);
              uint32_t v=0; if(fp) v=ld_acq(fp);
              __syncwarp();
              if(lane==0&&nit==0) ST(3+(v&0));
              nit++;
              uint32_t b2=__ballot_sync(~0u,has&&(v>=thr||only1)), b1=__ballot_sync(~0u,has&&!no1&&v+sl1>=thr);
              b2&=b2>>1; b2&=b2>>2; b1&=b1>>1; b1&=b1>>2;
              b2&=0x111111u; b1&=0x111u;
              if(!__ballot_sync(~0u,has)) break;
              if(b2|b1){
                const int rs=(int)__shfl_sync(~0u,v,4*T_QA);
                const uint32_t bu=__ballot_sync(~0u,cl<=T_QA||qr>=NRB||(cl==T_KV?2*((ca+KVUP)>>7)<=(rs>>2)+KLEAD:(cl==T_M1?ca>>3:cr)<=qr+MLEAD));
                int got=-1;
                while(got<0&&(b2|b1)){
                  uint32_t bb=(b2&bu)?(b2&bu):(b1?b1:b2);
                  if(Q15&&(((b1|b2)>>(4*T_QA))&1)&&qr>=NRB-Q15) bb=1u<<(4*T_QA);
                  #define RD(c) ((bb>>(4*(c)))&1)
                  const int w=RD(T_KV)?T_KV:(RD(T_M2)?T_M2:(RD(T_M1)?T_M1:(RD(T_OP)?T_OP:T_QA)));
                  if(lane==4*w){ const int tk=(int)atomicAdd(g_cnt+C_NEXT+cl*32+cr,1u); if(tk<n_it(cl,cr)) got=cr*4096+tk+(cl==T_KV?KVUP:0)+(tk!=ca?65536:0); }
                  got=__shfl_sync(~0u,got,4*w);
                  if(got>=0){ type=w; rbk=(got>>12)&15; a=got&4095; erl=!((b2>>(4*w))&1)||(w==T_QA&&got>=65536); }
                  b2&=~(1u<<(4*w)); b1&=~(1u<<(4*w));
                }
                if(got>=0) break;
              } else {
                __nanosleep(100);
                if(++guard>WGUARD){ g_err=21; break; }
              }
            }
          }
        }
        __syncwarp();
        if(lane==0){
          const uint32_t sl=it&1;
          int idx=0;
          if(type==T_KV){ rbk=2*(a>>7)+(a&1); a=(a>>1)&63; }
          if(type==T_M1){ rbk=a>>3; a&=7; }
          mbar_wait(IEMPTY+sl*8,((it>>1)&1)^1);
          idesc[sl*8]=type; idesc[sl*8+1]=rbk; idesc[sl*8+2]=a; idesc[sl*8+3]=pos; idesc[sl*8+4]=idx; idesc[sl*8+5]=erl;
          mbar_arrive(IFULL+sl*8);
          pos+=type==T_M2?24:(type==T_OP?pu_st(nsp(rbk)):(type==T_QA?12:10));
        }
        __syncwarp();
        it++;
        if(type==T_END){ if(fin) break; fin=true; }
      }
    } else if(warp==8){
      if(lane==0){
        uint32_t st=0, ph=1;
        for(uint32_t it=0;;it++){
          const uint32_t sl=it&1;
          mbar_wait(IFULL+sl*8,(it>>1)&1);
          const int type=idesc[sl*8], rbk=idesc[sl*8+1], a=idesc[sl*8+2], erl=idesc[sl*8+5];
          mbar_arrive(IEMPTY+sl*8);
          if(type==T_END) break;
          if(MODE&&type==T_OP){
            const int ns=nsp(rbk), nkb=pu_st(ns), bps=40/nkb, ub=40960/ns, seg=rbk*4+a/ns, trig=rbk>=LATE?nkb-1:max(nkb-TRIG,0);
            const uint8_t* pp=g_p+seg*81920; const CUtensorMap* um=&P.m[ns==1?M_U1:(ns==2?M_U2:(ns==5?M_U5:M_U10))]; const int c1=(a%ns)*(20/ns);
            if(erl) cnt_wait(C_QA+rbk,32);
            FAG();
            for(int kb=0;kb<nkb;kb++){
              mbar_wait(EMPTY+st*8,ph);
              const uint32_t d=sb+st*STG, fb=FULL+st*8;
              mbar_expect(fb,bps*(ub+2048));
              asm volatile("cp.async.bulk.tensor.3d.shared::cluster.global.mbarrier::complete_tx::bytes [%0], [%1, {0, %3, %4}], [%2];"::"r"(d),"l"(um),"r"(fb),"r"(c1),"r"(seg*40+kb*bps):"memory");
              bulk_g2s(d+bps*ub,pp,bps*2048,fb); pp+=bps*2048;
              if(kb==trig) mbar_arrive(REQ);
              if(++st==NST){ st=0; ph^=1; }
            }
            continue;
          }
          int ma=M_XN,mb,col0=a*192,k0=0,nkb=10,nbox=3; const int row0=rbk*128;
          if(MODE==0||type==T_KV){ mb=a<32?M_WK:M_WV; col0=(a&31)*192; }
          else if(type==T_M1){ ma=M_Y; mb=M_W1; }
          else if(type==T_QA){ mb=M_WQ; }
          else {
            const int nt=a&3; col0=nt<2?nt*192:128+nt*128; nbox=nt<2?3:2;
            ma=M_H; mb=M_W2; nkb=24;
          }
          if(MODE) FAG();
          const CUtensorMap* A=&P.m[ma]; const CUtensorMap* B=&P.m[mb];
          const int trig=(MODE&&type<=T_QA&&rbk>=LATE)?nkb-1:max(nkb-(type==T_QA?TRIG-2:TRIG),0);
          for(int kb=0;kb<nkb;kb++){
            mbar_wait(EMPTY+st*8,ph);
            const uint32_t d=sb+st*STG, fb=FULL+st*8;
            mbar_expect(fb,16384+nbox*8192);
            const int kk=k0+kb*64;
            tma2d(d,A,kk,row0,fb); tma2d(d+8192,A,kk,row0+64,fb);
            if(MODE==0){
              const int r=rbk&1, j=2*r;
              tma2dm(d+16384+j*8192,B,col0+j*64,kk,fb);
              if((kb&1)==r) tma2dm(d+24576,B,col0+64,kk,fb);
            }
            else for(int j=0;j<nbox;j++) tma2d(d+16384+j*8192,B,col0+j*64,kk,fb);
            if(kb==trig) mbar_arrive(REQ);
            if(++st==NST){ st=0; ph^=1; }
          }
          if(MODE&&type==T_QA){
            for(int m=0;m<2;m++){
              mbar_wait(EMPTY+st*8,ph);
              const uint32_t d=sb+st*STG, fb=FULL+st*8;
              mbar_expect(fb,3*BOXK);
              for(int j=0;j<3;j++) tma2d(d+j*BOXK,&P.m[M_K],col0+j*64,row0+m*64,fb);
              if(erl&&!m) flag_wait(rbk,a);
              for(int j=0;j<3;j++) tma2d(d+j*BOXK+8192,&P.m[M_KM],col0+j*64,rbk*32+m*16,fb);
              if(++st==NST){ st=0; ph^=1; }
            }
          }
        }
      }
      __syncwarp();
    } else if(warp<11){
      const int wg=warp-9;
      const uint32_t S0=sb+W_SLOT, E0=EF+wg*16; int sq=4+2*wg;
      for(uint32_t it=wg;;it+=2){
        mbar_wait(IFULL+wg*8,(it>>1)&1);
        const int type=idesc[wg*8], rbk=idesc[wg*8+1], a=idesc[wg*8+2];
        __syncwarp();
        if(lane==0) mbar_arrive(IEMPTY+wg*8);
        if(type==T_END) break;
        if(MODE&&type==T_QA&&lane==0){ mbar_arrive(E0); mbar_arrive(E0+8); }
        const int row0=rbk*128;
        int map=-1,col0=a*192,nbox=3,cnt=-1;
        if(MODE==0||type==T_KV){ map=a<32?M_K:M_V; col0=(a&31)*192; cnt=C_KV+rbk; }
        else if(type==T_M1){ map=M_H; cnt=C_M1+rbk; }
        else if(type==T_M2){ const int nt=a&3; col0=nt<2?nt*192:128+nt*128; nbox=nt<2?3:2; map=M_GATE; cnt=C_M2+rbk; }
        else if(type==T_OP) map=M_OUT;
        if(MODE&&(type==T_M1||type==T_M2)&&lane==0){ const uint32_t bb=sb+W_BAR+224+wg*8; mbar_expect(bb,nbox*128); bulk_g2s(sb+W_BAR+256+wg*384,(type==T_M1?P.b1:P.b2)+col0,nbox*128,bb); }
        if(it&&lane==0) mbar_wait(TOK,(it&1)^1);
        if(MODE&&map<0){
          if(lane==0) mbar_arrive(TOK);
          { __syncwarp(); bar_sync(sq,160); sq^=1; } if(lane==0) red_rel(g_cnt+C_QA+rbk);
        } else if(MODE&&map==M_OUT){
          if(lane==0){ mbar_arrive(E0); mbar_arrive(E0+8); }
          { __syncwarp(); bar_sync(sq,160); sq^=1; }
          { __syncwarp(); bar_sync(sq,160); sq^=1; }
          if(lane==0) mbar_arrive(TOK);
        } else {
          if(lane==0){ mbar_arrive(E0); mbar_arrive(E0+8); }
          for(int m=0;m<2;m++){
            { __syncwarp(); bar_sync(sq,160); sq^=1; }
            if(lane==0){
              for(int j=0;j<nbox;j++) tma_st(&P.m[map],S0+m*SLOT+j*BOXS,col0+j*64,row0+m*64);
              bulk_commit();
            }
          }
          if(lane==0){
            bulk_wait_rd(); mbar_arrive(TOK);
            bulk_wait(); FAG(); red_rel(g_cnt+cnt);
          }
        }
        __syncwarp();
      }
      if(lane==0) bulk_wait();
    }
  } else {
    asm volatile("setmaxnreg.inc.sync.aligned.u32 232;");
    const int wg=warp>>2, wq=warp&3, g=lane>>2, t=lane&3;
    const uint32_t E0=EF+wg*16;
    const uint32_t ra=sb+W_SLOT+(16*wq+(lane&7)+((lane>>3)&1)*8)*128;
    uint32_t e0=0, eb=0; int sq=4+2*wg;
    #pragma unroll 1
    for(uint32_t it=0;;it++){
      mbar_wait(IFULL+wg*8,it&1);
      const int type=idesc[wg*8], rbk=idesc[wg*8+1], a=idesc[wg*8+2]; const uint32_t pos=idesc[wg*8+3];
      __syncwarp();
      if(lane==0) mbar_arrive(IEMPTY+wg*8);
      if(type==T_END) break;
      mbar_wait(sb+W_BAR+144,wg^1);
      if(MODE&&type==T_OP){
        const int ns=nsp(rbk);
        if(ns_used(1)&&ns==1) pu_item<1>(P,rbk,a,pos,sb,tid,e0,sq);
        if(ns_used(2)&&ns==2) pu_item<2>(P,rbk,a,pos,sb,tid,e0,sq);
        if(ns_used(5)&&ns==5) pu_item<5>(P,rbk,a,pos,sb,tid,e0,sq);
        if(ns_used(10)&&ns==10) pu_item<10>(P,rbk,a,pos,sb,tid,e0,sq);
      } else {
        if(MODE==0||type!=T_QA){
          if(MODE==0||type>=T_M1||(a&3)<2) gemm_item<192,MODE>(P,type,rbk,a,pos,sb,tid,ra,e0,eb,sq); else gemm_item<128,MODE>(P,type,rbk,a,pos,sb,tid,ra,e0,eb,sq);
        } else {
          float acc[192];
          QT(0);
          mainloop<192,0,2>(acc,10,sb,lane,pos);
          QT(1);
          const int sgl=wq>>1, rh=wq&1;
          {
            uint32_t q[96];
            float s[2][40];
            QT(2);
            #pragma unroll
            for(int m=0;m<2;m++){
              const uint32_t ks=(pos+10+m)&3;
              const uint32_t dk=((sb+ks*STG)>>4)|(1u<<16);
              #pragma unroll
              for(int i=QPK?0:48*m;i<(QPK?96-96*m:48*m+48);i++) q[i]=pack_bf16(acc[2*i],acc[2*i+1]);
              mbar_wait(FULL+ks*8,((pos+10+m)>>2)&1);
              #pragma unroll
              for(int i=0;i<40;i++) s[m][i]=0.f;
              wg_arrive();
              #pragma unroll
              for(int T=0;T<12;T++) wgmma_rs<80>(s[m],q+48*m+4*T,dk+(T>>2)*(BOXK/16)+(T&3)*2,T);
              wg_commit();
              wg_wait<0>();
              if(lane==0) mbar_arrive(EMPTY+ks*8);
              QT(3+m);
            }
            const float NEG=rb(-1e9f);
            #pragma unroll
            for(int m=0;m<2;m++){
              float sc[5][4];
              float mx[2]={-3.4e38f,-3.4e38f};
              #pragma unroll
              for(int n=0;n<5;n++)
                #pragma unroll
                for(int i=0;i<4;i+=2){
                  const float u0=n?(sgl?s[m][12+4*n+i]:s[m][4*n-4+i]):(sgl?s[m][36+i]:s[m][32+i]);
                  const float u1=n?(sgl?s[m][13+4*n+i]:s[m][4*n-3+i]):(sgl?s[m][37+i]:s[m][33+i]);
                  const uint32_t r=pack_bf16(u0,u1);
                  const uint32_t w=pack_bf16(__uint_as_float(r<<16)*0.07216878364870322f,__uint_as_float(r&0xffff0000u)*0.07216878364870322f);
                  float v0=__uint_as_float(w<<16), v1=__uint_as_float(w&0xffff0000u);
                  if(n>0){ const int key=8*(n-1)+2*t, row=16*rh+g+4*i; if(key>row) v0=NEG; if(key+1>row) v1=NEG; }
                  sc[n][i]=v0; sc[n][i+1]=v1; mx[i>>1]=fmaxf(mx[i>>1],fmaxf(v0,v1));
                }
              float sum[2]={0.f,0.f};
              #pragma unroll
              for(int r=0;r<2;r++){ mx[r]=fmaxf(mx[r],__shfl_xor_sync(~0u,mx[r],1)); mx[r]=fmaxf(mx[r],__shfl_xor_sync(~0u,mx[r],2)); }
              #pragma unroll
              for(int n=0;n<5;n++)
                #pragma unroll
                for(int i=0;i<4;i++){ const float e=ex2((sc[n][i]-mx[i>>1])*1.4426950408889634f); sc[n][i]=e; sum[i>>1]+=e; }
              #pragma unroll
              for(int r=0;r<2;r++){ sum[r]+=__shfl_xor_sync(~0u,sum[r],1); sum[r]+=__shfl_xor_sync(~0u,sum[r],2); sum[r]=rcp(sum[r]); }
              uint8_t* pd=g_p+(uint32_t)((rbk*4+m*2+sgl)*81920+rh*256+lane*4);
              #pragma unroll
              for(int n=0;n<5;n++){
                uint8_t* q=pd+(n?a*2048+(n-1)*512:(32+(a>>2))*2048+(a&3)*512);
                stg1(q,pack_bf16(sc[n][0]*sum[0],sc[n][1]*sum[0])); stg1(q+128,pack_bf16(sc[n][2]*sum[1],sc[n][3]*sum[1]));
              }
            }
          }
          QT(5);
          mbar_wait(E0,e0); mbar_wait(E0+8,e0);
          bar_arrive(sq,160); sq^=1;
          e0^=1;
        }
      }
    }
  }
  if(MODE==0) cluster_sync();
}
typedef CUresult (*EncFn)(CUtensorMap*,CUtensorMapDataType,cuuint32_t,void*,const cuuint64_t*,const cuuint64_t*,const cuuint32_t*,const cuuint32_t*,CUtensorMapInterleave,CUtensorMapSwizzle,CUtensorMapL2promotion,CUtensorMapFloatOOBfill);
static EncFn enc(){
  static EncFn fn=nullptr;
  if(!fn){ void* p=nullptr; cudaDriverEntryPointQueryResult qr; cudaGetDriverEntryPoint("cuTensorMapEncodeTiled",&p,cudaEnableDefault,&qr); fn=(EncFn)p; }
  return fn;
}
static CUtensorMap mku(const void* base,uint32_t b1,uint32_t b2){
  CUtensorMap m; cuuint64_t gd[3]={256,20,NSEG*40}; cuuint64_t gs[2]={2048,40960}; cuuint32_t bd[3]={256,b1,b2}; cuuint32_t es[3]={1,1,1};
  enc()(&m,CU_TENSOR_MAP_DATA_TYPE_FLOAT64,3,(void*)base,gd,gs,bd,es,CU_TENSOR_MAP_INTERLEAVE_NONE,CU_TENSOR_MAP_SWIZZLE_NONE,CU_TENSOR_MAP_L2_PROMOTION_L2_128B,CU_TENSOR_MAP_FLOAT_OOB_FILL_NONE);
  return m;
}
static CUtensorMap mk2d(const void* base,uint64_t cols,uint64_t rows,uint32_t bc,uint32_t br){
  EncFn fn=enc();
  CUtensorMap m; cuuint64_t gd[2]={cols,rows}; cuuint64_t gs[1]={cols*2}; cuuint32_t bd[2]={bc,br}; cuuint32_t es[2]={1,1};
  fn(&m,CU_TENSOR_MAP_DATA_TYPE_BFLOAT16,2,(void*)base,gd,gs,bd,es,CU_TENSOR_MAP_INTERLEAVE_NONE,CU_TENSOR_MAP_SWIZZLE_128B,CU_TENSOR_MAP_L2_PROMOTION_L2_128B,CU_TENSOR_MAP_FLOAT_OOB_FILL_NONE);
  return m;
}
template<class T> static T* sym(T& s){ void* p; cudaGetSymbolAddress(&p,s); return (T*)p; }
}

int g_reconly=0; int g_kvgrid=132;
extern "C" void kernel_launch(void* const* d_in, const int* in_sizes, int n_in, void* d_out, int out_size) {
  using namespace rk;
  const bf16* x=(const bf16*)d_in[0]; const bf16* mem0=(const bf16*)d_in[1];
  const bf16* Wq=(const bf16*)d_in[2]; const bf16* Wk=(const bf16*)d_in[3]; const bf16* Wv=(const bf16*)d_in[4]; const bf16* Wo=(const bf16*)d_in[5];
  const bf16* w1=(const bf16*)d_in[8]; const bf16* b1=(const bf16*)d_in[9]; const bf16* w2=(const bf16*)d_in[10]; const bf16* b2=(const bf16*)d_in[11];
  cudaStream_t st=cudaStreamPerThread;
  cudaFuncSetAttribute(k_rec,cudaFuncAttributeMaxDynamicSharedMemorySize,SM_TOTAL);
  cudaFuncSetAttribute(k_work<0>,cudaFuncAttributeMaxDynamicSharedMemorySize,W_TOTAL);
  cudaFuncSetAttribute(k_work<1>,cudaFuncAttributeMaxDynamicSharedMemorySize,W_TOTAL);
  bf16* k=(bf16*)sym(g_k); bf16* v=(bf16*)sym(g_v);
  WParams P;
  P.m[M_XN]=mk2d(sym(g_xn),D,S,64,64); P.m[M_Y]=mk2d(sym(g_y),D,S,64,64); P.m[M_H]=mk2d(sym(g_h),F,S,64,64);
  P.m[M_K]=mk2d(k,HD,S,64,64); P.m[M_V]=mk2d(v,HD,S,64,64); P.m[M_GATE]=mk2d(sym(g_gate),D,S,64,64);
  P.m[M_WQ]=mk2d(Wq,HD,D,64,64); P.m[M_WK]=mk2d(Wk,HD,D,64,64); P.m[M_WV]=mk2d(Wv,HD,D,64,64);
  P.m[M_W1]=mk2d(w1,F,D,64,64); P.m[M_W2]=mk2d(w2,D,F,64,64);
  P.m[M_KM]=mk2d(sym(g_km),HD,NSEG*8,64,16);
  P.m[M_U1]=mku(sym(g_u),20,1); P.m[M_U2]=mku(sym(g_u),10,2); P.m[M_U5]=mku(sym(g_u),4,4); P.m[M_U10]=mku(sym(g_u),2,5);
  P.x=x; P.b1=b1; P.b2=b2; P.out=(bf16*)d_out; P.wq=Wq; P.wo=Wo;
  k_pre<<<S/8+1,256,0,st>>>(x,mem0);
  if(!(g_reconly&1)){
    cudaLaunchConfig_t cfg={}; cfg.gridDim=dim3(g_kvgrid); cfg.blockDim=dim3(384); cfg.dynamicSmemBytes=W_TOTAL; cfg.stream=st;
    cudaLaunchAttribute at[2]; at[0].id=cudaLaunchAttributeClusterDimension; at[0].val.clusterDim.x=2; at[0].val.clusterDim.y=1; at[0].val.clusterDim.z=1;
    at[1].id=cudaLaunchAttributeProgrammaticStreamSerialization; at[1].val.programmaticStreamSerializationAllowed=1; cfg.attrs=at; cfg.numAttrs=2;
    cudaLaunchKernelEx(&cfg,k_work<0>,P);
  }
  if(!(g_reconly&4)){
    cudaLaunchConfig_t cfg={}; cfg.gridDim=dim3(NCTA); cfg.blockDim=dim3(256); cfg.dynamicSmemBytes=SM_TOTAL; cfg.stream=st;
    cudaLaunchAttribute at[2]; at[0].id=cudaLaunchAttributeClusterDimension; at[0].val.clusterDim.x=3; at[0].val.clusterDim.y=1; at[0].val.clusterDim.z=1;
    at[1].id=cudaLaunchAttributeProgrammaticStreamSerialization; at[1].val.programmaticStreamSerializationAllowed=1; cfg.attrs=at; cfg.numAttrs=2;
    CUtensorMap tk=mk2d(k,HD,S,64,32), tv=mk2d(v,HD,S,64,32);
    cudaLaunchKernelEx(&cfg,k_rec,tk,tv,Wq,Wk,Wv,Wo,0u);
  }
  if(!(g_reconly&2)){
    cudaLaunchConfig_t cfg={}; cfg.gridDim=dim3(132); cfg.blockDim=dim3(384); cfg.dynamicSmemBytes=W_TOTAL; cfg.stream=st;
    cudaLaunchAttribute at[1]; at[0].id=cudaLaunchAttributeProgrammaticStreamSerialization; at[0].val.programmaticStreamSerializationAllowed=1; cfg.attrs=at; cfg.numAttrs=PDL;
    cudaLaunchKernelEx(&cfg,k_work<1>,P);
  }
}
```

```cpp
#include <cuda_runtime.h>
#include <cuda_bf16.h>
#include <stdint.h>
#include <cuda.h>

namespace rk {
typedef __nv_bfloat16 bf16;
constexpr int S=2048, D=640, H=32, DH=192, HD=6144, NSEG=64, F=1536;
constexpr uint32_t SENT=0xFFFFFFFFu;
#define GUARDN 400000
constexpr int GUARD=GUARDN;
constexpr int NCTA=96;

__device__ __align__(128) bf16 g_xn[S*D];
__device__ __align__(128) bf16 g_y[S*D];
__device__ __align__(128) bf16 g_h[S*F];
__device__ __align__(128) bf16 g_gate[S*D];
__device__ __align__(128) bf16 g_k[(size_t)S*HD];
__device__ __align__(128) bf16 g_v[(size_t)S*HD];
__device__ __align__(128) bf16 g_km[NSEG*8*HD];
__device__ __align__(128) uint32_t g_flag[NCTA*32];
__device__ __align__(1024) uint8_t g_u[(size_t)NSEG*40*40960];
__device__ __align__(1024) uint8_t g_p[(size_t)NSEG*40*2048];
#define NSTAB 0xAAA5522222222222ull
__host__ __device__ constexpr int nsp(int rb){ return (int)((NSTAB>>(4*rb))&15); }
__host__ __device__ constexpr bool ns_used(int n){ for(int r=0;r<16;r++) if(nsp(r)==n) return true; return false; }
constexpr int C_NEXT=0, C_KV=256, C_M1=272, C_M2=288, C_OP=304, C_QA=320, C_NUM=384;
__device__ __align__(128) uint32_t g_cnt[C_NUM];
#define PDL 1
__device__ __align__(1024) unsigned long long g_acc[NSEG*2560];
constexpr unsigned long long ACC_INIT=0ull-32ull*((0x5A000000ull<<32)+0xD0000000ull+1ull);
__device__ __align__(128) uint32_t g_nrm[NCTA*2+32];
__device__ int g_err;
__device__ unsigned long long g_gt[128*4];
#define GT(i) do{ if(threadIdx.x==0){ unsigned long long g0; asm volatile("mov.u64 %0, %%globaltimer;":"=l"(g0)); g_gt[blockIdx.x*4+(i)]=g0; } }while(0)

__device__ __forceinline__ float rb(float x){ return __bfloat162float(__float2bfloat16(x)); }
__device__ __forceinline__ uint32_t pack_bf16(float lo,float hi){ uint32_t r; asm("cvt.rn.bf16x2.f32 %0, %1, %2;":"=r"(r):"f"(hi),"f"(lo)); return r; }
__device__ __forceinline__ uint32_t movm(uint32_t a){ uint32_t d; asm volatile("movmatrix.sync.aligned.m8n8.trans.b16 %0, %1;":"=r"(d):"r"(a)); return d; }
__device__ __forceinline__ uint4 ldg_rlx4(const uint32_t* p){ uint4 v; asm volatile("ld.relaxed.gpu.global.v4.u32 {%0,%1,%2,%3}, [%4];":"=r"(v.x),"=r"(v.y),"=r"(v.z),"=r"(v.w):"l"(p):"memory"); return v; }
__device__ __forceinline__ void stg_rlx1(uint32_t* p,uint32_t a){ asm volatile("st.relaxed.gpu.global.u32 [%0], %1;"::"l"(p),"r"(a):"memory"); }
__device__ __forceinline__ void stg_rlx2(uint32_t* p,uint32_t a,uint32_t b){ asm volatile("st.relaxed.gpu.global.v2.u32 [%0], {%1,%2};"::"l"(p),"r"(a),"r"(b):"memory"); }
__device__ __forceinline__ void stg1(void* p,uint32_t a){ asm volatile("st.global.u32 [%0], %1;"::"l"(p),"r"(a):"memory"); }
__device__ __forceinline__ void stg4(void* p,uint32_t a,uint32_t b,uint32_t c,uint32_t d){ asm volatile("st.global.v4.u32 [%0], {%1,%2,%3,%4};"::"l"(p),"r"(a),"r"(b),"r"(c),"r"(d):"memory"); }
__device__ __forceinline__ void bar_sync(int id,int n){ asm volatile("bar.sync %0, %1;"::"r"(id),"r"(n):"memory"); }
__device__ __forceinline__ void bar_arrive(int id,int n){ asm volatile("bar.arrive %0, %1;"::"r"(id),"r"(n):"memory"); }
__device__ __forceinline__ void mma16816(float* d,const uint32_t* a,uint32_t b0,uint32_t b1){
  asm volatile("mma.sync.aligned.m16n8k16.row.col.f32.bf16.bf16.f32 {%0,%1,%2,%3},{%4,%5,%6,%7},{%8,%9},{%0,%1,%2,%3};"
   :"+f"(d[0]),"+f"(d[1]),"+f"(d[2]),"+f"(d[3]):"r"(a[0]),"r"(a[1]),"r"(a[2]),"r"(a[3]),"r"(b0),"r"(b1));
}
__device__ __forceinline__ void mma1688(float* d,uint32_t a0,uint32_t a1,uint32_t b0){
  asm volatile("mma.sync.aligned.m16n8k8.row.col.f32.bf16.bf16.f32 {%0,%1,%2,%3},{%4,%5},{%6},{%0,%1,%2,%3};"
   :"+f"(d[0]),"+f"(d[1]),"+f"(d[2]),"+f"(d[3]):"r"(a0),"r"(a1),"r"(b0));
}
__device__ __forceinline__ void ldsm4t(uint32_t* r,uint32_t addr){ asm volatile("ldmatrix.sync.aligned.m8n8.x4.trans.shared.b16 {%0,%1,%2,%3}, [%4];":"=r"(r[0]),"=r"(r[1]),"=r"(r[2]),"=r"(r[3]):"r"(addr):"memory"); }
__device__ __forceinline__ void ldsm4(uint32_t* r,uint32_t addr){ asm volatile("ldmatrix.sync.aligned.m8n8.x4.shared.b16 {%0,%1,%2,%3}, [%4];":"=r"(r[0]),"=r"(r[1]),"=r"(r[2]),"=r"(r[3]):"r"(addr):"memory"); }
__device__ __forceinline__ void stsm4(uint32_t a,uint32_t r0,uint32_t r1,uint32_t r2,uint32_t r3){ asm volatile("stmatrix.sync.aligned.m8n8.x4.shared.b16 [%0], {%1,%2,%3,%4};"::"r"(a),"r"(r0),"r"(r1),"r"(r2),"r"(r3):"memory"); }
__device__ __forceinline__ void stsm2(uint32_t a,uint32_t r0,uint32_t r1){ asm volatile("stmatrix.sync.aligned.m8n8.x2.shared.b16 [%0], {%1,%2};"::"r"(a),"r"(r0),"r"(r1):"memory"); }
__device__ __forceinline__ void cp16(uint32_t dst,const void* src){ asm volatile("cp.async.cg.shared.global [%0], [%1], 16;"::"r"(dst),"l"(src):"memory"); }
__device__ __forceinline__ void cp_wait_all(){ asm volatile("cp.async.wait_all;":::"memory"); }
__device__ __forceinline__ void fence_async(){ asm volatile("fence.proxy.async.shared::cta;":::"memory"); }
__device__ __forceinline__ void sts4f(uint32_t a,const float* v){ asm volatile("st.shared.v4.f32 [%0], {%1,%2,%3,%4};"::"r"(a),"f"(v[0]),"f"(v[1]),"f"(v[2]),"f"(v[3]):"memory"); }
__device__ __forceinline__ void sts4(uint32_t a,uint4 v){ asm volatile("st.shared.v4.u32 [%0], {%1,%2,%3,%4};"::"r"(a),"r"(v.x),"r"(v.y),"r"(v.z),"r"(v.w):"memory"); }
__device__ __forceinline__ void sts4r(uint32_t a,const uint32_t* v){ asm volatile("st.shared.v4.u32 [%0], {%1,%2,%3,%4};"::"r"(a),"r"(v[0]),"r"(v[1]),"r"(v[2]),"r"(v[3]):"memory"); }
__device__ __forceinline__ void sts2(uint32_t a,uint32_t x,uint32_t y){ asm volatile("st.shared.v2.u32 [%0], {%1,%2};"::"r"(a),"r"(x),"r"(y):"memory"); }
__device__ __forceinline__ float4 lds4f(uint32_t a){ float4 v; asm volatile("ld.shared.v4.f32 {%0,%1,%2,%3}, [%4];":"=f"(v.x),"=f"(v.y),"=f"(v.z),"=f"(v.w):"r"(a):"memory"); return v; }
__device__ __forceinline__ float2 lds2f(uint32_t a){ float2 v; asm volatile("ld.shared.v2.f32 {%0,%1}, [%2];":"=f"(v.x),"=f"(v.y):"r"(a):"memory"); return v; }
__device__ __forceinline__ uint4 lds4(uint32_t a){ uint4 v; asm volatile("ld.shared.v4.u32 {%0,%1,%2,%3}, [%4];":"=r"(v.x),"=r"(v.y),"=r"(v.z),"=r"(v.w):"r"(a):"memory"); return v; }
__device__ __forceinline__ void lds4r(uint32_t* r,uint32_t a){ asm volatile("ld.shared.v4.u32 {%0,%1,%2,%3}, [%4];":"=r"(r[0]),"=r"(r[1]),"=r"(r[2]),"=r"(r[3]):"r"(a):"memory"); }
__device__ __forceinline__ uint2 lds2(uint32_t a){ uint2 v; asm volatile("ld.shared.v2.u32 {%0,%1}, [%2];":"=r"(v.x),"=r"(v.y):"r"(a):"memory"); return v; }
__device__ __forceinline__ float ex2(float x){ float r; asm("ex2.approx.ftz.f32 %0, %1;":"=f"(r):"f"(x)); return r; }
__device__ __forceinline__ float rcp(float x){ float r; asm("rcp.approx.ftz.f32 %0, %1;":"=f"(r):"f"(x)); return r; }
__device__ __forceinline__ void mbar_init(uint32_t a,int n){ asm volatile("mbarrier.init.shared.b64 [%0], %1;"::"r"(a),"r"(n):"memory"); }
__device__ __forceinline__ void mbar_expect(uint32_t a,int bytes){ asm volatile("mbarrier.arrive.expect_tx.shared.b64 _, [%0], %1;"::"r"(a),"r"(bytes):"memory"); }
__device__ __forceinline__ void mbar_arrive(uint32_t a){ asm volatile("mbarrier.arrive.shared.b64 _, [%0];"::"r"(a):"memory"); }
__device__ __forceinline__ bool mbar_try(uint32_t a,uint32_t par){ uint32_t ok; asm volatile("{\n.reg .pred p;\nmbarrier.try_wait.parity.shared.b64 p, [%1], %2;\nselp.u32 %0,1,0,p;\n}":"=r"(ok):"r"(a),"r"(par):"memory"); return ok; }
__device__ __forceinline__ bool mbar_test(uint32_t a,uint32_t par){ uint32_t ok; asm volatile("{\n.reg .pred p;\nmbarrier.test_wait.parity.shared.b64 p, [%1], %2;\nselp.u32 %0,1,0,p;\n}":"=r"(ok):"r"(a),"r"(par):"memory"); return ok; }
__device__ __forceinline__ bool mbar_try_cl(uint32_t a,uint32_t par){ uint32_t ok; asm volatile("{\n.reg .pred p;\nmbarrier.try_wait.parity.acquire.cluster.shared::cta.b64 p, [%1], %2;\nselp.u32 %0,1,0,p;\n}":"=r"(ok):"r"(a),"r"(par):"memory"); return ok; }
__device__ __forceinline__ void bulk_g2s(uint32_t dst,const void* src,int bytes,uint32_t mb){ asm volatile("cp.async.bulk.shared::cluster.global.mbarrier::complete_tx::bytes [%0], [%1], %2, [%3];"::"r"(dst),"l"(src),"r"(bytes),"r"(mb):"memory"); }
__device__ __forceinline__ uint32_t mapa(uint32_t a,uint32_t r){ uint32_t d; asm("mapa.shared::cluster.u32 %0, %1, %2;":"=r"(d):"r"(a),"r"(r)); return d; }
__device__ __forceinline__ void st_async2(uint32_t ra,uint32_t x,uint32_t y,uint32_t rmb){ asm volatile("st.async.weak.shared::cluster.mbarrier::complete_tx::bytes.v2.b32 [%0], {%1,%2}, [%3];"::"r"(ra),"r"(x),"r"(y),"r"(rmb):"memory"); }
__device__ __forceinline__ void st_async4(uint32_t ra,uint32_t x,uint32_t y,uint32_t z,uint32_t w,uint32_t rmb){ asm volatile("st.async.weak.shared::cluster.mbarrier::complete_tx::bytes.v4.b32 [%0], {%1,%2,%3,%4}, [%5];"::"r"(ra),"r"(x),"r"(y),"r"(z),"r"(w),"r"(rmb):"memory"); }
__device__ __forceinline__ void stg_rlx4(uint32_t* p,uint32_t a,uint32_t b,uint32_t c,uint32_t d){ asm volatile("st.relaxed.gpu.global.v4.u32 [%0], {%1,%2,%3,%4};"::"l"(p),"r"(a),"r"(b),"r"(c),"r"(d):"memory"); }
__device__ __forceinline__ void red64(void* p,uint32_t lo,uint32_t hi){ asm volatile("{\n.reg .b64 v;\nmov.b64 v, {%1,%2};\nred.relaxed.gpu.global.add.u64 [%0], v;\n}"::"l"(p),"r"(lo),"r"(hi):"memory"); }
__device__ __forceinline__ uint32_t amax2(uint32_t a,uint32_t b){ uint32_t r; asm("max.xorsign.abs.bf16x2 %0, %1, %2;":"=r"(r):"r"(a),"r"(b)); return r; }
__device__ __forceinline__ void cluster_sync(){ asm volatile("barrier.cluster.arrive.release.aligned;\nbarrier.cluster.wait.acquire.aligned;":::"memory"); }
__device__ __forceinline__ uint32_t ld_acq(const uint32_t* p){ uint32_t v; asm volatile("ld.acquire.gpu.global.u32 %0, [%1];":"=r"(v):"l"(p):"memory"); return v; }
__device__ __forceinline__ void fence_async_all(){ asm volatile("fence.proxy.async;":::"memory"); }
__device__ __forceinline__ void fence_async_g(){ asm volatile("fence.proxy.async.global;":::"memory"); }
__device__ __forceinline__ void fence_rel(){ asm volatile("fence.release.gpu;":::"memory"); }
__device__ __forceinline__ void fence_acq(){ asm volatile("fence.acquire.gpu;":::"memory"); }
__device__ __forceinline__ void fence_gpu(){ asm volatile("fence.acq_rel.gpu;":::"memory"); }

template<int NL,class V,class LDF,class OKF>
__device__ __forceinline__ int poll1(V* u,LDF ld,OKF ok,bool& dead,int code){
  #pragma unroll
  for(int i=0;i<NL;i++) u[i]=ld(i);
  int guard=0;
  while(true){
    bool f[NL]; bool a=true;
    #pragma unroll
    for(int i=0;i<NL;i++){ f[i]=ok(u[i]); a=a&&f[i]; }
    if(__all_sync(~0u,a)||dead) break;
    #pragma unroll
    for(int i=0;i<NL;i++) if(!f[i]) u[i]=ld(i);
    if(++guard>GUARD){ dead=true; g_err=code; }
  }
  return guard;
}
template<int NL,class V,class LDF,class OKF>
__device__ __forceinline__ int poll2(V* u,LDF ld,OKF ok,bool& dead,int code){
  int guard=0;
  while(true){
    bool f[NL]; bool a=true;
    #pragma unroll
    for(int i=0;i<NL;i++){ f[i]=ok(u[i]); a=a&&f[i]; }
    if(__all_sync(~0u,a)||dead) break;
    #pragma unroll
    for(int i=0;i<NL;i++) if(!f[i]) u[i]=ld(i);
    if(++guard>GUARD){ dead=true; g_err=code; }
  }
  return guard;
}
__device__ __forceinline__ void spin(uint32_t n){ uint32_t t0,t1; asm volatile("mov.u32 %0, %%clock;":"=r"(t0)); do{ asm volatile("mov.u32 %0, %%clock;":"=r"(t1)); }while(t1-t0<n); }
template<int N> __device__ __forceinline__ void wgmma(float* d,uint32_t da,uint32_t db,int sc);
template<int N> __device__ __forceinline__ void wgmma_rs(float* d,const uint32_t* a,uint32_t db,int sc);
template<> __device__ __forceinline__ void wgmma<128>(float* d,uint32_t da,uint32_t db,int sc){
  asm volatile("{\n.reg .pred p;\n.reg .b64 xa, xb;\nmov.b64 xa, {%64, 0x40000040};\nmov.b64 xb, {%65, 0x40000040};\nsetp.ne.b32 p, %66, 0;\nwgmma.mma_async.sync.aligned.m64n128k16.f32.bf16.bf16 {%0,%1,%2,%3,%4,%5,%6,%7,%8,%9,%10,%11,%12,%13,%14,%15,%16,%17,%18,%19,%20,%21,%22,%23,%24,%25,%26,%27,%28,%29,%30,%31,%32,%33,%34,%35,%36,%37,%38,%39,%40,%41,%42,%43,%44,%45,%46,%47,%48,%49,%50,%51,%52,%53,%54,%55,%56,%57,%58,%59,%60,%61,%62,%63}, xa, xb, p, 1, 1, 0, 1;\n}"
   :"+f"(d[0]),"+f"(d[1]),"+f"(d[2]),"+f"(d[3]),"+f"(d[4]),"+f"(d[5]),"+f"(d[6]),"+f"(d[7]),"+f"(d[8]),"+f"(d[9]),"+f"(d[10]),"+f"(d[11]),"+f"(d[12]),"+f"(d[13]),"+f"(d[14]),"+f"(d[15]),"+f"(d[16]),"+f"(d[17]),"+f"(d[18]),"+f"(d[19]),"+f"(d[20]),"+f"(d[21]),"+f"(d[22]),"+f"(d[23]),"+f"(d[24]),"+f"(d[25]),"+f"(d[26]),"+f"(d[27]),"+f"(d[28]),"+f"(d[29]),"+f"(d[30]),"+f"(d[31]),"+f"(d[32]),"+f"(d[33]),"+f"(d[34]),"+f"(d[35]),"+f"(d[36]),"+f"(d[37]),"+f"(d[38]),"+f"(d[39]),"+f"(d[40]),"+f"(d[41]),"+f"(d[42]),"+f"(d[43]),"+f"(d[44]),"+f"(d[45]),"+f"(d[46]),"+f"(d[47]),"+f"(d[48]),"+f"(d[49]),"+f"(d[50]),"+f"(d[51]),"+f"(d[52]),"+f"(d[53]),"+f"(d[54]),"+f"(d[55]),"+f"(d[56]),"+f"(d[57]),"+f"(d[58]),"+f"(d[59]),"+f"(d[60]),"+f"(d[61]),"+f"(d[62]),"+f"(d[63]):"r"(da),"r"(db),"r"(sc));
}
template<> __device__ __forceinline__ void wgmma<192>(float* d,uint32_t da,uint32_t db,int sc){
  asm volatile("{\n.reg .pred p;\n.reg .b64 xa, xb;\nmov.b64 xa, {%96, 0x40000040};\nmov.b64 xb, {%97, 0x40000040};\nsetp.ne.b32 p, %98, 0;\nwgmma.mma_async.sync.aligned.m64n192k16.f32.bf16.bf16 {%0,%1,%2,%3,%4,%5,%6,%7,%8,%9,%10,%11,%12,%13,%14,%15,%16,%17,%18,%19,%20,%21,%22,%23,%24,%25,%26,%27,%28,%29,%30,%31,%32,%33,%34,%35,%36,%37,%38,%39,%40,%41,%42,%43,%44,%45,%46,%47,%48,%49,%50,%51,%52,%53,%54,%55,%56,%57,%58,%59,%60,%61,%62,%63,%64,%65,%66,%67,%68,%69,%70,%71,%72,%73,%74,%75,%76,%77,%78,%79,%80,%81,%82,%83,%84,%85,%86,%87,%88,%89,%90,%91,%92,%93,%94,%95}, xa, xb, p, 1, 1, 0, 1;\n}"
   :"+f"(d[0]),"+f"(d[1]),"+f"(d[2]),"+f"(d[3]),"+f"(d[4]),"+f"(d[5]),"+f"(d[6]),"+f"(d[7]),"+f"(d[8]),"+f"(d[9]),"+f"(d[10]),"+f"(d[11]),"+f"(d[12]),"+f"(d[13]),"+f"(d[14]),"+f"(d[15]),"+f"(d[16]),"+f"(d[17]),"+f"(d[18]),"+f"(d[19]),"+f"(d[20]),"+f"(d[21]),"+f"(d[22]),"+f"(d[23]),"+f"(d[24]),"+f"(d[25]),"+f"(d[26]),"+f"(d[27]),"+f"(d[28]),"+f"(d[29]),"+f"(d[30]),"+f"(d[31]),"+f"(d[32]),"+f"(d[33]),"+f"(d[34]),"+f"(d[35]),"+f"(d[36]),"+f"(d[37]),"+f"(d[38]),"+f"(d[39]),"+f"(d[40]),"+f"(d[41]),"+f"(d[42]),"+f"(d[43]),"+f"(d[44]),"+f"(d[45]),"+f"(d[46]),"+f"(d[47]),"+f"(d[48]),"+f"(d[49]),"+f"(d[50]),"+f"(d[51]),"+f"(d[52]),"+f"(d[53]),"+f"(d[54]),"+f"(d[55]),"+f"(d[56]),"+f"(d[57]),"+f"(d[58]),"+f"(d[59]),"+f"(d[60]),"+f"(d[61]),"+f"(d[62]),"+f"(d[63]),"+f"(d[64]),"+f"(d[65]),"+f"(d[66]),"+f"(d[67]),"+f"(d[68]),"+f"(d[69]),"+f"(d[70]),"+f"(d[71]),"+f"(d[72]),"+f"(d[73]),"+f"(d[74]),"+f"(d[75]),"+f"(d[76]),"+f"(d[77]),"+f"(d[78]),"+f"(d[79]),"+f"(d[80]),"+f"(d[81]),"+f"(d[82]),"+f"(d[83]),"+f"(d[84]),"+f"(d[85]),"+f"(d[86]),"+f"(d[87]),"+f"(d[88]),"+f"(d[89]),"+f"(d[90]),"+f"(d[91]),"+f"(d[92]),"+f"(d[93]),"+f"(d[94]),"+f"(d[95]):"r"(da),"r"(db),"r"(sc));
}
template<> __device__ __forceinline__ void wgmma_rs<64>(float* d,const uint32_t* a,uint32_t db,int sc){
  asm volatile("{\n.reg .pred p;\n.reg .b64 xb;\nmov.b64 xb, {%36, 0x40000040};\nsetp.ne.b32 p, %37, 0;\nwgmma.mma_async.sync.aligned.m64n64k16.f32.bf16.bf16 {%0,%1,%2,%3,%4,%5,%6,%7,%8,%9,%10,%11,%12,%13,%14,%15,%16,%17,%18,%19,%20,%21,%22,%23,%24,%25,%26,%27,%28,%29,%30,%31}, {%32,%33,%34,%35}, xb, p, 1, 1, 0;\n}"
   :"+f"(d[0]),"+f"(d[1]),"+f"(d[2]),"+f"(d[3]),"+f"(d[4]),"+f"(d[5]),"+f"(d[6]),"+f"(d[7]),"+f"(d[8]),"+f"(d[9]),"+f"(d[10]),"+f"(d[11]),"+f"(d[12]),"+f"(d[13]),"+f"(d[14]),"+f"(d[15]),"+f"(d[16]),"+f"(d[17]),"+f"(d[18]),"+f"(d[19]),"+f"(d[20]),"+f"(d[21]),"+f"(d[22]),"+f"(d[23]),"+f"(d[24]),"+f"(d[25]),"+f"(d[26]),"+f"(d[27]),"+f"(d[28]),"+f"(d[29]),"+f"(d[30]),"+f"(d[31]):"r"(a[0]),"r"(a[1]),"r"(a[2]),"r"(a[3]),"r"(db),"r"(sc));
}
#define PPF 0
#define PPFA(i) (size_t)(i)
__device__ __align__(128) uint32_t g_sml[NCTA];
constexpr int PRE_T=704;
__global__ void __launch_bounds__(PRE_T) k_pre(const bf16* __restrict__ x,const bf16* __restrict__ mem0){
  const int warp=threadIdx.x>>5, lane=threadIdx.x&31;
  const int row=blockIdx.x*(PRE_T/32)+warp;
  asm volatile("griddepcontrol.launch_dependents;");
  if(threadIdx.x==0){ uint32_t sm_; asm volatile("mov.u32 %0, %%smid;":"=r"(sm_)); g_sml[blockIdx.x]=sm_; }
  {
    int i=blockIdx.x*PRE_T+threadIdx.x; constexpr int n=(NCTA-1)*PRE_T;
    if(blockIdx.x==NCTA-1){
      if(warp>=8) return;
      extern __shared__ uint32_t smx[];
      uint32_t w[10], mx=0;
      #pragma unroll
      for(int j=0;j<10;j++){ const int k=threadIdx.x+256*j; const uint16_t* mp=(const uint16_t*)mem0+(((k>>3)&3)*2+((k>>5)&1))*D+(k>>6)*16+(k&7);
        w[j]=mp[0]|((uint32_t)mp[8]<<16); mx=max(mx,max(w[j]&0x7fffu,(w[j]>>16)&0x7fffu)); }
      mx=__reduce_max_sync(~0u,mx); if(lane==0) smx[warp]=mx;
      bar_sync(1,256);
      #pragma unroll
      for(int j=0;j<8;j++) mx=max(mx,smx[j]);
      const uint32_t eb=min(max(mx>>7,40u),254u); const float sc=__uint_as_float((280u-eb)<<23);
      #pragma unroll
      for(int j=0;j<10;j++) g_acc[threadIdx.x+256*j]=((unsigned long long)(long long)__float2int_rn(__uint_as_float(w[j]&0xffff0000u)*sc)<<35)+((unsigned long long)(long long)__float2int_rn(__uint_as_float(w[j]<<16)*sc)<<6);
      if(threadIdx.x<NCTA*2) g_nrm[threadIdx.x]=SENT;
      if(threadIdx.x==0) g_nrm[NCTA*2]=(eb-29u)<<23;
      return;
    }
    for(int k=1280+i;k<NSEG*1280;k+=n) ((ulonglong2*)g_acc)[k]=make_ulonglong2(ACC_INIT,ACC_INIT);
    if(i==0) g_err=0;
    if(i<NCTA*32) g_flag[i]=0;
    if(i<C_NUM) g_cnt[i]=0;
  }
  if(row>=S) return;
  float v[20];
  {
    const uint32_t* p=(const uint32_t*)(x+(size_t)row*D);
    #pragma unroll
    for(int i=0;i<10;i++){ uint32_t u=p[lane+32*i]; v[2*i]=__uint_as_float(u<<16); v[2*i+1]=__uint_as_float(u&0xffff0000u); }
  }
  #pragma unroll
  for(int pass=0;pass<2;pass++){
    float s=0;
    #pragma unroll
    for(int i=0;i<20;i++) s+=v[i];
    #pragma unroll
    for(int o=16;o;o>>=1) s+=__shfl_xor_sync(~0u,s,o);
    float mean=s*(1.f/D);
    float q=0;
    #pragma unroll
    for(int i=0;i<20;i++){ float d=v[i]-mean; q+=d*d; }
    #pragma unroll
    for(int o=16;o;o>>=1) q+=__shfl_xor_sync(~0u,q,o);
    float var=rb(q*(1.f/D)), mb=rb(mean);
    float den=rb(sqrtf(rb(var+1e-5f)));
    uint32_t* o=(uint32_t*)((pass?g_y:g_xn)+(size_t)row*D);
    #pragma unroll
    for(int i=0;i<10;i++){
      float a=rb(rb(v[2*i]-mb)/den), b=rb(rb(v[2*i+1]-mb)/den);
      v[2*i]=a; v[2*i+1]=b;
      o[lane+32*i]=pack_bf16(a,b);
    }
  }
}

#define ULAY 0
#define WGO 1
#define UBP 4
#define URM 63
#define UEB 24
#define NOF 0
#define EXD 0
#define UEX 1
#define ADELAY 0
#define KP 4
#define UXP 16
#define OPF 99
#define XGP 0
#define W3O 250
#define FW 3
#define WPA 1
#define WPB 1
#define PD 1000
#define PPOS 2
#define ADP 0
#define ADUP 64
#define ADDN 4
constexpr int SM_QS=0;
constexpr int SM_KS=49152;
constexpr int SM_OS=131072;
constexpr int SM_RED=180224;
constexpr int SM_P=SM_RED+3584;
constexpr int SM_PM=SM_RED+4096+3584;
constexpr int SM_MB=SM_PM+128;
constexpr int SM_MX=SM_PM+192, SM_SCL=SM_PM+224;
constexpr int SM_X5=SM_RED+8192+3584;
constexpr int SM_KX=SM_RED+16384;
constexpr int SM_VX=SM_KX+4096;
constexpr int SM_SCX=SM_VX+14336;
constexpr int SM_KRED=SM_SCX+6144;
constexpr int SM_VMX=SM_KRED+8192;
constexpr int SM_TOTAL=SM_VMX+3072, SM_NR=SM_VMX;
static_assert(SM_TOTAL<=232448,"smem");
__device__ __forceinline__ void wg32_rs(float* d,const uint32_t* a,uint32_t db){
  asm volatile("{\n.reg .b64 xb;\nmov.b64 xb, {%20, 0x40000040};\nwgmma.mma_async.sync.aligned.m64n32k16.f32.bf16.bf16 {%0,%1,%2,%3,%4,%5,%6,%7,%8,%9,%10,%11,%12,%13,%14,%15}, {%16,%17,%18,%19}, xb, 1, 1, 1, 0;\n}"
   :"+f"(d[0]),"+f"(d[1]),"+f"(d[2]),"+f"(d[3]),"+f"(d[4]),"+f"(d[5]),"+f"(d[6]),"+f"(d[7]),"+f"(d[8]),"+f"(d[9]),"+f"(d[10]),"+f"(d[11]),"+f"(d[12]),"+f"(d[13]),"+f"(d[14]),"+f"(d[15])
   :"r"(a[0]),"r"(a[1]),"r"(a[2]),"r"(a[3]),"r"(db));
}
__device__ __forceinline__ void wg32_rs0(float* d,const uint32_t* a,uint32_t db){
  asm volatile("{\n.reg .b64 xb;\nmov.b64 xb, {%20, 0x40000040};\nwgmma.mma_async.sync.aligned.m64n32k16.f32.bf16.bf16 {%0,%1,%2,%3,%4,%5,%6,%7,%8,%9,%10,%11,%12,%13,%14,%15}, {%16,%17,%18,%19}, xb, 0, 1, 1, 0;\n}"
   :"=f"(d[0]),"=f"(d[1]),"=f"(d[2]),"=f"(d[3]),"=f"(d[4]),"=f"(d[5]),"=f"(d[6]),"=f"(d[7]),"=f"(d[8]),"=f"(d[9]),"=f"(d[10]),"=f"(d[11]),"=f"(d[12]),"=f"(d[13]),"=f"(d[14]),"=f"(d[15])
   :"r"(a[0]),"r"(a[1]),"r"(a[2]),"r"(a[3]),"r"(db));
}
__device__ __forceinline__ void wg32_ss(float* d,uint32_t da,uint32_t db){
  asm volatile("{\n.reg .b64 xa, xb;\nmov.b64 xa, {%16, 0x00000180};\nmov.b64 xb, {%17, 0x40000040};\nwgmma.mma_async.sync.aligned.m64n32k16.f32.bf16.bf16 {%0,%1,%2,%3,%4,%5,%6,%7,%8,%9,%10,%11,%12,%13,%14,%15}, xa, xb, 1, 1, 1, 0, 0;\n}"
   :"+f"(d[0]),"+f"(d[1]),"+f"(d[2]),"+f"(d[3]),"+f"(d[4]),"+f"(d[5]),"+f"(d[6]),"+f"(d[7]),"+f"(d[8]),"+f"(d[9]),"+f"(d[10]),"+f"(d[11]),"+f"(d[12]),"+f"(d[13]),"+f"(d[14]),"+f"(d[15])
   :"r"(da),"r"(db));
}
__device__ __forceinline__ void wg32_ss0(float* d,uint32_t da,uint32_t db){
  asm volatile("{\n.reg .b64 xa, xb;\nmov.b64 xa, {%16, 0x00000180};\nmov.b64 xb, {%17, 0x40000040};\nwgmma.mma_async.sync.aligned.m64n32k16.f32.bf16.bf16 {%0,%1,%2,%3,%4,%5,%6,%7,%8,%9,%10,%11,%12,%13,%14,%15}, xa, xb, 0, 1, 1, 0, 0;\n}"
   :"=f"(d[0]),"=f"(d[1]),"=f"(d[2]),"=f"(d[3]),"=f"(d[4]),"=f"(d[5]),"=f"(d[6]),"=f"(d[7]),"=f"(d[8]),"=f"(d[9]),"=f"(d[10]),"=f"(d[11]),"=f"(d[12]),"=f"(d[13]),"=f"(d[14]),"=f"(d[15])
   :"r"(da),"r"(db));
}
template<int V> struct IC{ static constexpr int v=V; };
__device__ __forceinline__ uint32_t lds1(uint32_t a){ uint32_t v; asm volatile("ld.shared.u32 %0, [%1];":"=r"(v):"r"(a):"memory"); return v; }
__device__ __forceinline__ void sts1(uint32_t a,uint32_t x){ asm volatile("st.shared.u32 [%0], %1;"::"r"(a),"r"(x):"memory"); }

#define TS(i)
#define TSB(i)
#define PC(i) (void)np
#define TW(i)
#define TF(i)
#define TFP(i)

__device__ __forceinline__ void cp_commit(){ asm volatile("cp.async.commit_group;":::"memory"); }
template<int N> __device__ __forceinline__ void cp_wait(){ asm volatile("cp.async.wait_group %0;"::"n"(N):"memory"); }
__device__ __forceinline__ void tma2d(uint32_t dst,const CUtensorMap* tm,int c0,int c1,uint32_t mb){
  asm volatile("cp.async.bulk.tensor.2d.shared::cluster.global.mbarrier::complete_tx::bytes [%0], [%1, {%3, %4}], [%2];"::"r"(dst),"l"(tm),"r"(mb),"r"(c0),"r"(c1):"memory"); }
__device__ __forceinline__ void tma2d_pf(const CUtensorMap* tm,int c0,int c1){
  asm volatile("cp.async.bulk.prefetch.tensor.2d.L2.global [%0, {%1, %2}];"::"l"(tm),"r"(c0),"r"(c1):"memory"); }
constexpr unsigned long long PL_EF=0x12F0000000000000ull, PL_EN=0x1000000000000000ull;
__device__ __forceinline__ void tma2dh(uint32_t dst,const CUtensorMap* tm,int c0,int c1,uint32_t mb,unsigned long long pl){
  asm volatile("cp.async.bulk.tensor.2d.shared::cluster.global.mbarrier::complete_tx::bytes.L2::cache_hint [%0], [%1, {%3, %4}], [%2], %5;"::"r"(dst),"l"(tm),"r"(mb),"r"(c0),"r"(c1),"l"(pl):"memory"); }
__device__ __forceinline__ void tma2d_pfh(const CUtensorMap* tm,int c0,int c1,unsigned long long pl){
  asm volatile("cp.async.bulk.prefetch.tensor.2d.L2.global.L2::cache_hint [%0, {%1, %2}], %3;"::"l"(tm),"r"(c0),"r"(c1),"l"(pl):"memory"); }
#define HV 0
#define HK 0
#define HP 0
#define HUS 0
struct RParams { CUtensorMap k,v,w[4]; const char* wq; const char* wo; };
#define SO 0
#define SA 1
#define SEF 7
#define SPF 1
__global__ void __launch_bounds__(256,1) k_rec(const __grid_constant__ RParams P,const uint32_t zero){
  extern __shared__ __align__(1024) uint8_t sm[];
  const int tid=threadIdx.x, warp=__shfl_sync(~0u,tid>>5,0), lane=tid&31, g=lane>>2, t=lane&3;
  const int b=blockIdx.x, h=b/3, c=b-3*h;
  const uint32_t sb=(uint32_t)__cvta_generic_to_shared(sm);
  const int kq=warp&3, mg=warp>>2, wt=warp-mg;
  const uint32_t s16=sb+lane*16;
  const uint32_t qs=lane*16+__shfl_sync(~0u,sb+(mg?SM_KS+kq*20480:SM_QS+kq*12288),0), m5u=__shfl_sync(~0u,sb+SM_X5+(kq>>1)*4096+(kq&1)*256,0), mo=((lane>>3)&1), os=sb+SM_OS+kq*12288+mo*6144+(lane>>4)*128+(lane&7)*16, us=sb+SM_VX+wt*2048+mo*512+(lane>>4)*128+(lane&7)*16;
  const uint32_t XS=sb+SM_MB, KVB=sb+SM_MB+8, XV=sb+SM_MB+16, XL=sb+SM_MB+24;
  #define tmK P.k
  #define tmV P.v
  GT(0);
  asm volatile("griddepcontrol.launch_dependents;");
  const int ntile=c==0?14:13, tile0=c==0?0:(1+13*c);
  uint32_t pw[40][4];
#define SG(i)
  SG(0);
  {
    static_assert(KP==4,"setup");
    const uint32_t qb=qs-lane*16, SBR=sb+SM_NR+128+warp*32, ob=sb+(mg?SM_OS:SM_RED)+kq*12288;
    unsigned long long plf, pln;
    asm volatile("createpolicy.fractional.L2::evict_first.b64 %0, 1.0;":"=l"(plf)); asm volatile("createpolicy.fractional.L2::evict_normal.b64 %0, 1.0;":"=l"(pln));
    const unsigned long long plq=(mg?(SEF&4):(SEF&2))?plf:pln, plo=(SEF&1)?plf:pln;
    auto wbox=[&](int rd,int sl,int mode){
      const int kb=rd?(sl<6?sl:sl-6):(sl<4?sl+6:sl), k=mg?(kb+5)%10:kb;
      const CUtensorMap* tm=&P.w[mg?(sl<(rd?6:4)?1:2):0];
      const int c0=h*DH+64*c, c1=80*kq+8*k;
      if(mode) asm volatile("cp.async.bulk.prefetch.tensor.3d.L2.global.L2::cache_hint [%0, {%1, %2, 0}], %3;"::"l"(tm),"r"(c0),"r"(c1),"l"(plq):"memory");
      else asm volatile("cp.async.bulk.tensor.3d.shared::cluster.global.mbarrier::complete_tx::bytes.L2::cache_hint [%0], [%1, {%3, %4, 0}], [%2], %5;"::"r"(qb+sl*2048),"l"(tm),"r"(SBR+((rd||(!mg&&sl>=4))?8:0)),"r"(c0),"r"(c1),"l"(plq):"memory");
    };
    if(lane==0){
      mbar_init(SBR,1); mbar_init(SBR+8,1); mbar_init(SBR+16,1);
      asm volatile("fence.mbarrier_init.release.cluster;":::"memory");
      mbar_expect(SBR,mg?20480:8192); mbar_expect(SBR+8,mg?20480:12288); mbar_expect(SBR+16,12288);
    }
    __syncwarp();
    if(lane<(mg?10:6)) wbox(0,lane,0);
    if(lane<6) asm volatile("cp.async.bulk.tensor.2d.shared::cluster.global.mbarrier::complete_tx::bytes.L2::cache_hint [%0], [%1, {%3, %4}], [%2], %5;"::"r"(ob+(mg?(lane>>1)*2048+(lane&1)*6144:lane*2048)),"l"(&P.w[3]),"r"(SBR+16),"r"((tile0+2*wt)*16),"r"(h*DH+((2*c+lane)%6)*32),"l"(plo):"memory");
    if(SPF&&lane<(mg?(SPF>1?10:0):4)) wbox(1,lane,1);
    __syncwarp();
    SG(1);
    float nr[4][2][4];
    #pragma unroll
    for(int i=0;i<32;i++) nr[i>>3][(i>>2)&1][i&3]=0.f;
    auto sq=[&](int n,const uint32_t* r){ mma16816(nr[n][0],r,r[0],r[2]); mma16816(nr[n][1],r,r[1],r[3]); };
    auto dg=[&](const float* d,int o){ return g==2*t?d[o]:(g==2*t+1?d[o+1]:0.f); };
    auto swait=[&](uint32_t a){ int gd=0; while(!mbar_try(a,0)){ if(++gd>GUARD){ g_err=9; break; } } };
    const int p8=((lane>>1)&3)+4*(lane&1), r16=(lane&7)+(lane>>4)*8;
    uint32_t ak[4], av[4], ao[2];
    #pragma unroll
    for(int j=0;j<4;j++){ ak[j]=qb+(p8+(lane>>4)*8)*128+(((2*j+mo)^p8)<<4); av[j]=qb+(p8+(lane>>4)*8)*128+(((2*((j+kq)&3)+mo)^p8)<<4); }
    #pragma unroll
    for(int i=0;i<2;i++) ao[i]=ob+r16*64+(((2*i+mo)^((lane>>1)&3))<<4);
    swait(SBR);
    SG(2);
    #pragma unroll
    for(int u=0;u<16;u++) ldsm4t(pw[u],ak[u&3]+(u>>2)*2048);
    if(SA&&!mg){
      uint32_t d0=0;
      #pragma unroll
      for(int u=0;u<16;u+=2) d0^=pw[u][0]^pw[u+1][0];
      if(lane+(d0&zero)<4) wbox(1,lane,0);
      __syncwarp();
    }
    swait(SBR+(mg?0:16));
    SG(3);
    uint32_t dp=0;
    {
      uint32_t a2[4];
      #pragma unroll
      for(int j=0;j<4;j++) a2[j]=mg?av[j]+8192:ao[j&1]+(j>>1)*1024;
      #pragma unroll
      for(int u=0;u<24;u++){ ldsm4t(pw[16+u],a2[u&3]+(u>>2)*2048); if(!SA) sq((u&1)*2,pw[16+u]); }
      #pragma unroll
      for(int u=0;u<40;u+=2) dp^=pw[u][0]^pw[u+1][0];
      dp&=zero;
    }
    if(lane+dp<(mg?10:(SA?0:4))) wbox(1,lane,0);
    __syncwarp();
    if(SA){
      #pragma unroll
      for(int u=0;u<24;u++) sq((u&1)*2,pw[16+u]);
    }
    SG(4);
    if(mg){
      swait(SBR+16);
      #pragma unroll 1
      for(int y=0;y<3;y++){
        uint32_t r[8][4];
        #pragma unroll
        for(int f=0;f<8;f++){ ldsm4t(r[f],ao[f&1]+y*2048+((f>>1)&1)*1024+(f>>2)*6144); sq(1+(f&1)*2,r[f]); }
        __syncwarp();
        #pragma unroll
        for(int f=0;f<8;f++) stsm4(os+y*2048+f*256,r[f][0],r[f][1],r[f][2],r[f][3]);
      }
    } else {
      bar_sync(5+dp,128);
      if(tid==96){
        mbar_init(XS,5); mbar_init(KVB,1); mbar_init(XV,1); mbar_init(XL,4);
        asm volatile("fence.mbarrier_init.release.cluster;":::"memory");
        mbar_expect(XS,4096); mbar_expect(XV,2048);
        int gd=0; while(ld_acq(g_cnt+C_KV)<64){ if(++gd>GUARD){ g_err=7; break; } } fence_async_g();
        mbar_expect(KVB,32*512);
        tma2d(sb+SM_KX,&tmK,h*DH+64*c,0,KVB);
        #pragma unroll 1
        for(int i=0;i<3;i++) tma2d(sb+SM_VX+i*4096,&tmV,h*DH+64*i,0,KVB);
        tma2d_pf(&tmK,h*DH+64*c,32); tma2d_pf(&tmV,h*DH+64*c,32);
      }
      if(tid==32) sts1(sb+SM_SCL+8,g_nrm[NCTA*2]);
      __syncwarp();
    }
    SG(5);
    swait(SBR+8);
    SG(6);
    #pragma unroll 1
    for(int y=0;y<(mg?10:6);y+=2){
      uint32_t r[8][4];
      #pragma unroll
      for(int j=0;j<8;j++) ldsm4t(r[j],(y<6?ak[j&3]:av[j&3])+y*2048+(j>>2)*2048);
      __syncwarp();
      #pragma unroll
      for(int j=0;j<8;j++) sts4r(qs+y*2048+j*512,r[j]);
      if(y>=6){
        #pragma unroll
        for(int j=0;j<8;j++) sq((j&1)*2,r[j]);
      }
    }
    SG(7);
    float d4[4][2];
    #pragma unroll
    for(int i=0;i<4;i++){ d4[i][0]=dg(nr[i][0],0); d4[i][1]=dg(nr[i][1],2); }
    float nv=mg?(d4[0][0]+d4[0][1])+(d4[2][0]+d4[2][1]):0.f;
    #pragma unroll
    for(int o=16;o;o>>=1) nv+=__shfl_xor_sync(~0u,nv,o);
    const uint32_t no=__reduce_max_sync(~0u,__float_as_uint(mg?fmaxf(d4[1][0]+d4[3][0],d4[1][1]+d4[3][1]):fmaxf(d4[0][0]+d4[2][0],d4[0][1]+d4[2][1])));
    if(lane==0){
      sts2(sb+SM_NR+warp*8,__float_as_uint(nv),no);
      #pragma unroll
      for(int i=0;i<3;i++) asm volatile("mbarrier.inval.shared.b64 [%0];"::"r"(SBR+i*8):"memory");
    }
  }
  fence_async();
  __syncthreads();
  SG(8);
  {
    float a=0.f; uint32_t o=0;
    if(warp==0){
      #pragma unroll
      for(int w=0;w<8;w++){ const uint2 x=lds2(sb+SM_NR+w*8); a+=__uint_as_float(x.x); o=max(o,x.y); }
      o=min(o,0x7f800000u);
    }
    asm volatile("barrier.cluster.arrive.relaxed.aligned;"::"r"(o):"memory");
    if(tid==0) stg_rlx2(g_nrm+b*2,min(__float_as_uint(a),0x7f800000u),o);
    asm volatile("barrier.cluster.wait.acquire.aligned;":::"memory");
  }
  SG(9);
  uint32_t pd=PD;
  bool dead=false;
  const uint32_t qrd=sb+SM_RED+1024+((lane>>3)&1)*4096+(lane>>4)*128+(lane&7)*16+kq*256;
  uint32_t rsc[2];
  rsc[0]=mapa(sb,c==2?0:c+1); rsc[1]=mapa(sb,c==0?2:c-1);
  GT(1);
  auto loop=[&](auto MGc){
  constexpr int MG=decltype(MGc)::v;
  uint32_t buf[8][4], um[2][2]={{0,0},{0,0}}, ex0=0, ex1=0;
  uint32_t eo1=(uint32_t)((32+(h>>2))*40960+(tile0+2*wt)*1024+(h&3)*128+lane*4), eo2=(uint32_t)(h*3072+(4*c+kq)*256+lane*4);
  uint32_t so=(uint32_t)((kq*10+MG*5)*512+(g&1)*256+(g>>1)*64+t*16)^zero;
  bool kvok=false;
  #define EXPU { char* um_=(char*)g_u+eo1; _Pragma("unroll") for(int i=0;i<2;i++) if(i==0||2*wt+1<ntile){ stg1(um_+i*1024,um[i][0]); stg1(um_+i*1024+512,um[i][1]); } }
  #define EXPK { char* ep=(char*)g_km+eo2; stg1(ep,ex0); stg1(ep+128,ex1); }
  #define UBULK { const uint32_t o_=(us-sb)&~2047u; asm volatile("{\n.reg .pred p;\nelect.sync _|p, 0xffffffff;\n@p cp.async.bulk.global.shared::cta.bulk_group.L2::cache_hint [%0], [%1], %2, %3;\n@p cp.async.bulk.commit_group;\n}" \
      ::"l"((char*)g_u+(uint32_t)(s*1638400+h*40960+tile0*1024-SM_VX+o_)),"r"(sb+o_),"r"(2*wt+1<ntile?2048:1024),"l"(s<HUS?PL_EF:PL_EN):"memory"); }
  uint32_t t0; asm volatile("mov.u32 %0, %%clock;":"=r"(t0)); t0-=4096;
  #define MB0(k) mb[k][0]
  #define MB1(k) mb[k][1]
  #pragma unroll 1
  for(int s=0;s<NSEG;s++){
    const bool last=s==NSEG-1;
    float u[2][16];
    const char* src=(const char*)g_acc+so;
    uint4 m[5];
    #define SPIN(T,N) { uint32_t t1; do{ asm volatile("mov.u32 %0, %%clock;":"=r"(t1)); }while((int)(t1-(T))<(int)(N)); }
    #define PLD { SPIN(t0,pd) _Pragma("unroll") for(int p=0;p<5;p++) m[p]=ldg_rlx4((const uint32_t*)(src+p*512)); SPIN(t0,pd) TFP(21); }
    {
      if(!kvok){ int gd=0; while(!mbar_try(KVB,s&1)){ if(dead) break; if(++gd>GUARD){ dead=true; g_err=6; } } }
      TFP(16);
      const uint32_t da=(((sb+SM_OS)>>4)&0x3fff)|(8u<<16);
      const uint32_t dv=(((sb+SM_VX)>>4)&0x3fff)|(1u<<16);
      const uint32_t vb[3]={dv+c*256,dv+(c==2?0:c+1)*256,dv+(c==0?2:c-1)*256};
      asm volatile("wgmma.fence.sync.aligned;":::"memory");
      if constexpr(MG){
        #pragma unroll
        for(int y=0;y<24;y++){
          const int i=WGO?(y&1):(y>=12), x=WGO?(y>>1):(y%12);
          if(x==0) wg32_ss0(u[i],da+i*16,vb[0]); else wg32_ss(u[i],da+(x*2+i)*16,vb[x>>2]+(x&3)*2);
          if(y==WPB){ EXPU SPIN(t0,0) }
        }
      } else {
        #pragma unroll
        for(int y=0;y<24;y++){
          const int i=WGO?(y&1):(y>=12), x=WGO?(y>>1):(y%12);
          if(x==0) wg32_rs0(u[i],pw[16+i],vb[0]); else wg32_rs(u[i],pw[16+x*2+i],vb[x>>2]+(x&3)*2);
          if(y==WPA&&warp!=3){ EXPU EXPK }
        }
      }
      asm volatile("wgmma.commit_group.sync.aligned;":::"memory");
      TFP(18);
      if(!MG&&warp==3){
        EXPK
        if(lane==0&&s+2<NSEG){ tma2d_pfh(&tmK,h*DH+64*c,(s+2)*32,HP&1?PL_EF:PL_EN); tma2d_pfh(&tmV,h*DH+64*c,(s+2)*32,HP&2?PL_EF:PL_EN); }
        __syncwarp();
        if(b<80&&lane<2&&s+2<NSEG) asm volatile("prefetch.global.L2 [%0];"::"l"(g_acc+(size_t)(s+2)*2560+b*32+lane*16));
      }
      PLD
    }
    const uint32_t mx=s16+SM_RED+kq*4096, m5=m5u+lane*8;
    {
      asm volatile("wgmma.wait_group.sync.aligned 0;":::"memory");
      TFP(19);
      if(MG||warp!=3){
        if(UEX) asm volatile("cp.async.bulk.wait_group 0;":::"memory");
        bar_sync(7,256);
        TFP(20);
        #pragma unroll
        for(int i=0;i<2;i++)
          #pragma unroll
          for(int kk=0;kk<2;kk++)
            stsm4(us+i*1024+kk*256,pack_bf16(u[i][8*kk],u[i][8*kk+1]),pack_bf16(u[i][8*kk+2],u[i][8*kk+3]),pack_bf16(u[i][8*kk+4],u[i][8*kk+5]),pack_bf16(u[i][8*kk+6],u[i][8*kk+7]));
        if(UEX){ fence_async(); if(UBP==0) UBULK }
        #pragma unroll
        for(int i=0;i<8;i++) lds4r(buf[i],qs+i*512);
      } else {
        #pragma unroll
        for(int i=0;i<8;i++) lds4r(buf[i],qs+i*512);
        bar_sync(7,256);
        asm volatile("{\n.reg .pred p, q;\nsetp.eq.u32 p, %0, 0;\nsetp.eq.and.u32 q, %1, 0, p;\n@q fence.release.gpu;\n@p st.relaxed.gpu.global.u32 [%2], %3;\n}"::"r"(lane),"r"((s&3)|NOF),"l"(g_flag+b*32),"r"(s):"memory");
      }
      SPIN(t0,pd)
      TFP(17);
    }
    uint32_t mb[10][2];
    {
      auto okf=[&](const uint4& v){ return ((v.x|v.z)&63u)==0; };
      const int np=poll2<5>(m,[&](int i){ return ldg_rlx4((const uint32_t*)(src+i*512)); },okf,dead,1);
      TW(0); PC(0); TFP(14);
      if(ADP){ if(np) pd=min(pd+ADUP,2000u); else pd=max(pd-ADDN,(uint32_t)ADP); }
      #pragma unroll
      for(int p=0;p<5;p++){
        mb[p][0]=pack_bf16((float)(int)__funnelshift_r(m[p].x,m[p].y,3),(float)(int)m[p].y);
        mb[p][1]=pack_bf16((float)(int)__funnelshift_r(m[p].z,m[p].w,3),(float)(int)m[p].w);
        if(p==0) sts2(MG?m5:mx-lane*8+3072,mb[0][0],mb[0][1]);
        if(p==2||p==4) sts4(mx+((MG?0:4)+(p>>2))*512,make_uint4(mb[p-1][0],mb[p-1][1],mb[p][0],mb[p][1]));
      }
      bar_arrive((MG?12:8)+kq,64);
      if(UEX&&UBP==1&&(MG||warp!=3)) UBULK
    }
    #define XGET { bar_sync((MG?8:12)+kq,64); const uint2 x=lds2(MG?mx-lane*8+3072:m5); mb[5][0]=x.x; mb[5][1]=x.y; \
      _Pragma("unroll") for(int p=0;p<2;p++){ const uint4 y=lds4(mx+((MG?4:0)+p)*512); mb[6+2*p][0]=y.x; mb[6+2*p][1]=y.y; mb[7+2*p][0]=y.z; mb[7+2*p][1]=y.w; } }
    #define XMAX { uint32_t a=amax2(amax2(amax2(mb[0][0],mb[0][1]),amax2(mb[1][0],mb[1][1])),amax2(amax2(amax2(mb[2][0],mb[2][1]),amax2(mb[3][0],mb[3][1])),amax2(mb[4][0],mb[4][1]))); \
      a=__reduce_max_sync(~0u,max(a&0x7fff0000u,(a<<16)&0x7fff0000u)); if(lane==0) sts1(sb+SM_MX+warp*4,a); }
    TS(0); TF(0);
    float acc[4][4]; uint32_t ux[2][2][4];
    #pragma unroll
    for(int i=0;i<4;i++){ acc[i][0]=acc[i][1]=acc[i][2]=acc[i][3]=0.f; }
    #define UXDEP (((ux[0][0][0]^ux[0][1][0])^(ux[1][0][0]^ux[1][1][0]))&zero)
    if constexpr(MG){
      #pragma unroll
      for(int y=0;y<10;y++){
        const int k=KP==4?(y<2?y:(y<4?y+4:(y<6?y-2:(y<8?y+2:y-4)))):(y<2?y:(y<2+KP?y+8-KP:y-KP));
        #pragma unroll
        for(int j=0;j<4;j++){
          if(k<10-KP){ mma16816(acc[j],buf[(k&1)*4+j],MB0(k),MB1(k)); lds4r(buf[(k&1)*4+j],qs+(k*4+j+8)*512); }
          else mma16816(acc[j],pw[k>=10-KP?(k-10+KP)*4+j:0],MB0(k),MB1(k));
        }
        if(y==XGP) XGET
        if(y==5) XMAX
        if(UEX&&UBP==y+2) UBULK
      }
      TF(1);
      {
        const uint32_t ra=s16+SM_KRED+kq*2048;
        #pragma unroll
        for(int i=0;i<4;i++) sts4f(ra+i*512,acc[i]);
      }
      bar_arrive(1,256);
#define VK(u) ((u)>>2)
      #pragma unroll
      for(int i=0;i<4;i++){ acc[i][0]=acc[i][1]=acc[i][2]=acc[i][3]=0.f; }
      #pragma unroll
      for(int y=0;y<40;y++){
        constexpr int NS_=4*KP;
        const int u=y<8?y:(y<20?y-8+NS_:(y<12+NS_?y-12:y));
        const int sl=(u+40-NS_)&7;
        if(u<NS_){ mma16816(acc[u&3],buf[sl],MB0(VK(u)),MB1(VK(u))); if(u+8<NS_) lds4r(buf[sl],qs+(48-NS_+u)*512); }
        else mma16816(acc[u&3],pw[u],MB0(VK(u)),MB1(VK(u)));
        if(y>=OPF&&y<OPF+8) ldsm4(buf[(y-OPF)&7],os+((y-OPF)&7)*256);
        if(y>=UXP&&y<UXP+4) ldsm4(ux[(y-UXP)>>1][(y-UXP)&1],us+((y-UXP)>>1)*1024+((y-UXP)&1)*256);
      }
      TF(2);
      const uint32_t ra=s16+SM_RED+1536;
      #pragma unroll
      for(int i=1;i<4;i++) sts4f(ra+kq*4096+i*512,acc[i]);
      bar_sync(3,128);
      const float cs=__uint_as_float(lds1(sb+SM_SCL+8+(s&1)*4));
      float4 c1=lds4f(ra+((kq+3)&3)*4096+512), d2=lds4f(ra+((kq+2)&3)*4096+1024), e2=lds4f(ra+((kq+1)&3)*4096+1536);
      const uint32_t p0=pack_bf16(((acc[0][0]+c1.x)+(d2.x+e2.x))*cs,((acc[0][1]+c1.y)+(d2.y+e2.y))*cs), p1=pack_bf16(((acc[0][2]+c1.z)+(d2.z+e2.z))*cs,((acc[0][3]+c1.w)+(d2.w+e2.w))*cs);
      if(UEX) asm volatile("cp.async.bulk.wait_group.read 0;":::"memory");
      bar_arrive(2+UXDEP,256);
      const uint32_t v0=movm(p0), v1=movm(p1);
      const uint32_t off=SM_VMX+(kq>>1)*512+lane*16+(kq&1)*8;
      #pragma unroll
      for(int r=0;r<2;r++) st_async2(rsc[r]+off+(2-r)*1024,v0,v1,rsc[r]+SM_MB+16);
      sts2(sb+off,v0,v1); __syncwarp(); if(lane==0) mbar_arrive(XL);
      TF(5);
      if(OPF>=40){
        #pragma unroll
        for(int i=0;i<8;i++) ldsm4(buf[i],os+i*256);
      }
    } else {
      uint32_t kb[8];
      #pragma unroll
      for(int y=0;y<10;y++){
        const int k=y<2?y:(y<4?y+4:(y<6?y-2:(y<8?y+2:y-4)));
        #pragma unroll
        for(int j=0;j<4;j++){
          if(k<6){ mma16816(acc[j],buf[(k&1)*4+j],MB0(k),MB1(k)); if(k<4) lds4r(buf[(k&1)*4+j],qs+(k*4+j+8)*512); }
          else mma16816(acc[j],pw[k>=6?(k-6)*4+j:0],MB0(k),MB1(k));
        }
        if(y==7){
          const uint32_t ka=sb+SM_KX+(8*kq+(lane&7))*128+((((lane>>3)^(2*kq))^(lane&7))<<4);
          ldsm4(kb,ka); ldsm4(kb+4,ka^64);
        }
        if(y==XGP) XGET
        if(y==5) XMAX
        if(UEX&&UBP==y+2&&warp!=3) UBULK
      }
      TF(1);
      {
        const uint32_t qa=s16+SM_RED+kq*4096+1024;
        #pragma unroll
        for(int i=0;i<2;i++) stsm4(qa+i*512,pack_bf16(acc[2*i][0],acc[2*i][1]),pack_bf16(acc[2*i][2],acc[2*i][3]),pack_bf16(acc[2*i+1][0],acc[2*i+1][1]),pack_bf16(acc[2*i+1][2],acc[2*i+1][3]));
      }
      TF(2);
      bar_sync(1,256);
      TS(1); TF(3);
      const uint32_t ra=s16+SM_KRED+kq*512;
      const float cs=__uint_as_float(lds1(sb+SM_SCL+8+(s&1)*4));
      float4 a3=lds4f(ra), c3=lds4f(ra+2048), d3=lds4f(ra+4096), e3=lds4f(ra+6144);
      uint32_t q[4][2][4];
      #pragma unroll
      for(int i=0;i<4;i++){ ldsm4t(q[i][0],qrd^(i*256)); ldsm4t(q[i][1],(qrd^(i*256))+8192); }
      const uint32_t p2=pack_bf16(((a3.x+c3.x)+(d3.x+e3.x))*cs,((a3.y+c3.y)+(d3.y+e3.y))*cs), p3=pack_bf16(((a3.z+c3.z)+(d3.z+e3.z))*cs,((a3.w+c3.w)+(d3.w+e3.w))*cs);
      const uint32_t f2=movm(p2), f3=movm(p3);
      ex0=f2; ex1=f3;
      float sc[6][4];
      #pragma unroll
      for(int i=0;i<6;i++){ sc[i][0]=sc[i][1]=sc[i][2]=sc[i][3]=0.f; }
      #pragma unroll
      for(int i=0;i<4;i++)
        #pragma unroll
        for(int jp=0;jp<2;jp++){
          mma16816(sc[(i&1)*2+jp],q[i][jp],kb[2*i],kb[2*i+1]);
          if(i==1) mma16816(sc[4+jp],q[0][jp],f2,f3);
        }
      const uint32_t w0=__float_as_uint(((sc[0][0]+sc[0][2])+(sc[1][0]+sc[1][2]))+((sc[2][0]+sc[2][2])+(sc[3][0]+sc[3][2]))), w1=__float_as_uint(((sc[0][1]+sc[0][3])+(sc[1][1]+sc[1][3]))+((sc[2][1]+sc[2][3])+(sc[3][1]+sc[3][3])));
      const uint32_t w2=__float_as_uint((sc[4][0]+sc[4][2])+(sc[5][0]+sc[5][2])), w3=__float_as_uint((sc[4][1]+sc[4][3])+(sc[5][1]+sc[5][3]));
      const uint32_t off=SM_SCX+(c*4+kq)*512+lane*16;
      #pragma unroll
      for(int r=0;r<2;r++) st_async4(rsc[r]+off,w0,w1,w2,w3,rsc[r]+SM_MB);
      sts4(sb+off,make_uint4(w0,w1,w2,w3)); __syncwarp(); if(lane==0) mbar_arrive(XS);
      TS(2); TF(5);
    }
    if(!MG&&warp==3){
      bar_arrive(2,256);
      const float ssc=0.07216878364870322f*__uint_as_float(lds1(sb+SM_SCL+8+(s&1)*4));
      uint32_t kvc; asm volatile("ld.relaxed.gpu.global.u32 %0, [%1];":"=r"(kvc):"l"(g_cnt+C_KV+(((s>>2)+1)&15)):"memory");
      TF(6);
      { int gd=0; while(!mbar_try(XS,s&1)){ if(dead) break; if(++gd>GUARD){ dead=true; g_err=2; } } }
      TF(7);
      float sv[10];
      {
        float4 u[12];
        #pragma unroll
        for(int n=0;n<12;n++) u[n]=lds4f(s16+SM_SCX+n*512);
        uint32_t r[5];
        #pragma unroll
        for(int n=0;n<4;n++) r[n+1]=pack_bf16((u[n].x+u[4+n].x)+u[8+n].x,(u[n].y+u[4+n].y)+u[8+n].y);
        r[0]=pack_bf16((((u[0].z+u[1].z)+(u[2].z+u[3].z))+((u[4].z+u[5].z)+(u[6].z+u[7].z)))+((u[8].z+u[9].z)+(u[10].z+u[11].z)),
                       (((u[0].w+u[1].w)+(u[2].w+u[3].w))+((u[4].w+u[5].w)+(u[6].w+u[7].w)))+((u[8].w+u[9].w)+(u[10].w+u[11].w)));
        #pragma unroll
        for(int n=0;n<5;n++){
          const uint32_t w=pack_bf16(__uint_as_float(r[n]<<16)*ssc,__uint_as_float(r[n]&0xffff0000u)*ssc);
          sv[2*n]=__uint_as_float(w<<16); sv[2*n+1]=__uint_as_float(w&0xffff0000u);
        }
      }
      TF(8);
      float mx=fmaxf(fmaxf(fmaxf(sv[2],sv[3]),fmaxf(sv[4],sv[5])),fmaxf(fmaxf(fmaxf(sv[6],sv[7]),fmaxf(sv[8],sv[9])),fmaxf(sv[0],sv[1])));
      mx=fmaxf(mx,__shfl_xor_sync(~0u,mx,1)); mx=fmaxf(mx,__shfl_xor_sync(~0u,mx,2));
      mx*=-1.4426950408889634f;
      #pragma unroll
      for(int i=0;i<10;i++) sv[i]=ex2(fmaf(sv[i],1.4426950408889634f,mx));
      sts1(sb+SM_PM+lane*4,pack_bf16(sv[0],sv[1]));
      sts4(s16+SM_P,make_uint4(pack_bf16(sv[2],sv[3]),pack_bf16(sv[4],sv[5]),pack_bf16(sv[6],sv[7]),pack_bf16(sv[8],sv[9])));
      TF(9);
      bar_sync(4,256);
      asm volatile("mov.u32 %0, %%clock;":"=r"(t0)); t0+=W3O;
      TF(11);
      if(lane==0){
        mbar_expect(XS,4096); mbar_expect(XV,2048);
        if((s&3)==2){ int gd=0; while(kvc<64&&s<NSEG-4){ kvc=ld_acq(g_cnt+C_KV+(s>>2)+1); if(++gd>GUARD){ g_err=7; break; } } fence_acq(); fence_async_g(); }
      }
      __syncwarp();
      eo2=(uint32_t)(s*98304+h*3072+(4*c+kq)*256+((s16-sb)>>2))^zero;
      TF(13);
    } else {
      if constexpr(!MG){
        #pragma unroll
        for(int i=0;i<2;i++){ ldsm4(ux[i][0],us+i*1024); ldsm4(ux[i][1],us+i*1024+256); }
        if(s==0&&warp==2){
          int gd=0; uint32_t x[6];
          #pragma unroll 1
          while(true){
            bool ok=true;
            #pragma unroll
            for(int i=0;i<6;i++){ asm volatile("ld.relaxed.gpu.global.u32 %0, [%1];":"=r"(x[i]):"l"(g_nrm+lane*6+i):"memory"); ok=ok&&x[i]!=SENT; }
            if(__all_sync(~0u,ok)) break;
            if(++gd>GUARD){ g_err=8; break; }
          }
          const float cw=27.5f*sqrtf((__uint_as_float(x[0])+__uint_as_float(x[2]))+__uint_as_float(x[4]))*sqrtf(__uint_as_float(max(x[1],max(x[3],x[5]))));
          sts1(sb+SM_SCL+4,__reduce_max_sync(~0u,__float_as_uint(cw)&0x7fffffffu));
          __syncwarp();
        }
        {
          const uint4 x=lds4(sb+SM_MX), y=lds4(sb+SM_MX+16); const float cw=__uint_as_float(lds1(sb+SM_SCL+4)), cs=__uint_as_float(lds1(sb+SM_SCL+8+(s&1)*4));
          const float mm=__uint_as_float(max(max(max(x.x,x.y),max(x.z,x.w)),max(max(y.x,y.y),max(y.z,y.w))))*cs;
          const uint32_t eo=min(max((__float_as_uint(cw*fmaxf(mm,1.f))>>23)&255u,37u),254u)-21u;
          if(tid==64){ sts1(sb+SM_SCL,eo*0x00800080u); sts1(sb+SM_SCL+12-(s&1)*4,(eo-3u)<<23); }
        }
        TF(4);
        if(UEX) asm volatile("cp.async.bulk.wait_group.read 0;":::"memory");
        bar_sync(2+UXDEP,256);
        if(!last&&lane==0){
          tma2dh(sb+SM_VX+kq*4096,&tmV,h*DH+64*kq,(s+1)*32,KVB,HV?PL_EF:PL_EN);
          if(kq==0) mbar_expect(KVB,32*512);
          if(kq==1) tma2dh(sb+SM_KX,&tmK,h*DH+64*c,(s+1)*32,KVB,HK?PL_EF:PL_EN);
        }
        __syncwarp();
      }
      float ca[2][2][4];
      #pragma unroll
      for(int i=0;i<2;i++)
        #pragma unroll
        for(int j=0;j<2;j++){ ca[i][j][0]=ca[i][j][1]=ca[i][j][2]=ca[i][j][3]=0.f; }
      TF(6);
      { int gd=0; while(!mbar_try(XL,s&1)){ if(dead) break; if(++gd>GUARD){ dead=true; g_err=5; } } }
      TF(7);
      uint4 vm[6];
      vm[0]=lds4(s16+SM_VMX); vm[1]=lds4(s16+SM_VMX+512);
      #define VB0(x) (((x)&1)?vm[(x)>>1].z:vm[(x)>>1].x)
      #define VB1(x) (((x)&1)?vm[(x)>>1].w:vm[(x)>>1].y)
      if constexpr(MG){
        #pragma unroll
        for(int x=0;x<12;x++){
          if(x==4){
            TF(8);
            { int gd=0; while(!mbar_try(XV,s&1)){ if(dead) break; if(++gd>GUARD){ dead=true; g_err=3; } } }
            TF(9);
            #pragma unroll
            for(int i=2;i<6;i++) vm[i]=lds4(s16+SM_VMX+i*512);
          }
          #pragma unroll
          for(int i=0;i<2;i++){
            mma16816(ca[i][x&1],buf[(x*2+i)&7],VB0(x),VB1(x));
            if(x<8) ldsm4(buf[(x*2+i)&7],os+(x*2+i+8)*256);
          }
        }
      } else {
        #pragma unroll
        for(int x=0;x<12;x++){
          if(x==4){
            TF(8);
            { int gd=0; while(!mbar_try(XV,s&1)){ if(dead) break; if(++gd>GUARD){ dead=true; g_err=3; } } }
            TF(9);
            #pragma unroll
            for(int i=2;i<6;i++) vm[i]=lds4(s16+SM_VMX+i*512);
          }
          #pragma unroll
          for(int i=0;i<2;i++) mma16816(ca[i][x&1],pw[16+x*2+i],VB0(x),VB1(x));
        }
      }
      TF(10);
      bar_sync(4,256);
      TS(3); TF(11);
      const uint4 pq=lds4(s16+SM_P); const uint32_t pm=lds1(sb+SM_PM+lane*4), on=lds1(sb+SM_SCL);
      kvok=mbar_test(KVB,(s&1)^1);
      const uint32_t one[4]={on,on,on,on};
      float d[2][4], e[4];
      #pragma unroll
      for(int i=0;i<4;i++){ d[0][i]=0.f; d[1][i]=0.f; e[i]=0.f; }
      mma16816(e,one,pq.x,pq.y); mma16816(d[0],ux[0][0],pq.x,pq.y); mma16816(d[1],ux[1][0],pq.x,pq.y);
      mma16816(e,one,pq.z,pq.w); mma16816(d[0],ux[0][1],pq.z,pq.w); mma16816(d[1],ux[1][1],pq.z,pq.w);
      mma1688(e,one[0],one[0],pm);
      #pragma unroll
      for(int i=0;i<2;i++){ um[i][0]=pack_bf16(ca[i][0][0]+ca[i][1][0],ca[i][0][1]+ca[i][1][1]); um[i][1]=pack_bf16(ca[i][0][2]+ca[i][1][2],ca[i][0][3]+ca[i][1][3]); mma1688(d[i],um[i][0],um[i][1],pm); }
      const float i0=rcp(e[0]), i1=rcp(e[1]);
      TF(12);
      const uint32_t ro=(tile0+2*wt)*512+t*64+g*8;
      char* dst=(char*)g_acc+(uint32_t)((s+1)*20480+ro);
      #pragma unroll
      for(int i=0;i<2;i++){
        if(!last&&(i==0||2*wt+1<ntile)){
          red64(dst+i*512,(__float_as_uint(fmaf(d[i][0],i0,12582912.f))<<6)+1u,__float_as_uint(fmaf(d[i][2],i0,12582912.f))<<3);
          red64(dst+i*512+256,(__float_as_uint(fmaf(d[i][1],i1,12582912.f))<<6)+1u,__float_as_uint(fmaf(d[i][3],i1,12582912.f))<<3);
        }
      }
      asm volatile("mov.u32 %0, %%clock;":"=r"(t0));
      {
        const uint32_t z=t0&zero;
        eo1=(uint32_t)(s*1638400+(32+(h>>2))*40960+(tile0+2*wt)*1024+(h&3)*128+((s16-sb)>>2))^z;
        if(!MG) eo2=(uint32_t)(s*98304+h*3072+(4*c+kq)*256+((s16-sb)>>2))^z;
      }
      TW(1);
      TS(4); TF(13);
    }
    so+=20480;
  }
  if(MG||warp!=3) EXPU
  if(!MG) EXPK
  };
  { if(mg) loop(IC<1>{}); else loop(IC<0>{}); }
  asm volatile("cp.async.bulk.wait_group 0;":::"memory");
  __syncthreads();
  if(tid==FW*32){ fence_rel(); stg_rlx1(g_flag+b*32,NSEG); }
  GT(2);
  cluster_sync();
}

#define XB 0
#define XU 0
#define KVQ 1024
#define KPF 0
#define XA 0
#define ROT 38
#define ROT0 3
#define HU 1
#define HQ 1
#define HX 0
#define FNS 40
#define UTM 0
#define UPF 0
#define KLEAD 16
#define MLEAD 16
#define QPK 1
#define FAG fence_async_g
enum { M_XN=0,M_Y,M_H,M_K,M_V,M_GATE,M_WQ,M_WK,M_WV,M_W1,M_W2,M_U1,M_U2,M_U5,M_U10,M_NUM,M_OUT };
struct WParams { CUtensorMap m[M_NUM]; const bf16* x; const bf16* b1; const bf16* b2; bf16* out; const bf16* wq; const bf16* wo; };
#define WPN 4
#define WPM 0
#define WPS 0
#define WPC 1920
#define WPF 99
enum { T_RED=0,T_OP=1,T_QA=2,T_M2=3,T_M1=4,T_KV=5,T_END=6 };
#define KVR 5
#define KVJ 16
constexpr int KVUP=128*KVR;
#define TRIG 10
#define SOV 1
#define LATE 15
#define E15 4
#define OPE 15
#define Q15 3
#define HB 1
#define EARLY 2
constexpr int NRB=16;
constexpr int STG=45056, NST=4, SLOT=24576, BOXS=8192;
constexpr int W_SLOT=NST*STG;
constexpr int W_BAR=W_SLOT+2*SLOT;
constexpr int W_TOTAL=W_BAR+1024;
static_assert(W_TOTAL<=232448,"smem");
#define ST(i)
#define QT(i)
__device__ __forceinline__ void stsm4n(uint32_t a,uint32_t r0,uint32_t r1,uint32_t r2,uint32_t r3){ asm volatile("stmatrix.sync.aligned.m8n8.x4.shared.b16 [%0], {%1,%2,%3,%4};"::"r"(a),"r"(r0),"r"(r1),"r"(r2),"r"(r3)); }
#define WGUARD 2000000
__host__ __device__ constexpr int n_uns(){ int n=0; while(n<16&&nsp(n)==1) n++; return n; }
__host__ __device__ constexpr int n_op(){ int n=0; for(int r=0;r<NRB;r++) n+=4*nsp(r); return n; }
__host__ __device__ constexpr int n_red(){ return 0; }
__host__ __device__ constexpr int pu_st(int ns){ return ns==1?40:(ns==2?20:(ns==5?10:8)); }

__device__ __forceinline__ void wg_arrive(){ asm volatile("wgmma.fence.sync.aligned;":::"memory"); }
__device__ __forceinline__ void wg_commit(){ asm volatile("wgmma.commit_group.sync.aligned;":::"memory"); }
template<int N> __device__ __forceinline__ void wg_wait(){ asm volatile("wgmma.wait_group.sync.aligned %0;"::"n"(N):"memory"); }
__device__ __forceinline__ void mbar_wait(uint32_t a,uint32_t par){ int gd=0; while(!mbar_try(a,par)){ if(++gd>WGUARD){ g_err=20; break; } } }
__device__ __forceinline__ uint32_t ld_rlx(const uint32_t* p){ uint32_t v; asm volatile("ld.relaxed.gpu.global.u32 %0, [%1];":"=r"(v):"l"(p):"memory"); return v; }
__device__ __forceinline__ float4 ld_rlx4f(const float4* p){ float4 v; asm volatile("ld.relaxed.gpu.global.v4.f32 {%0,%1,%2,%3}, [%4];":"=f"(v.x),"=f"(v.y),"=f"(v.z),"=f"(v.w):"l"(p):"memory"); return v; }
__device__ __forceinline__ void red_rel(uint32_t* p){ asm volatile("red.release.gpu.global.add.u32 [%0], 1;"::"l"(p):"memory"); }
__device__ __forceinline__ void tma_st(const CUtensorMap* tm,uint32_t src,int c0,int c1){
  asm volatile("cp.async.bulk.tensor.2d.global.shared::cta.bulk_group [%0, {%2, %3}], [%1];"::"l"(tm),"r"(src),"r"(c0),"r"(c1):"memory"); }
#define KEF 4
__device__ __forceinline__ void tma_st_ef(const CUtensorMap* tm,uint32_t src,int c0,int c1){
  asm volatile("{\n.reg .b64 pl;\ncreatepolicy.fractional.L2::evict_first.b64 pl, 1.0;\ncp.async.bulk.tensor.2d.global.shared::cta.bulk_group.L2::cache_hint [%0, {%2, %3}], [%1], pl;\n}"::"l"(tm),"r"(src),"r"(c0),"r"(c1):"memory"); }
__device__ __forceinline__ void bulk_commit(){ asm volatile("cp.async.bulk.commit_group;":::"memory"); }
__device__ __forceinline__ void bulk_wait_rd(){ asm volatile("cp.async.bulk.wait_group.read 0;":::"memory"); }
__device__ __forceinline__ void bulk_wait(){ asm volatile("cp.async.bulk.wait_group 0;":::"memory"); }
__device__ __forceinline__ void mbar_arrive_cl(uint32_t a){ asm volatile("mbarrier.arrive.shared::cluster.b64 _, [%0];"::"r"(a):"memory"); }
__device__ __forceinline__ void tma2dm(uint32_t dst,const CUtensorMap* tm,int c0,int c1,uint32_t mb){
  asm volatile("cp.async.bulk.tensor.2d.shared::cluster.global.mbarrier::complete_tx::bytes.multicast::cluster [%0], [%1, {%3, %4}], [%2], %5;"::"r"(dst),"l"(tm),"r"(mb),"r"(c0),"r"(c1),"h"((uint16_t)3):"memory"); }

template<int N,int CL,int XS> __device__ __forceinline__ void mainloop(float* acc,int nkb,uint32_t sb,int lane,uint32_t pos){
  const uint32_t eb=CL?mapa(sb+W_BAR+32,lane&1):sb+W_BAR+32;
  uint32_t pst=0;
  #pragma unroll
  for(int i=0;i<N/2;i++){ acc[i]=0.f; acc[96+i]=0.f; }
  #pragma unroll 1
  for(int kb=0;kb<nkb;kb++,pos++){
    const uint32_t st=pos&3;
    mbar_wait(sb+W_BAR+st*8,(pos>>2)&1);
    if(!XS&&kb==nkb-1&&(threadIdx.x&127)==0) mbar_arrive(sb+W_BAR+144);
    const uint32_t a=sb+st*STG;
    const uint32_t da=((a>>4)&0x3fff)|(1u<<16);
    const uint32_t db=da+1024+(511u<<16);
    wg_arrive();
    #pragma unroll
    for(int k=0;k<4;k++){ wgmma<N>(acc,da+2*k,db+128*k,kb|k); wgmma<N>(acc+96,da+512+2*k,db+128*k,kb|k); }
    wg_commit();
    if(kb>0){ wg_wait<1>(); if(CL){ if(lane<2) mbar_arrive_cl(eb+pst*8); } else if(lane==0) mbar_arrive(eb+pst*8); }
    pst=st;
  }
  if(XS){
    #pragma unroll
    for(int x=0;x<XS;x++) mbar_wait(sb+W_BAR+((pos+x)&3)*8,((pos+x)>>2)&1);
    if((threadIdx.x&127)==0) mbar_arrive(sb+W_BAR+144);
  }
  wg_wait<0>();
  if(CL){ if(lane<2) mbar_arrive_cl(eb+pst*8); } else if(lane==0) mbar_arrive(eb+pst*8);
}
__device__ __forceinline__ uint32_t act2(uint32_t u,uint32_t bb,float c1,float c3){
  uint32_t s; asm("add.rn.bf16x2 %0, %1, %2;":"=r"(s):"r"(u),"r"(bb));
  float r[2]={__uint_as_float(s<<16), __uint_as_float(s&0xffff0000u)};
  #pragma unroll
  for(int i=0;i<2;i++){
    const float z=r[i]*fmaf(r[i]*r[i],c3,c1);
    r[i]=r[i]*rcp(1.f+ex2(z));
  }
  return pack_bf16(r[0],r[1]);
}
__device__ __forceinline__ uint32_t fin1(uint32_t s,uint32_t x,uint32_t gq){
  const uint32_t p=pack_bf16(__uint_as_float(s<<16)*__uint_as_float(gq<<16),__uint_as_float(s&0xffff0000u)*__uint_as_float(gq&0xffff0000u));
  return pack_bf16(__uint_as_float(x<<16)+__uint_as_float(p<<16),__uint_as_float(x&0xffff0000u)+__uint_as_float(p&0xffff0000u));
}
template<int NT> __device__ __forceinline__ void stage_pk(const uint32_t* p,uint32_t ra,int lane){
  const int sw=lane&7, hi=lane>>4;
  #pragma unroll
  for(int T=0;T<NT;T++) stsm4n(ra+(T>>2)*BOXS+((((2*T+hi)&7)^sw)<<4),p[4*T],p[4*T+1],p[4*T+2],p[4*T+3]);
}
__device__ __noinline__ void post_pass(uint32_t sl,int nbox,uint32_t ba,float c1,float c3){
  const int lane=threadIdx.x&31, r=lane>>3, c=lane&7;
  __syncwarp();
  #pragma unroll 1
  for(int j=0;j<nbox;j++){
    uint4 u[4]; uint32_t a[4];
    #pragma unroll
    for(int i=0;i<4;i++){ const int rr=4*i+r; a[i]=sl+j*BOXS+rr*128+((c^(rr&7))<<4); u[i]=lds4(a[i]); }
    const uint4 bb=lds4(ba+j*128+c*16);
    #pragma unroll
    for(int i=0;i<4;i++){
      uint4& v=u[i];
      v.x=act2(v.x,bb.x,c1,c3); v.y=act2(v.y,bb.y,c1,c3); v.z=act2(v.z,bb.z,c1,c3); v.w=act2(v.w,bb.w,c1,c3);
      sts4(a[i],v);
    }
  }
}
__device__ __forceinline__ uint4 ldg_h4(const uint32_t* p){ uint4 v; if(HX&1) asm volatile("ld.relaxed.gpu.global.L2::cache_hint.v4.u32 {%0,%1,%2,%3}, [%4], %5;":"=r"(v.x),"=r"(v.y),"=r"(v.z),"=r"(v.w):"l"(p),"l"(PL_EF):"memory"); else v=ldg_rlx4(p); return v; }
__device__ __forceinline__ void stg_h4(void* p,uint32_t a,uint32_t b,uint32_t c,uint32_t d){ if(HX&2) asm volatile("st.global.L2::cache_hint.v4.u32 [%0], {%1,%2,%3,%4}, %5;"::"l"(p),"r"(a),"r"(b),"r"(c),"r"(d),"l"(PL_EF):"memory"); else *(uint4*)p=make_uint4(a,b,c,d); }
__device__ __forceinline__ void wg32_pu(float* d,uint32_t da,uint32_t db,int sc){
  asm volatile("{\n.reg .pred p;\n.reg .b64 xa, xb;\nmov.b64 xa, {%16, 32};\nmov.b64 xb, {%17, 8};\nsetp.ne.b32 p, %18, 0;\nwgmma.mma_async.sync.aligned.m64n32k16.f32.bf16.bf16 {%0,%1,%2,%3,%4,%5,%6,%7,%8,%9,%10,%11,%12,%13,%14,%15}, xa, xb, p, 1, 1, 0, 0;\n}"
   :"+f"(d[0]),"+f"(d[1]),"+f"(d[2]),"+f"(d[3]),"+f"(d[4]),"+f"(d[5]),"+f"(d[6]),"+f"(d[7]),"+f"(d[8]),"+f"(d[9]),"+f"(d[10]),"+f"(d[11]),"+f"(d[12]),"+f"(d[13]),"+f"(d[14]),"+f"(d[15])
   :"r"(da),"r"(db),"r"(sc));
}
__device__ __forceinline__ void wg16_rs(float* d,const uint32_t* a,uint32_t db,int sc){
  asm volatile("{\n.reg .pred p;\n.reg .b64 xb;\nmov.b64 xb, {%12, 192};\nsetp.ne.b32 p, %13, 0;\nwgmma.mma_async.sync.aligned.m64n16k16.f32.bf16.bf16 {%0,%1,%2,%3,%4,%5,%6,%7}, {%8,%9,%10,%11}, xb, p, 1, 1, 0;\n}"
   :"+f"(d[0]),"+f"(d[1]),"+f"(d[2]),"+f"(d[3]),"+f"(d[4]),"+f"(d[5]),"+f"(d[6]),"+f"(d[7]):"r"(a[0]),"r"(a[1]),"r"(a[2]),"r"(a[3]),"r"(db),"r"(sc));
}
__device__ __forceinline__ void stsm4t(uint32_t a,uint32_t r0,uint32_t r1,uint32_t r2,uint32_t r3){ asm volatile("stmatrix.sync.aligned.m8n8.x4.trans.shared.b16 [%0], {%1,%2,%3,%4};"::"r"(a),"r"(r0),"r"(r1),"r"(r2),"r"(r3):"memory"); }
template<int NS> __device__ __forceinline__ void pu_item(const WParams& P,int rbk,int a,uint32_t pos,uint32_t sb,int tid,uint32_t& e0,int& sq){
  constexpr int MT=10/NS, NKB=pu_st(NS), BPS=40/NKB, H0=(MT+1)/2;
  const int lane=tid&31, wg=tid>>7, wq=(tid>>5)&3;
  const int seg=rbk*4+a/NS, part=a%NS;
  const uint32_t go=(uint32_t)((seg*32+wq*8+(lane>>3))*D+part*MT*64+(lane&7)*8);
  uint4 xx[MT][2], gg[MT][2];
  auto ldx=[&](int m){
    #pragma unroll
    for(int j=m*H0;j<m*H0+H0&&j<MT;j++)
      #pragma unroll
      for(int i=0;i<2;i++){ const uint32_t o=go+i*4*D+j*64; xx[j][i]=ldg_h4((const uint32_t*)(P.x+o)); gg[j][i]=ldg_h4((const uint32_t*)(g_gate+o)); }
  };
  if(NS>1){ ldx(0); ldx(1); }
  float acc[MT][16];
  #pragma unroll
  for(int i=0;i<MT*16;i++) acc[i>>4][i&15]=0.f;
  uint32_t pst=0;
  #pragma unroll 1
  for(int kb=0;kb<NKB;kb++,pos++){
    const uint32_t st=pos&3;
    mbar_wait(sb+W_BAR+st*8,(pos>>2)&1);
    if(kb==NKB-1&&(tid&127)==0) mbar_arrive(sb+W_BAR+144);
    const uint32_t sa=((sb+st*STG)>>4)&0x3fff, da=sa|(8u<<16), db=(sa+BPS*MT*256)|(32u<<16);
    wg_arrive();
    #pragma unroll
    for(int j=0;j<BPS;j++)
      #pragma unroll
      for(int k=0;k<2;k++)
        #pragma unroll
        for(int m=0;m<MT;m++) wg32_pu(acc[m],da+(j*MT+m)*256+k*16,db+j*128+k*64,kb|j|k);
    wg_commit();
    if(kb>0){ wg_wait<1>(); if(lane==0) mbar_arrive(sb+W_BAR+32+pst*8); }
    pst=st;
  }
  wg_wait<0>();
  if(lane==0) mbar_arrive(sb+W_BAR+32+pst*8);
  const uint32_t wa=sb+W_SLOT+((lane>>4)*8+(lane&7))*128+(((2*wq+((lane>>3)&1))^(lane&7))<<4);
  const uint32_t rd=sb+W_SLOT+(wq*8+(lane>>3))*128+(((lane&7)^(lane>>3))<<4);
  #pragma unroll
  for(int m=0;m<2;m++){
    mbar_wait(sb+W_BAR+96+wg*16+m*8,e0);
    if(m*H0<MT){
      #pragma unroll
      for(int j=0;j<H0&&m*H0+j<MT;j++){ const float* q=acc[m*H0+j<MT?m*H0+j:0];
        #pragma unroll
        for(int i=0;i<2;i++) stsm4t(wa+m*SLOT+j*4096+i*2048,pack_bf16(q[8*i],q[8*i+1]),pack_bf16(q[8*i+2],q[8*i+3]),pack_bf16(q[8*i+4],q[8*i+5]),pack_bf16(q[8*i+6],q[8*i+7])); }
      if(NS==1) ldx(m);
      bar_sync(8+wg,128);
      #pragma unroll
      for(int j=0;j<H0&&m*H0+j<MT;j++)
        #pragma unroll
        for(int i=0;i<2;i++){
          const uint4 u=lds4((rd^(i*64))+m*SLOT+j*4096+i*512), x=xx[m*H0+j<MT?m*H0+j:0][i], g=gg[m*H0+j<MT?m*H0+j:0][i];
          stg_h4(P.out+go+i*4*D+(m*H0+j)*64,fin1(u.x,x.x,g.x),fin1(u.y,x.y,g.y),fin1(u.z,x.z,g.z),fin1(u.w,x.w,g.w));
        }
    }
    bar_arrive(sq,160); sq^=1;
  }
  e0^=1;
}
template<int N,int MODE> __device__ __forceinline__ void gemm_item(const WParams& P,int type,int rbk,int a,uint32_t pos,uint32_t sb,int tid,uint32_t ra,uint32_t& e0,uint32_t& eb,int& sq){
  const int lane=tid&31, wg=tid>>7;
  const uint32_t E0=sb+W_BAR+96+wg*16;
  float acc[192];
  mainloop<N,MODE==0,0>(acc,(MODE&&type==T_M2)?24:10,sb,lane,pos);
  uint32_t p[2][N/4];
  #pragma unroll
  for(int m=0;m<2;m++)
    #pragma unroll
    for(int i=0;i<N/4;i++) p[m][i]=pack_bf16(acc[96*m+2*i],acc[96*m+2*i+1]);
  const float c1=type==T_M1?-2.302208198144325f:-1.4426950408889634f, c3=type==T_M1?-0.10294323958f:0.f;
  const int wq=(tid>>5)&3;
  if(MODE&&type!=T_KV){ mbar_wait(sb+W_BAR+224+wg*8,eb); eb^=1; }
  #pragma unroll
  for(int m=0;m<2;m++){
    mbar_wait(E0+m*8,e0);
    stage_pk<N/16>(p[m],ra+m*SLOT,lane);
    if(MODE&&type!=T_KV) post_pass(sb+W_SLOT+m*SLOT+wq*2048,N/64,sb+W_BAR+256+wg*384,c1,c3);
    fence_async();
    bar_arrive(sq,160); sq^=1;
  }
  e0^=1;
}
__device__ __forceinline__ int n_it(int c,int r){ return c==T_OP?4*nsp(r):(c==T_QA?32:(c==T_M2?4:(r?0:(c==T_M1?128:(c==T_KV?(1024-KVUP)/2:0))))); }
__device__ __forceinline__ void flag_wait(int rbk,int a,int lane){
  const uint32_t need=4*rbk+4; const uint32_t* f=g_flag+a*96+(lane%3)*32; int gd=0;
  while(!__all_sync(~0u,lane>2||ld_acq(f)>=need)){ __nanosleep(FNS); if(++gd>WGUARD){ g_err=22; break; } }
}
__device__ __forceinline__ void cnt_wait(int c,uint32_t thr){
  int gd=0;
  while(ld_acq(g_cnt+c)<thr){ __nanosleep(40); if(++gd>WGUARD){ g_err=23; break; } }
}
template<int MODE>
__global__ void __launch_bounds__(384,1) k_work(const __grid_constant__ WParams P){
  extern __shared__ __align__(1024) uint8_t sm[];
  const uint32_t sb=(uint32_t)__cvta_generic_to_shared(sm);
  const int tid=threadIdx.x, warp=__shfl_sync(~0u,tid>>5,0), lane=tid&31;
  const uint32_t FULL=sb+W_BAR, EMPTY=sb+W_BAR+32, IFULL=sb+W_BAR+64, IEMPTY=sb+W_BAR+80, EF=sb+W_BAR+96, REQ=sb+W_BAR+128, TOK=sb+W_BAR+136;
  volatile int* idesc=(volatile int*)(sm+W_BAR+160);
  if(tid==352) ST(0);
  if(tid==0){
    for(int i=0;i<NST;i++){ mbar_init(FULL+i*8,1); mbar_init(EMPTY+i*8,MODE?4:8); mbar_init(EF+i*8,1); }
    for(int i=0;i<2;i++){ mbar_init(IFULL+i*8,1); mbar_init(IEMPTY+i*8,6); mbar_init(sb+W_BAR+224+i*8,1); }
    mbar_init(REQ,1); mbar_init(TOK,1); mbar_init(sb+W_BAR+144,1);
    if(MODE==0){ mbar_init(sb+W_BAR+240,1); mbar_init(sb+W_BAR+248,1); uint32_t sm_; asm volatile("mov.u32 %0, %%smid;":"=r"(sm_)); idesc[6]=sm_; }
    asm volatile("fence.mbarrier_init.release.cluster;":::"memory");
  }
  __syncthreads();
  #define S0(i)
  S0(0)
  if(MODE==0){ cluster_sync(); S0(1) asm volatile("griddepcontrol.wait;":::"memory"); asm volatile("griddepcontrol.launch_dependents;"); }
  S0(2)
  if(warp>=8){
    asm volatile("setmaxnreg.dec.sync.aligned.u32 40;");
    if(warp==11){
      uint32_t it=0, pos=0;
      int guard=0; bool fin=false;
      const int cl=lane>>2, cj=lane&3;
      int sidx=MODE?-1:blockIdx.x; int nit=0;
      if(lane==0) ST(1);
      while(true){
        int type=T_END, rbk=0, a=0, erl=0;
        if(!fin){
          if(it) mbar_wait(REQ,(it&1)^1);
          if(MODE==0){
            const uint32_t i0=blockIdx.x<128?KVR:0;
            if(it<i0){ type=T_KV; a=it*128+((blockIdx.x+(it>=ROT0?(it-ROT0+1)*ROT:0))&127); }
            else {
              const uint32_t mb=sb+W_BAR+240+(it&1)*8;
              int tk=4096;
              if(blockIdx.x&1){
                int gd=0; while(!mbar_try_cl(mb,((it-i0)>>1)&1)){ if(++gd>WGUARD){ g_err=24; break; } }
                tk=idesc[(it&1)*8+7];
              } else {
                if(it==i0){
                  uint32_t o; asm volatile("ld.shared::cluster.u32 %0, [%1];":"=r"(o):"r"(mapa(sb+W_BAR+160+24,1)):"memory");
                  const uint32_t m=idesc[6]; uint32_t q=KVQ+KVR-i0;
                  #pragma unroll
                  for(int i=0;i<3;i++){ const uint32_t v=ld_rlx(g_sml+lane+32*i); if(v==m||v==o) q=min(q,KVR-i0+(lane+32*i<3*KVJ?0:1)); }
                  sidx=__reduce_min_sync(~0u,q);
                }
                if(lane==0){
                  if(sidx--) tk=(int)atomicAdd(g_cnt+C_NEXT+T_KV*32,1u);
                  asm volatile("st.shared::cluster.u32 [%0], %1;\nmbarrier.arrive.release.cluster.shared::cluster.b64 _, [%2];"::"r"(mapa(sb+W_BAR+160+(it&1)*32+28,1)),"r"(tk),"r"(mapa(mb,1)):"memory");
                }
                tk=__shfl_sync(~0u,tk,0);
              }
              if(tk<n_it(T_KV,0)){ type=T_KV; a=KVUP+2*tk+(blockIdx.x&1); }
            }
          }
          else if(sidx>=0){ type=T_KV; a=sidx; sidx=-1; }
          else {
            while(true){
              const uint4 nx=ldg_rlx4(g_cnt+C_NEXT+cl*32+cj*4);
              int cand=(int)nx.x<n_it(cl,4*cj)?4*cj*4096+nx.x:((int)nx.y<n_it(cl,4*cj+1)?(4*cj+1)*4096+nx.y:((int)nx.z<n_it(cl,4*cj+2)?(4*cj+2)*4096+nx.z:((int)nx.w<n_it(cl,4*cj+3)?(4*cj+3)*4096+nx.w:65536)));
              cand=min(cand,__shfl_xor_sync(~0u,cand,1)); cand=min(cand,__shfl_xor_sync(~0u,cand,2));
              const int cr=cand>>12, ca=cand&4095, qr=__shfl_sync(~0u,cr,4*T_QA);
              const bool has=cr<NRB;
              if(lane==0&&nit==0) ST(5);
              const uint32_t* fp=nullptr; uint32_t thr=0, sl1=0; bool only1=false, no1=cl>=T_M2;
              if(has&&cl<=T_M2){
                if(cl==T_QA){ if(cj<3){ fp=g_flag+ca*96+cj*32; thr=4*cr+4; sl1=cr==NRB-1?E15:EARLY; } else { fp=g_cnt+C_KV+min(cr+1,NRB-1); thr=64; only1=true; } }
                else if(cj==0){ fp=g_cnt+(cl==T_OP?C_QA:C_M1)+cr; thr=cl==T_OP?32:8; sl1=thr; }
                else if(cj==1){ if(cl==T_OP){ fp=g_cnt+C_M2+cr; thr=4; } if(cr<OPE||qr<=cr) no1=true; }
              }
              __syncwarp();
              if(lane==0&&nit==0) ST(2);
              uint32_t v=0; if(fp) v=ld_acq(fp);
              __syncwarp();
              if(lane==0&&nit==0) ST(3+(v&0));
              nit++;
              uint32_t b2=__ballot_sync(~0u,has&&(v>=thr||only1)), b1=__ballot_sync(~0u,has&&!no1&&v+sl1>=thr);
              b2&=b2>>1; b2&=b2>>2; b1&=b1>>1; b1&=b1>>2;
              b2&=0x111111u; b1&=0x111u;
              if(!__ballot_sync(~0u,has)) break;
              if(b2|b1){
                const int rs=(int)__shfl_sync(~0u,v,4*T_QA);
                const uint32_t bu=__ballot_sync(~0u,cl<=T_QA||qr>=NRB||(cl==T_KV?2*((2*ca+KVUP)>>7)<=(rs>>2)+KLEAD:(cl==T_M1?ca>>3:cr)<=qr+MLEAD));
                int got=-1;
                while(got<0&&(b2|b1)){
                  uint32_t bb=(b2&bu)?(b2&bu):(b1?b1:b2);
                  if(Q15&&(((b1|b2)>>(4*T_QA))&1)&&qr>=NRB-Q15) bb=1u<<(4*T_QA);
                  #define RD(c) ((bb>>(4*(c)))&1)
                  const int w=RD(T_KV)?T_KV:(RD(T_M2)?T_M2:(RD(T_M1)?T_M1:(RD(T_OP)?T_OP:T_QA)));
                  if(lane==4*w){ const int tk=(int)atomicAdd(g_cnt+C_NEXT+cl*32+cr,1u); if(tk<n_it(cl,cr)) got=cr*4096+(cl==T_KV?KVUP+2*tk:tk)+(tk!=ca?65536:0); }
                  got=__shfl_sync(~0u,got,4*w);
                  if(got>=0){ type=w; rbk=(got>>12)&15; a=got&4095; if(w==T_KV) sidx=a+1; erl=!((b2>>(4*w))&1)||(w==T_QA&&got>=65536); }
                  b2&=~(1u<<(4*w)); b1&=~(1u<<(4*w));
                }
                if(got>=0) break;
              } else {
                __nanosleep(100);
                if(++guard>WGUARD){ g_err=21; break; }
              }
            }
          }
        }
        __syncwarp();
        if(lane==0){
          const uint32_t sl=it&1;
          int idx=0;
          if(type==T_KV){ rbk=2*(a>>7)+(a&1); a=(a>>1)&63; }
          if(type==T_M1){ rbk=a>>3; a&=7; }
          mbar_wait(IEMPTY+sl*8,((it>>1)&1)^1);
          idesc[sl*8]=type; idesc[sl*8+1]=rbk; idesc[sl*8+2]=a; idesc[sl*8+3]=pos; idesc[sl*8+4]=idx; idesc[sl*8+5]=erl;
          mbar_arrive(IFULL+sl*8);
          pos+=type==T_M2?24:(type==T_OP?pu_st(nsp(rbk)):10);
        }
        __syncwarp();
        if(MODE==0&&it>=WPF&&it<WPF+WPN){
          constexpr int NC=WPC, NI=(NC/132+WPN)/WPN;
          uint32_t acc=0;
          #pragma unroll 2
          for(int i=0;i<NI;i++){
            const int ci=((it-WPF)*NI+i)*132+blockIdx.x;
            if(ci<NC){
              const char* p=(const char*)((ci<1920)==(WPS==0)?P.wo:P.wq)+(size_t)(ci<1920?ci:ci-1920)*4096+lane*128;
              if(WPM==0) asm volatile("prefetch.global.L2 [%0];"::"l"(p):"memory");
              else { uint32_t v; asm volatile("ld.global.L1::no_allocate.L2::128B.u32 %0, [%1];":"=r"(v):"l"(p):"memory"); acc|=v; }
            }
          }
          if(WPM&&acc==0x12345678u&&guard==77) g_err=1;
        }
        it++;
        if(type==T_END){ if(fin) break; fin=true; }
      }
    } else if(warp==8){
      if(lane==0){
        uint32_t st=0, ph=1;
        for(uint32_t it=0;;it++){
          const uint32_t sl=it&1;
          mbar_wait(IFULL+sl*8,(it>>1)&1);
          const int type=idesc[sl*8], rbk=idesc[sl*8+1], a=idesc[sl*8+2], erl=idesc[sl*8+5];
          mbar_arrive(IEMPTY+sl*8);
          if(type==T_END) break;
          if(MODE&&type==T_OP){
            const int ns=nsp(rbk), nkb=pu_st(ns), bps=40/nkb, ub=40960/ns, seg=rbk*4+a/ns, trig=rbk>=LATE?nkb-1:max(nkb-TRIG,0);
            const uint8_t* pp=g_p+seg*81920; const CUtensorMap* um=&P.m[ns==1?M_U1:(ns==2?M_U2:(ns==5?M_U5:M_U10))]; const int c1=(a%ns)*(20/ns);
            if(erl) cnt_wait(C_QA+rbk,32);
            FAG();
            for(int kb=0;kb<nkb;kb++){
              mbar_wait(EMPTY+st*8,ph);
              const uint32_t d=sb+st*STG, fb=FULL+st*8;
              mbar_expect(fb,bps*(ub+2048));
              asm volatile("cp.async.bulk.tensor.3d.shared::cluster.global.mbarrier::complete_tx::bytes.L2::cache_hint [%0], [%1, {0, %3, %4}], [%2], %5;"::"r"(d),"l"(um),"r"(fb),"r"(c1),"r"((XU?(seg&3):seg)*40+kb*bps),"l"(HU?PL_EF:PL_EN):"memory");
              bulk_g2s(d+bps*ub,pp,bps*2048,fb); pp+=bps*2048;
              if(kb==trig) mbar_arrive(REQ);
              if(++st==NST){ st=0; ph^=1; }
            }
            continue;
          }
          int ma=M_XN,mb,col0=a*192,k0=0,nkb=10,nbox=3; const int row0=rbk*128;
          if(MODE==0||type==T_KV){ mb=a<32?M_WK:M_WV; col0=(a&31)*192; }
          else if(type==T_M1){ ma=M_Y; mb=M_W1; }
          else if(type==T_QA){ mb=M_WQ; }
          else {
            const int nt=a&3; col0=nt<2?nt*192:128+nt*128; nbox=nt<2?3:2;
            ma=M_H; mb=M_W2; nkb=24;
          }
          if(MODE) FAG();
          const CUtensorMap* A=&P.m[ma]; const CUtensorMap* B=&P.m[mb]; const unsigned long long pa=(MODE&&(((HX&32)&&type==T_M2)||((HX&64)&&type==T_M1)))?PL_EF:PL_EN;
          const int trig=(MODE&&type<=T_QA&&rbk>=LATE)?nkb-1:max(nkb-TRIG,0);
          for(int kb=0;kb<nkb;kb++){
            mbar_wait(EMPTY+st*8,ph);
            const uint32_t d=sb+st*STG, fb=FULL+st*8;
            mbar_expect(fb,(MODE==0&&XA)?(XA==1?32768:16384+8192*(XA==2?3:1)-(XA==2?8192:0)):16384+((MODE&&XB)?XB:nbox)*8192);
            const int kk=k0+kb*64;
            tma2dh(d,A,kk,row0,fb,pa); if(!(MODE==0&&XA==2)) tma2dh(d+8192,A,kk,row0+64,fb,pa);
            if(MODE==0){
              const int r=rbk&1, j=2*r;
              if(XA!=3) tma2dm(d+16384+j*8192,B,col0+j*64,kk,fb);
              if(XA!=1) if((kb&1)==r) tma2dm(d+24576,B,col0+64,kk,fb);
            }
            else for(int j=0;j<(XB?XB:nbox);j++) tma2d(d+16384+j*8192,B,col0+j*64,kk,fb);
            if(kb==trig) mbar_arrive(REQ);
            if(++st==NST){ st=0; ph^=1; }
          }
        }
      }
      __syncwarp();
    } else if(warp<11){
      const int wg=warp-9;
      const uint32_t S0=sb+W_SLOT, E0=EF+wg*16; int sq=4+2*wg;
      for(uint32_t it=wg;;it+=2){
        mbar_wait(IFULL+wg*8,(it>>1)&1);
        const int type=idesc[wg*8], rbk=idesc[wg*8+1], a=idesc[wg*8+2], erl=idesc[wg*8+5];
        __syncwarp();
        if(lane==0) mbar_arrive(IEMPTY+wg*8);
        if(type==T_END) break;
        const int row0=rbk*128;
        int map=-1,col0=a*192,nbox=3,cnt=-1;
        if(MODE==0||type==T_KV){ map=a<32?M_K:M_V; col0=(a&31)*192; cnt=C_KV+rbk; }
        else if(type==T_M1){ map=M_H; cnt=C_M1+rbk; }
        else if(type==T_M2){ const int nt=a&3; col0=nt<2?nt*192:128+nt*128; nbox=nt<2?3:2; map=M_GATE; cnt=C_M2+rbk; }
        else if(type==T_OP) map=M_OUT;
        if(MODE&&(type==T_M1||type==T_M2)&&lane==0){ const uint32_t bb=sb+W_BAR+224+wg*8; mbar_expect(bb,nbox*128); bulk_g2s(sb+W_BAR+256+wg*384,(type==T_M1?P.b1:P.b2)+col0,nbox*128,bb); }
        const char* kp=(const char*)g_km+(uint32_t)(rbk*393216+a*3072);
        if(KPF&&MODE&&map<0){
          if(lane<6) tma2d_pfh(&P.m[M_K],col0+(lane>>1)*64,row0+(lane&1)*64,HQ&2?PL_EF:PL_EN);
          if(!erl&&lane<4) asm volatile("cp.async.bulk.prefetch.L2.global [%0], 3072;"::"l"(kp+lane*98304):"memory");
          __syncwarp();
        }
        if(it&&lane==0) mbar_wait(TOK,(it&1)^1);
        if(MODE&&map<0){
          if(lane==0){
            FAG();
            for(int m=0;m<2;m++){
              mbar_expect(E0+m*8,SLOT);
              for(int j=0;j<3;j++) tma2dh(S0+m*SLOT+j*BOXS,&P.m[M_K],col0+j*64,row0+m*64,E0+m*8,HQ?PL_EF:PL_EN);
            }
            mbar_expect(sb+W_BAR+224+wg*8,12288);
          }
          if(erl){ __syncwarp(); flag_wait(rbk,a,lane); FAG(); }
          { __syncwarp(); bar_sync(sq,160); sq^=1; }
          if(lane==0){ for(int j=0;j<4;j++) bulk_g2s(S0+j*3072,kp+j*98304,3072,sb+W_BAR+224+wg*8); }
          { __syncwarp(); bar_sync(sq,160); sq^=1; }
          if(lane==0) mbar_arrive(TOK);
          { __syncwarp(); bar_sync(sq,160); sq^=1; } if(lane==0) red_rel(g_cnt+C_QA+rbk);
        } else if(MODE&&map==M_OUT){
          if(lane==0){ mbar_arrive(E0); mbar_arrive(E0+8); }
          { __syncwarp(); bar_sync(sq,160); sq^=1; }
          { __syncwarp(); bar_sync(sq,160); sq^=1; }
          if(lane==0) mbar_arrive(TOK);
        } else {
          if(lane==0){ mbar_arrive(E0); mbar_arrive(E0+8); }
          for(int m=0;m<2;m++){
            { __syncwarp(); bar_sync(sq,160); sq^=1; }
            if(lane==0){
              if(MODE?(((HX&16)&&type==T_KV)||((HX&4)&&type==T_M2)||((HX&8)&&type==T_M1)):rbk>=KEF){ for(int j=0;j<nbox;j++) tma_st_ef(&P.m[map],S0+m*SLOT+j*BOXS,col0+j*64,row0+m*64); }
              else for(int j=0;j<nbox;j++) tma_st(&P.m[map],S0+m*SLOT+j*BOXS,col0+j*64,row0+m*64);
              bulk_commit();
            }
          }
          if(lane==0){
            bulk_wait_rd(); mbar_arrive(TOK);
            bulk_wait(); FAG(); red_rel(g_cnt+cnt);
          }
        }
        __syncwarp();
      }
      if(lane==0) bulk_wait();
    }
  } else {
    asm volatile("setmaxnreg.inc.sync.aligned.u32 232;");
    const int wg=warp>>2, wq=warp&3, g=lane>>2, t=lane&3;
    const uint32_t E0=EF+wg*16;
    const uint32_t ra=sb+W_SLOT+(16*wq+(lane&7)+((lane>>3)&1)*8)*128;
    uint32_t e0=0, eb=0; int sq=4+2*wg;
    #pragma unroll 1
    for(uint32_t it=0;;it++){
      mbar_wait(IFULL+wg*8,it&1);
      const int type=idesc[wg*8], rbk=idesc[wg*8+1], a=idesc[wg*8+2]; const uint32_t pos=idesc[wg*8+3];
      __syncwarp();
      if(lane==0) mbar_arrive(IEMPTY+wg*8);
      if(type==T_END) break;
      mbar_wait(sb+W_BAR+144,wg^1);
      if(MODE&&type==T_OP){
        const int ns=nsp(rbk);
        if(ns_used(1)&&ns==1) pu_item<1>(P,rbk,a,pos,sb,tid,e0,sq);
        if(ns_used(2)&&ns==2) pu_item<2>(P,rbk,a,pos,sb,tid,e0,sq);
        if(ns_used(5)&&ns==5) pu_item<5>(P,rbk,a,pos,sb,tid,e0,sq);
        if(ns_used(10)&&ns==10) pu_item<10>(P,rbk,a,pos,sb,tid,e0,sq);
      } else {
        if(MODE==0||type!=T_QA){
          if(MODE==0||type>=T_M1||(a&3)<2) gemm_item<192,MODE>(P,type,rbk,a,pos,sb,tid,ra,e0,eb,sq); else gemm_item<128,MODE>(P,type,rbk,a,pos,sb,tid,ra,e0,eb,sq);
        } else {
          float acc[192];
          QT(0);
          mainloop<192,0,0>(acc,10,sb,lane,pos);
          QT(1);
          const int sgl=wq>>1, rh=wq&1;
          {
            uint32_t q[96];
            float s[2][16], sm[2][8];
            #pragma unroll
            for(int i=95;i>=0;i--) q[i]=pack_bf16(acc[2*i],acc[2*i+1]);
            QT(2);
            #pragma unroll
            for(int m=0;m<2;m++){
              const uint32_t dk=((sb+W_SLOT+m*SLOT)>>4)|(1u<<16);
              float u[32];
              mbar_wait(E0+m*8,e0);
              #pragma unroll
              for(int i=0;i<32;i++) u[i]=0.f;
              wg_arrive();
              #pragma unroll
              for(int T=0;T<12;T++) wgmma_rs<64>(u,q+48*m+4*T,dk+(T>>2)*(BOXS/16)+(T&3)*2,T);
              wg_commit();
              wg_wait<0>();
              if(m==0){ bar_arrive(sq,160); sq^=1; }
              #pragma unroll
              for(int i=0;i<16;i++) s[m][i]=sgl?u[16+i]:u[i];
            }
            QT(3);
            mbar_wait(sb+W_BAR+224+wg*8,eb); eb^=1;
            #pragma unroll
            for(int i=0;i<16;i++) sm[i>>3][i&7]=0.f;
            wg_arrive();
            #pragma unroll
            for(int T=0;T<12;T++)
              #pragma unroll
              for(int m=0;m<2;m++) wg16_rs(sm[m],q+48*m+4*T,(((sb+W_SLOT)>>4)|(8u<<16))+m*384+T*16,T);
            wg_commit();
            wg_wait<0>();
            bar_arrive(sq,160); sq^=1;
            QT(4);
            const float NEG=rb(-1e9f);
            #pragma unroll
            for(int m=0;m<2;m++){
              float sc[5][4];
              float mx[2]={-3.4e38f,-3.4e38f};
              #pragma unroll
              for(int n=0;n<5;n++)
                #pragma unroll
                for(int i=0;i<4;i+=2){
                  const float u0=n?s[m][n?4*n-4+i:0]:(sgl?sm[m][4+i]:sm[m][i]);
                  const float u1=n?s[m][n?4*n-3+i:0]:(sgl?sm[m][5+i]:sm[m][i+1]);
                  const uint32_t r=pack_bf16(u0,u1);
                  const uint32_t w=pack_bf16(__uint_as_float(r<<16)*0.07216878364870322f,__uint_as_float(r&0xffff0000u)*0.07216878364870322f);
                  float v0=__uint_as_float(w<<16), v1=__uint_as_float(w&0xffff0000u);
                  if(n>0){ const int key=8*(n-1)+2*t, row=16*rh+g+4*i; if(key>row) v0=NEG; if(key+1>row) v1=NEG; }
                  sc[n][i]=v0; sc[n][i+1]=v1; mx[i>>1]=fmaxf(mx[i>>1],fmaxf(v0,v1));
                }
              float sum[2]={0.f,0.f};
              #pragma unroll
              for(int r=0;r<2;r++){ mx[r]=fmaxf(mx[r],__shfl_xor_sync(~0u,mx[r],1)); mx[r]=fmaxf(mx[r],__shfl_xor_sync(~0u,mx[r],2)); }
              #pragma unroll
              for(int n=0;n<5;n++)
                #pragma unroll
                for(int i=0;i<4;i++){ const float e=ex2((sc[n][i]-mx[i>>1])*1.4426950408889634f); sc[n][i]=e; sum[i>>1]+=e; }
              #pragma unroll
              for(int r=0;r<2;r++){ sum[r]+=__shfl_xor_sync(~0u,sum[r],1); sum[r]+=__shfl_xor_sync(~0u,sum[r],2); sum[r]=rcp(sum[r]); }
              uint8_t* pd=g_p+(uint32_t)((rbk*4+m*2+sgl)*81920+rh*256+lane*4);
              #pragma unroll
              for(int n=0;n<5;n++){
                uint8_t* q=pd+(n?a*2048+(n-1)*512:(32+(a>>2))*2048+(a&3)*512);
                stg1(q,pack_bf16(sc[n][0]*sum[0],sc[n][1]*sum[0])); stg1(q+128,pack_bf16(sc[n][2]*sum[1],sc[n][3]*sum[1]));
              }
            }
          }
          QT(5);
          bar_arrive(sq,160); sq^=1;
          e0^=1;
        }
      }
    }
  }
  if(MODE==0) cluster_sync();
}
typedef CUresult (*EncFn)(CUtensorMap*,CUtensorMapDataType,cuuint32_t,void*,const cuuint64_t*,const cuuint64_t*,const cuuint32_t*,const cuuint32_t*,CUtensorMapInterleave,CUtensorMapSwizzle,CUtensorMapL2promotion,CUtensorMapFloatOOBfill);
static EncFn enc(){
  static EncFn fn=nullptr;
  if(!fn){ void* p=nullptr; cudaDriverEntryPointQueryResult qr; cudaGetDriverEntryPoint("cuTensorMapEncodeTiled",&p,cudaEnableDefault,&qr); fn=(EncFn)p; }
  return fn;
}
static CUtensorMap mku(const void* base,uint32_t b1,uint32_t b2){
  CUtensorMap m; cuuint64_t gd[3]={256,20,NSEG*40}; cuuint64_t gs[2]={2048,40960}; cuuint32_t bd[3]={256,b1,b2}; cuuint32_t es[3]={1,1,1};
  enc()(&m,CU_TENSOR_MAP_DATA_TYPE_FLOAT64,3,(void*)base,gd,gs,bd,es,CU_TENSOR_MAP_INTERLEAVE_NONE,CU_TENSOR_MAP_SWIZZLE_NONE,CU_TENSOR_MAP_L2_PROMOTION_L2_128B,CU_TENSOR_MAP_FLOAT_OOB_FILL_NONE);
  return m;
}
static CUtensorMap mk2d(const void* base,uint64_t cols,uint64_t rows,uint32_t bc,uint32_t br){
  EncFn fn=enc();
  CUtensorMap m; cuuint64_t gd[2]={cols,rows}; cuuint64_t gs[1]={cols*2}; cuuint32_t bd[2]={bc,br}; cuuint32_t es[2]={1,1};
  fn(&m,CU_TENSOR_MAP_DATA_TYPE_BFLOAT16,2,(void*)base,gd,gs,bd,es,CU_TENSOR_MAP_INTERLEAVE_NONE,bc==32?CU_TENSOR_MAP_SWIZZLE_64B:CU_TENSOR_MAP_SWIZZLE_128B,CU_TENSOR_MAP_L2_PROMOTION_L2_128B,CU_TENSOR_MAP_FLOAT_OOB_FILL_NONE);
  return m;
}
static CUtensorMap mkw(const void* base){
  CUtensorMap m; cuuint64_t gd[3]={HD,D/2,2}; cuuint64_t gs[2]={HD*4,HD*2}; cuuint32_t bd[3]={64,8,2}; cuuint32_t es[3]={1,1,1};
  enc()(&m,CU_TENSOR_MAP_DATA_TYPE_BFLOAT16,3,(void*)base,gd,gs,bd,es,CU_TENSOR_MAP_INTERLEAVE_NONE,CU_TENSOR_MAP_SWIZZLE_128B,CU_TENSOR_MAP_L2_PROMOTION_L2_128B,CU_TENSOR_MAP_FLOAT_OOB_FILL_NONE);
  return m;
}
template<class T> static T* sym(T& s){ void* p; cudaGetSymbolAddress(&p,s); return (T*)p; }
}

#define XPQ Wq
#define XPO Wo
int g_reconly=0; int g_kvgrid=132;
extern "C" void kernel_launch(void* const* d_in, const int* in_sizes, int n_in, void* d_out, int out_size) {
  using namespace rk;
  const bf16* x=(const bf16*)d_in[0]; const bf16* mem0=(const bf16*)d_in[1];
  const bf16* Wq=(const bf16*)d_in[2]; const bf16* Wk=(const bf16*)d_in[3]; const bf16* Wv=(const bf16*)d_in[4]; const bf16* Wo=(const bf16*)d_in[5];
  const bf16* w1=(const bf16*)d_in[8]; const bf16* b1=(const bf16*)d_in[9]; const bf16* w2=(const bf16*)d_in[10]; const bf16* b2=(const bf16*)d_in[11];
  cudaStream_t st=cudaStreamPerThread;
  cudaFuncSetAttribute(k_rec,cudaFuncAttributeMaxDynamicSharedMemorySize,SM_TOTAL);
  cudaFuncSetAttribute(k_work<0>,cudaFuncAttributeMaxDynamicSharedMemorySize,W_TOTAL);
  cudaFuncSetAttribute(k_work<1>,cudaFuncAttributeMaxDynamicSharedMemorySize,W_TOTAL);
  bf16* k=(bf16*)sym(g_k); bf16* v=(bf16*)sym(g_v);
  WParams P;
  P.m[M_XN]=mk2d(sym(g_xn),D,S,64,64); P.m[M_Y]=mk2d(sym(g_y),D,S,64,64); P.m[M_H]=mk2d(sym(g_h),F,S,64,64);
  P.m[M_K]=mk2d(k,HD,S,64,64); P.m[M_V]=mk2d(v,HD,S,64,64); P.m[M_GATE]=mk2d(sym(g_gate),D,S,64,64);
  P.m[M_WQ]=mk2d(Wq,HD,D,64,64); P.m[M_WK]=mk2d(Wk,HD,D,64,64); P.m[M_WV]=mk2d(Wv,HD,D,64,64);
  P.m[M_W1]=mk2d(w1,F,D,64,64); P.m[M_W2]=mk2d(w2,D,F,64,64);
  P.m[M_U1]=mku(sym(g_u),20,1); P.m[M_U2]=mku(sym(g_u),10,2); P.m[M_U5]=mku(sym(g_u),4,4); P.m[M_U10]=mku(sym(g_u),2,5);
  P.x=x; P.b1=b1; P.b2=b2; P.out=(bf16*)d_out; P.wq=Wq; P.wo=Wo;
  cudaFuncSetAttribute(k_pre,cudaFuncAttributeMaxDynamicSharedMemorySize,SM_TOTAL);
  {
    cudaLaunchConfig_t cfg={}; cfg.gridDim=dim3(NCTA); cfg.blockDim=dim3(PRE_T); cfg.dynamicSmemBytes=SM_TOTAL; cfg.stream=st;
    cudaLaunchAttribute at[1]; at[0].id=cudaLaunchAttributeClusterDimension; at[0].val.clusterDim.x=3; at[0].val.clusterDim.y=1; at[0].val.clusterDim.z=1; cfg.attrs=at; cfg.numAttrs=1;
    cudaLaunchKernelEx(&cfg,k_pre,x,mem0);
  }
  if(!(g_reconly&1)){
    cudaLaunchConfig_t cfg={}; cfg.gridDim=dim3(g_kvgrid); cfg.blockDim=dim3(384); cfg.dynamicSmemBytes=W_TOTAL; cfg.stream=st;
    cudaLaunchAttribute at[2]; at[0].id=cudaLaunchAttributeClusterDimension; at[0].val.clusterDim.x=2; at[0].val.clusterDim.y=1; at[0].val.clusterDim.z=1;
    at[1].id=cudaLaunchAttributeProgrammaticStreamSerialization; at[1].val.programmaticStreamSerializationAllowed=1; cfg.attrs=at; cfg.numAttrs=2;
    cudaLaunchKernelEx(&cfg,k_work<0>,P);
  }
  if(!(g_reconly&4)){
    cudaLaunchConfig_t cfg={}; cfg.gridDim=dim3(NCTA); cfg.blockDim=dim3(256); cfg.dynamicSmemBytes=SM_TOTAL; cfg.stream=st;
    cudaLaunchAttribute at[2]; at[0].id=cudaLaunchAttributeClusterDimension; at[0].val.clusterDim.x=3; at[0].val.clusterDim.y=1; at[0].val.clusterDim.z=1;
    at[1].id=cudaLaunchAttributeProgrammaticStreamSerialization; at[1].val.programmaticStreamSerializationAllowed=1; cfg.attrs=at; cfg.numAttrs=2;
    RParams R; R.k=mk2d(k,HD,S,64,32); R.v=mk2d(v,HD,S,64,32); R.w[0]=mkw(XPQ); R.w[1]=mkw(Wk); R.w[2]=mkw(Wv); R.w[3]=mk2d(XPO,D,HD,32,32); R.wq=(const char*)XPQ; R.wo=(const char*)XPO;
    cudaLaunchKernelEx(&cfg,k_rec,R,0u);
  }
  if(!(g_reconly&2)){
    cudaLaunchConfig_t cfg={}; cfg.gridDim=dim3(132); cfg.blockDim=dim3(384); cfg.dynamicSmemBytes=W_TOTAL; cfg.stream=st;
    cudaLaunchAttribute at[1]; at[0].id=cudaLaunchAttributeProgrammaticStreamSerialization; at[0].val.programmaticStreamSerializationAllowed=1; cfg.attrs=at; cfg.numAttrs=PDL;
    cudaLaunchKernelEx(&cfg,k_work<1>,P);
  }
}
```

```cpp
#include <cuda_runtime.h>
#include <cuda_bf16.h>
#include <stdint.h>
#include <cuda.h>

namespace rk {
typedef __nv_bfloat16 bf16;
constexpr int S=2048, D=640, H=32, DH=192, HD=6144, NSEG=64, F=1536;
constexpr uint32_t SENT=0xFFFFFFFFu;
#define GUARDN 400000
constexpr int GUARD=GUARDN;
constexpr int NCTA=96;

__device__ __align__(128) bf16 g_xn[S*D];
__device__ __align__(128) bf16 g_y[S*D];
__device__ __align__(128) bf16 g_h[S*F];
__device__ __align__(128) bf16 g_gate[S*D];
__device__ __align__(128) bf16 g_k[(size_t)S*HD];
__device__ __align__(128) bf16 g_v[(size_t)S*HD];
__device__ __align__(128) bf16 g_km[NSEG*8*HD];
__device__ __align__(128) uint32_t g_flag[NCTA*32];
__device__ __align__(1024) uint8_t g_u[(size_t)NSEG*40*40960];
__device__ __align__(1024) uint8_t g_p[(size_t)NSEG*40*2048];
#define NSTAB 0xAAA5522222222222ull
__host__ __device__ constexpr int nsp(int rb){ return (int)((NSTAB>>(4*rb))&15); }
__host__ __device__ constexpr bool ns_used(int n){ for(int r=0;r<16;r++) if(nsp(r)==n) return true; return false; }
constexpr int C_NEXT=0, C_KV=256, C_M1=272, C_M2=288, C_OP=304, C_QA=320, C_NUM=384;
__device__ __align__(128) uint32_t g_cnt[C_NUM];
#define PDL 1
__device__ __align__(1024) unsigned long long g_acc[NSEG*2560];
constexpr unsigned long long ACC_INIT=0ull-32ull*((0x5A000000ull<<32)+0xD0000000ull+1ull);
__device__ __align__(128) uint32_t g_nrm[NCTA*2+32];
__device__ int g_err;
__device__ unsigned long long g_gt[128*4];
#define GT(i) do{ if(threadIdx.x==0){ unsigned long long g0; asm volatile("mov.u64 %0, %%globaltimer;":"=l"(g0)); g_gt[blockIdx.x*4+(i)]=g0; } }while(0)

__device__ __forceinline__ float rb(float x){ return __bfloat162float(__float2bfloat16(x)); }
__device__ __forceinline__ uint32_t pack_bf16(float lo,float hi){ uint32_t r; asm("cvt.rn.bf16x2.f32 %0, %1, %2;":"=r"(r):"f"(hi),"f"(lo)); return r; }
__device__ __forceinline__ uint32_t movm(uint32_t a){ uint32_t d; asm volatile("movmatrix.sync.aligned.m8n8.trans.b16 %0, %1;":"=r"(d):"r"(a)); return d; }
__device__ __forceinline__ uint4 ldg_rlx4(const uint32_t* p){ uint4 v; asm volatile("ld.relaxed.gpu.global.v4.u32 {%0,%1,%2,%3}, [%4];":"=r"(v.x),"=r"(v.y),"=r"(v.z),"=r"(v.w):"l"(p):"memory"); return v; }
__device__ __forceinline__ void stg_rlx1(uint32_t* p,uint32_t a){ asm volatile("st.relaxed.gpu.global.u32 [%0], %1;"::"l"(p),"r"(a):"memory"); }
__device__ __forceinline__ void stg_rlx2(uint32_t* p,uint32_t a,uint32_t b){ asm volatile("st.relaxed.gpu.global.v2.u32 [%0], {%1,%2};"::"l"(p),"r"(a),"r"(b):"memory"); }
__device__ __forceinline__ void stg1(void* p,uint32_t a){ asm volatile("st.global.u32 [%0], %1;"::"l"(p),"r"(a):"memory"); }
__device__ __forceinline__ void stg4(void* p,uint32_t a,uint32_t b,uint32_t c,uint32_t d){ asm volatile("st.global.v4.u32 [%0], {%1,%2,%3,%4};"::"l"(p),"r"(a),"r"(b),"r"(c),"r"(d):"memory"); }
__device__ __forceinline__ void bar_sync(int id,int n){ asm volatile("bar.sync %0, %1;"::"r"(id),"r"(n):"memory"); }
__device__ __forceinline__ void bar_arrive(int id,int n){ asm volatile("bar.arrive %0, %1;"::"r"(id),"r"(n):"memory"); }
__device__ __forceinline__ void mma16816(float* d,const uint32_t* a,uint32_t b0,uint32_t b1){
  asm volatile("mma.sync.aligned.m16n8k16.row.col.f32.bf16.bf16.f32 {%0,%1,%2,%3},{%4,%5,%6,%7},{%8,%9},{%0,%1,%2,%3};"
   :"+f"(d[0]),"+f"(d[1]),"+f"(d[2]),"+f"(d[3]):"r"(a[0]),"r"(a[1]),"r"(a[2]),"r"(a[3]),"r"(b0),"r"(b1));
}
__device__ __forceinline__ void mma1688(float* d,uint32_t a0,uint32_t a1,uint32_t b0){
  asm volatile("mma.sync.aligned.m16n8k8.row.col.f32.bf16.bf16.f32 {%0,%1,%2,%3},{%4,%5},{%6},{%0,%1,%2,%3};"
   :"+f"(d[0]),"+f"(d[1]),"+f"(d[2]),"+f"(d[3]):"r"(a0),"r"(a1),"r"(b0));
}
__device__ __forceinline__ void ldsm4t(uint32_t* r,uint32_t addr){ asm volatile("ldmatrix.sync.aligned.m8n8.x4.trans.shared.b16 {%0,%1,%2,%3}, [%4];":"=r"(r[0]),"=r"(r[1]),"=r"(r[2]),"=r"(r[3]):"r"(addr):"memory"); }
__device__ __forceinline__ void ldsm4(uint32_t* r,uint32_t addr){ asm volatile("ldmatrix.sync.aligned.m8n8.x4.shared.b16 {%0,%1,%2,%3}, [%4];":"=r"(r[0]),"=r"(r[1]),"=r"(r[2]),"=r"(r[3]):"r"(addr):"memory"); }
__device__ __forceinline__ void stsm4(uint32_t a,uint32_t r0,uint32_t r1,uint32_t r2,uint32_t r3){ asm volatile("stmatrix.sync.aligned.m8n8.x4.shared.b16 [%0], {%1,%2,%3,%4};"::"r"(a),"r"(r0),"r"(r1),"r"(r2),"r"(r3):"memory"); }
__device__ __forceinline__ void stsm2(uint32_t a,uint32_t r0,uint32_t r1){ asm volatile("stmatrix.sync.aligned.m8n8.x2.shared.b16 [%0], {%1,%2};"::"r"(a),"r"(r0),"r"(r1):"memory"); }
__device__ __forceinline__ void cp16(uint32_t dst,const void* src){ asm volatile("cp.async.cg.shared.global [%0], [%1], 16;"::"r"(dst),"l"(src):"memory"); }
__device__ __forceinline__ void cp_wait_all(){ asm volatile("cp.async.wait_all;":::"memory"); }
__device__ __forceinline__ void fence_async(){ asm volatile("fence.proxy.async.shared::cta;":::"memory"); }
__device__ __forceinline__ void sts4f(uint32_t a,const float* v){ asm volatile("st.shared.v4.f32 [%0], {%1,%2,%3,%4};"::"r"(a),"f"(v[0]),"f"(v[1]),"f"(v[2]),"f"(v[3]):"memory"); }
__device__ __forceinline__ void sts4(uint32_t a,uint4 v){ asm volatile("st.shared.v4.u32 [%0], {%1,%2,%3,%4};"::"r"(a),"r"(v.x),"r"(v.y),"r"(v.z),"r"(v.w):"memory"); }
__device__ __forceinline__ void sts4r(uint32_t a,const uint32_t* v){ asm volatile("st.shared.v4.u32 [%0], {%1,%2,%3,%4};"::"r"(a),"r"(v[0]),"r"(v[1]),"r"(v[2]),"r"(v[3]):"memory"); }
__device__ __forceinline__ void sts2(uint32_t a,uint32_t x,uint32_t y){ asm volatile("st.shared.v2.u32 [%0], {%1,%2};"::"r"(a),"r"(x),"r"(y):"memory"); }
__device__ __forceinline__ float4 lds4f(uint32_t a){ float4 v; asm volatile("ld.shared.v4.f32 {%0,%1,%2,%3}, [%4];":"=f"(v.x),"=f"(v.y),"=f"(v.z),"=f"(v.w):"r"(a):"memory"); return v; }
__device__ __forceinline__ float2 lds2f(uint32_t a){ float2 v; asm volatile("ld.shared.v2.f32 {%0,%1}, [%2];":"=f"(v.x),"=f"(v.y):"r"(a):"memory"); return v; }
__device__ __forceinline__ uint4 lds4(uint32_t a){ uint4 v; asm volatile("ld.shared.v4.u32 {%0,%1,%2,%3}, [%4];":"=r"(v.x),"=r"(v.y),"=r"(v.z),"=r"(v.w):"r"(a):"memory"); return v; }
__device__ __forceinline__ void lds4r(uint32_t* r,uint32_t a){ asm volatile("ld.shared.v4.u32 {%0,%1,%2,%3}, [%4];":"=r"(r[0]),"=r"(r[1]),"=r"(r[2]),"=r"(r[3]):"r"(a):"memory"); }
__device__ __forceinline__ uint2 lds2(uint32_t a){ uint2 v; asm volatile("ld.shared.v2.u32 {%0,%1}, [%2];":"=r"(v.x),"=r"(v.y):"r"(a):"memory"); return v; }
__device__ __forceinline__ float ex2(float x){ float r; asm("ex2.approx.ftz.f32 %0, %1;":"=f"(r):"f"(x)); return r; }
__device__ __forceinline__ float rcp(float x){ float r; asm("rcp.approx.ftz.f32 %0, %1;":"=f"(r):"f"(x)); return r; }
__device__ __forceinline__ void mbar_init(uint32_t a,int n){ asm volatile("mbarrier.init.shared.b64 [%0], %1;"::"r"(a),"r"(n):"memory"); }
__device__ __forceinline__ void mbar_expect(uint32_t a,int bytes){ asm volatile("mbarrier.arrive.expect_tx.shared.b64 _, [%0], %1;"::"r"(a),"r"(bytes):"memory"); }
__device__ __forceinline__ void mbar_arrive(uint32_t a){ asm volatile("mbarrier.arrive.shared.b64 _, [%0];"::"r"(a):"memory"); }
__device__ __forceinline__ bool mbar_try(uint32_t a,uint32_t par){ uint32_t ok; asm volatile("{\n.reg .pred p;\nmbarrier.try_wait.parity.shared.b64 p, [%1], %2;\nselp.u32 %0,1,0,p;\n}":"=r"(ok):"r"(a),"r"(par):"memory"); return ok; }
__device__ __forceinline__ bool mbar_test(uint32_t a,uint32_t par){ uint32_t ok; asm volatile("{\n.reg .pred p;\nmbarrier.test_wait.parity.shared.b64 p, [%1], %2;\nselp.u32 %0,1,0,p;\n}":"=r"(ok):"r"(a),"r"(par):"memory"); return ok; }
__device__ __forceinline__ bool mbar_try_cl(uint32_t a,uint32_t par){ uint32_t ok; asm volatile("{\n.reg .pred p;\nmbarrier.try_wait.parity.acquire.cluster.shared::cta.b64 p, [%1], %2;\nselp.u32 %0,1,0,p;\n}":"=r"(ok):"r"(a),"r"(par):"memory"); return ok; }
__device__ __forceinline__ void bulk_g2s(uint32_t dst,const void* src,int bytes,uint32_t mb){ asm volatile("cp.async.bulk.shared::cluster.global.mbarrier::complete_tx::bytes [%0], [%1], %2, [%3];"::"r"(dst),"l"(src),"r"(bytes),"r"(mb):"memory"); }
__device__ __forceinline__ uint32_t mapa(uint32_t a,uint32_t r){ uint32_t d; asm("mapa.shared::cluster.u32 %0, %1, %2;":"=r"(d):"r"(a),"r"(r)); return d; }
__device__ __forceinline__ void st_async2(uint32_t ra,uint32_t x,uint32_t y,uint32_t rmb){ asm volatile("st.async.weak.shared::cluster.mbarrier::complete_tx::bytes.v2.b32 [%0], {%1,%2}, [%3];"::"r"(ra),"r"(x),"r"(y),"r"(rmb):"memory"); }
__device__ __forceinline__ void st_async4(uint32_t ra,uint32_t x,uint32_t y,uint32_t z,uint32_t w,uint32_t rmb){ asm volatile("st.async.weak.shared::cluster.mbarrier::complete_tx::bytes.v4.b32 [%0], {%1,%2,%3,%4}, [%5];"::"r"(ra),"r"(x),"r"(y),"r"(z),"r"(w),"r"(rmb):"memory"); }
__device__ __forceinline__ void stg_rlx4(uint32_t* p,uint32_t a,uint32_t b,uint32_t c,uint32_t d){ asm volatile("st.relaxed.gpu.global.v4.u32 [%0], {%1,%2,%3,%4};"::"l"(p),"r"(a),"r"(b),"r"(c),"r"(d):"memory"); }
__device__ __forceinline__ void red64(void* p,uint32_t lo,uint32_t hi){ asm volatile("{\n.reg .b64 v;\nmov.b64 v, {%1,%2};\nred.relaxed.gpu.global.add.u64 [%0], v;\n}"::"l"(p),"r"(lo),"r"(hi):"memory"); }
__device__ __forceinline__ uint32_t amax2(uint32_t a,uint32_t b){ uint32_t r; asm("max.xorsign.abs.bf16x2 %0, %1, %2;":"=r"(r):"r"(a),"r"(b)); return r; }
__device__ __forceinline__ void cluster_sync(){ asm volatile("barrier.cluster.arrive.release.aligned;\nbarrier.cluster.wait.acquire.aligned;":::"memory"); }
__device__ __forceinline__ uint32_t ld_acq(const uint32_t* p){ uint32_t v; asm volatile("ld.acquire.gpu.global.u32 %0, [%1];":"=r"(v):"l"(p):"memory"); return v; }
__device__ __forceinline__ void fence_async_all(){ asm volatile("fence.proxy.async;":::"memory"); }
__device__ __forceinline__ void fence_async_g(){ asm volatile("fence.proxy.async.global;":::"memory"); }
__device__ __forceinline__ void fence_rel(){ asm volatile("fence.release.gpu;":::"memory"); }
__device__ __forceinline__ void fence_acq(){ asm volatile("fence.acquire.gpu;":::"memory"); }
__device__ __forceinline__ void fence_gpu(){ asm volatile("fence.acq_rel.gpu;":::"memory"); }

template<int NL,class V,class LDF,class OKF>
__device__ __forceinline__ int poll1(V* u,LDF ld,OKF ok,bool& dead,int code){
  #pragma unroll
  for(int i=0;i<NL;i++) u[i]=ld(i);
  int guard=0;
  while(true){
    bool f[NL]; bool a=true;
    #pragma unroll
    for(int i=0;i<NL;i++){ f[i]=ok(u[i]); a=a&&f[i]; }
    if(__all_sync(~0u,a)||dead) break;
    #pragma unroll
    for(int i=0;i<NL;i++) if(!f[i]) u[i]=ld(i);
    if(++guard>GUARD){ dead=true; g_err=code; }
  }
  return guard;
}
template<int NL,class V,class LDF,class OKF>
__device__ __forceinline__ int poll2(V* u,LDF ld,OKF ok,bool& dead,int code){
  int guard=0;
  while(true){
    bool f[NL]; bool a=true;
    #pragma unroll
    for(int i=0;i<NL;i++){ f[i]=ok(u[i]); a=a&&f[i]; }
    if(__all_sync(~0u,a)||dead) break;
    #pragma unroll
    for(int i=0;i<NL;i++) if(!f[i]) u[i]=ld(i);
    if(++guard>GUARD){ dead=true; g_err=code; }
  }
  return guard;
}
__device__ __forceinline__ void spin(uint32_t n){ uint32_t t0,t1; asm volatile("mov.u32 %0, %%clock;":"=r"(t0)); do{ asm volatile("mov.u32 %0, %%clock;":"=r"(t1)); }while(t1-t0<n); }
template<int N> __device__ __forceinline__ void wgmma(float* d,uint32_t da,uint32_t db,int sc);
template<int N> __device__ __forceinline__ void wgmma_rs(float* d,const uint32_t* a,uint32_t db,int sc);
template<> __device__ __forceinline__ void wgmma<128>(float* d,uint32_t da,uint32_t db,int sc){
  asm volatile("{\n.reg .pred p;\n.reg .b64 xa, xb;\nmov.b64 xa, {%64, 0x40000040};\nmov.b64 xb, {%65, 0x40000040};\nsetp.ne.b32 p, %66, 0;\nwgmma.mma_async.sync.aligned.m64n128k16.f32.bf16.bf16 {%0,%1,%2,%3,%4,%5,%6,%7,%8,%9,%10,%11,%12,%13,%14,%15,%16,%17,%18,%19,%20,%21,%22,%23,%24,%25,%26,%27,%28,%29,%30,%31,%32,%33,%34,%35,%36,%37,%38,%39,%40,%41,%42,%43,%44,%45,%46,%47,%48,%49,%50,%51,%52,%53,%54,%55,%56,%57,%58,%59,%60,%61,%62,%63}, xa, xb, p, 1, 1, 0, 1;\n}"
   :"+f"(d[0]),"+f"(d[1]),"+f"(d[2]),"+f"(d[3]),"+f"(d[4]),"+f"(d[5]),"+f"(d[6]),"+f"(d[7]),"+f"(d[8]),"+f"(d[9]),"+f"(d[10]),"+f"(d[11]),"+f"(d[12]),"+f"(d[13]),"+f"(d[14]),"+f"(d[15]),"+f"(d[16]),"+f"(d[17]),"+f"(d[18]),"+f"(d[19]),"+f"(d[20]),"+f"(d[21]),"+f"(d[22]),"+f"(d[23]),"+f"(d[24]),"+f"(d[25]),"+f"(d[26]),"+f"(d[27]),"+f"(d[28]),"+f"(d[29]),"+f"(d[30]),"+f"(d[31]),"+f"(d[32]),"+f"(d[33]),"+f"(d[34]),"+f"(d[35]),"+f"(d[36]),"+f"(d[37]),"+f"(d[38]),"+f"(d[39]),"+f"(d[40]),"+f"(d[41]),"+f"(d[42]),"+f"(d[43]),"+f"(d[44]),"+f"(d[45]),"+f"(d[46]),"+f"(d[47]),"+f"(d[48]),"+f"(d[49]),"+f"(d[50]),"+f"(d[51]),"+f"(d[52]),"+f"(d[53]),"+f"(d[54]),"+f"(d[55]),"+f"(d[56]),"+f"(d[57]),"+f"(d[58]),"+f"(d[59]),"+f"(d[60]),"+f"(d[61]),"+f"(d[62]),"+f"(d[63]):"r"(da),"r"(db),"r"(sc));
}
template<> __device__ __forceinline__ void wgmma<192>(float* d,uint32_t da,uint32_t db,int sc){
  asm volatile("{\n.reg .pred p;\n.reg .b64 xa, xb;\nmov.b64 xa, {%96, 0x40000040};\nmov.b64 xb, {%97, 0x40000040};\nsetp.ne.b32 p, %98, 0;\nwgmma.mma_async.sync.aligned.m64n192k16.f32.bf16.bf16 {%0,%1,%2,%3,%4,%5,%6,%7,%8,%9,%10,%11,%12,%13,%14,%15,%16,%17,%18,%19,%20,%21,%22,%23,%24,%25,%26,%27,%28,%29,%30,%31,%32,%33,%34,%35,%36,%37,%38,%39,%40,%41,%42,%43,%44,%45,%46,%47,%48,%49,%50,%51,%52,%53,%54,%55,%56,%57,%58,%59,%60,%61,%62,%63,%64,%65,%66,%67,%68,%69,%70,%71,%72,%73,%74,%75,%76,%77,%78,%79,%80,%81,%82,%83,%84,%85,%86,%87,%88,%89,%90,%91,%92,%93,%94,%95}, xa, xb, p, 1, 1, 0, 1;\n}"
   :"+f"(d[0]),"+f"(d[1]),"+f"(d[2]),"+f"(d[3]),"+f"(d[4]),"+f"(d[5]),"+f"(d[6]),"+f"(d[7]),"+f"(d[8]),"+f"(d[9]),"+f"(d[10]),"+f"(d[11]),"+f"(d[12]),"+f"(d[13]),"+f"(d[14]),"+f"(d[15]),"+f"(d[16]),"+f"(d[17]),"+f"(d[18]),"+f"(d[19]),"+f"(d[20]),"+f"(d[21]),"+f"(d[22]),"+f"(d[23]),"+f"(d[24]),"+f"(d[25]),"+f"(d[26]),"+f"(d[27]),"+f"(d[28]),"+f"(d[29]),"+f"(d[30]),"+f"(d[31]),"+f"(d[32]),"+f"(d[33]),"+f"(d[34]),"+f"(d[35]),"+f"(d[36]),"+f"(d[37]),"+f"(d[38]),"+f"(d[39]),"+f"(d[40]),"+f"(d[41]),"+f"(d[42]),"+f"(d[43]),"+f"(d[44]),"+f"(d[45]),"+f"(d[46]),"+f"(d[47]),"+f"(d[48]),"+f"(d[49]),"+f"(d[50]),"+f"(d[51]),"+f"(d[52]),"+f"(d[53]),"+f"(d[54]),"+f"(d[55]),"+f"(d[56]),"+f"(d[57]),"+f"(d[58]),"+f"(d[59]),"+f"(d[60]),"+f"(d[61]),"+f"(d[62]),"+f"(d[63]),"+f"(d[64]),"+f"(d[65]),"+f"(d[66]),"+f"(d[67]),"+f"(d[68]),"+f"(d[69]),"+f"(d[70]),"+f"(d[71]),"+f"(d[72]),"+f"(d[73]),"+f"(d[74]),"+f"(d[75]),"+f"(d[76]),"+f"(d[77]),"+f"(d[78]),"+f"(d[79]),"+f"(d[80]),"+f"(d[81]),"+f"(d[82]),"+f"(d[83]),"+f"(d[84]),"+f"(d[85]),"+f"(d[86]),"+f"(d[87]),"+f"(d[88]),"+f"(d[89]),"+f"(d[90]),"+f"(d[91]),"+f"(d[92]),"+f"(d[93]),"+f"(d[94]),"+f"(d[95]):"r"(da),"r"(db),"r"(sc));
}
template<> __device__ __forceinline__ void wgmma_rs<64>(float* d,const uint32_t* a,uint32_t db,int sc){
  asm volatile("{\n.reg .pred p;\n.reg .b64 xb;\nmov.b64 xb, {%36, 0x40000040};\nsetp.ne.b32 p, %37, 0;\nwgmma.mma_async.sync.aligned.m64n64k16.f32.bf16.bf16 {%0,%1,%2,%3,%4,%5,%6,%7,%8,%9,%10,%11,%12,%13,%14,%15,%16,%17,%18,%19,%20,%21,%22,%23,%24,%25,%26,%27,%28,%29,%30,%31}, {%32,%33,%34,%35}, xb, p, 1, 1, 0;\n}"
   :"+f"(d[0]),"+f"(d[1]),"+f"(d[2]),"+f"(d[3]),"+f"(d[4]),"+f"(d[5]),"+f"(d[6]),"+f"(d[7]),"+f"(d[8]),"+f"(d[9]),"+f"(d[10]),"+f"(d[11]),"+f"(d[12]),"+f"(d[13]),"+f"(d[14]),"+f"(d[15]),"+f"(d[16]),"+f"(d[17]),"+f"(d[18]),"+f"(d[19]),"+f"(d[20]),"+f"(d[21]),"+f"(d[22]),"+f"(d[23]),"+f"(d[24]),"+f"(d[25]),"+f"(d[26]),"+f"(d[27]),"+f"(d[28]),"+f"(d[29]),"+f"(d[30]),"+f"(d[31]):"r"(a[0]),"r"(a[1]),"r"(a[2]),"r"(a[3]),"r"(db),"r"(sc));
}
#define PPF 0
#define PPN 61440
#define PPFA(i) (size_t)(i)
__device__ __align__(128) uint32_t g_sml[NCTA];
constexpr int PRE_T=704;
__global__ void __launch_bounds__(PRE_T) k_pre(const bf16* __restrict__ x,const bf16* __restrict__ mem0,const char* wk,const char* wv){
  const int warp=threadIdx.x>>5, lane=threadIdx.x&31;
  const int row=blockIdx.x*(PRE_T/32)+warp;
  asm volatile("griddepcontrol.launch_dependents;");
  if(threadIdx.x==0){ uint32_t sm_; asm volatile("mov.u32 %0, %%smid;":"=r"(sm_)); g_sml[blockIdx.x]=sm_; }
  uint2 u[5];
  static_assert(2*(NCTA-1)*PRE_T>=(NSEG-1)*1280,"init");
  {
    int i=blockIdx.x*PRE_T+threadIdx.x; constexpr int n=(NCTA-1)*PRE_T;
    if(blockIdx.x==NCTA-1){
      if(warp>=8) return;
      extern __shared__ uint32_t smx[];
      uint32_t w[10], mx=0;
      #pragma unroll
      for(int j=0;j<10;j++){ const int k=threadIdx.x+256*j; const uint16_t* mp=(const uint16_t*)mem0+(((k>>3)&3)*2+((k>>5)&1))*D+(k>>6)*16+(k&7);
        w[j]=mp[0]|((uint32_t)mp[8]<<16); mx=max(mx,max(w[j]&0x7fffu,(w[j]>>16)&0x7fffu)); }
      mx=__reduce_max_sync(~0u,mx); if(lane==0) smx[warp]=mx;
      bar_sync(1,256);
      #pragma unroll
      for(int j=0;j<8;j++) mx=max(mx,smx[j]);
      const uint32_t eb=min(max(mx>>7,40u),254u); const float sc=__uint_as_float((280u-eb)<<23);
      #pragma unroll
      for(int j=0;j<10;j++) g_acc[threadIdx.x+256*j]=((unsigned long long)(long long)__float2int_rn(__uint_as_float(w[j]&0xffff0000u)*sc)<<35)+((unsigned long long)(long long)__float2int_rn(__uint_as_float(w[j]<<16)*sc)<<6);
      if(threadIdx.x<NCTA*2) g_nrm[threadIdx.x]=SENT;
      if(threadIdx.x==0) g_nrm[NCTA*2]=(eb-29u)<<23;
      return;
    }
    const uint2* p=(const uint2*)(x+(size_t)min(row,S-1)*D);
    #pragma unroll
    for(int j=0;j<5;j++) asm volatile("ld.global.nc.v2.u32 {%0,%1}, [%2];":"=r"(u[j].x),"=r"(u[j].y):"l"(p+lane+32*j));
    #pragma unroll
    for(int j=0;j<2;j++){ const int k=1280+i+j*n; if(k<NSEG*1280) ((ulonglong2*)g_acc)[k]=make_ulonglong2(ACC_INIT,ACC_INIT); }
    if(i==0) g_err=0;
    if(i<NCTA*32) g_flag[i]=0;
    if(i<C_NUM) g_cnt[i]=0;
  }
  #define PFW { const int i=blockIdx.x*PRE_T+threadIdx.x; if(i<PPN){ asm volatile("prefetch.global.L2 [%0];"::"l"(wk+(size_t)i*128+(u[4].y&zr)):"memory"); asm volatile("prefetch.global.L2 [%0];"::"l"(wv+(size_t)i*128+(u[4].y&zr)):"memory"); } }
  const uint32_t zr=PPF==2?(uint32_t)((size_t)wk&1):0u;
  if(PPF) PFW
  if(row>=S) return;
  float v[20];
  #pragma unroll
  for(int i=0;i<5;i++){ v[4*i]=__uint_as_float(u[i].x<<16); v[4*i+1]=__uint_as_float(u[i].x&0xffff0000u); v[4*i+2]=__uint_as_float(u[i].y<<16); v[4*i+3]=__uint_as_float(u[i].y&0xffff0000u); }
  #pragma unroll
  for(int pass=0;pass<2;pass++){
    float s=0;
    #pragma unroll
    for(int i=0;i<20;i++) s+=v[i];
    #pragma unroll
    for(int o=16;o;o>>=1) s+=__shfl_xor_sync(~0u,s,o);
    float mean=s*(1.f/D);
    float q=0;
    #pragma unroll
    for(int i=0;i<20;i++){ float d=v[i]-mean; q+=d*d; }
    #pragma unroll
    for(int o=16;o;o>>=1) q+=__shfl_xor_sync(~0u,q,o);
    float var=rb(q*(1.f/D)), mb=rb(mean);
    float den=rb(sqrtf(rb(var+1e-5f)));
    const float id=1.f/den;
    uint2* o=(uint2*)((pass?g_y:g_xn)+(size_t)row*D);
    #pragma unroll
    for(int i=0;i<5;i++){
      uint32_t w[2];
      #pragma unroll
      for(int j=0;j<2;j++){
        const uint32_t d=pack_bf16(v[4*i+2*j]-mb,v[4*i+2*j+1]-mb);
        w[j]=pack_bf16(__uint_as_float(d<<16)*id,__uint_as_float(d&0xffff0000u)*id);
        v[4*i+2*j]=__uint_as_float(w[j]<<16); v[4*i+2*j+1]=__uint_as_float(w[j]&0xffff0000u);
      }
      o[lane+32*i]=make_uint2(w[0],w[1]);
    }
  }
}

#define ULAY 0
#define WGO 1
#define UBP 4
#define URM 63
#define UEB 24
#define NOF 0
#define EXD 0
#define UEX 1
#define ADELAY 0
#define KP 4
#define UXP 16
#define OPF 99
#define XGP 0
#define W3O 250
#define FW 3
#define WPA 1
#define WPB 1
#define PD 1000
#define PPOS 2
#define ADP 0
#define ADUP 64
#define ADDN 4
constexpr int SM_QS=0;
constexpr int SM_KS=49152;
constexpr int SM_OS=131072;
constexpr int SM_RED=180224;
constexpr int SM_P=SM_RED+3584;
constexpr int SM_PM=SM_RED+4096+3584;
constexpr int SM_MB=SM_PM+128;
constexpr int SM_MX=SM_PM+192, SM_SCL=SM_PM+224;
constexpr int SM_X5=SM_RED+8192+3584;
constexpr int SM_KX=SM_RED+16384;
constexpr int SM_VX=SM_KX+4096;
constexpr int SM_SCX=SM_VX+14336;
constexpr int SM_KRED=SM_SCX+6144;
constexpr int SM_VMX=SM_KRED+8192;
constexpr int SM_TOTAL=SM_VMX+3072, SM_NR=SM_VMX;
static_assert(SM_TOTAL<=232448,"smem");
__device__ __forceinline__ void wg32_rs(float* d,const uint32_t* a,uint32_t db){
  asm volatile("{\n.reg .b64 xb;\nmov.b64 xb, {%20, 0x40000040};\nwgmma.mma_async.sync.aligned.m64n32k16.f32.bf16.bf16 {%0,%1,%2,%3,%4,%5,%6,%7,%8,%9,%10,%11,%12,%13,%14,%15}, {%16,%17,%18,%19}, xb, 1, 1, 1, 0;\n}"
   :"+f"(d[0]),"+f"(d[1]),"+f"(d[2]),"+f"(d[3]),"+f"(d[4]),"+f"(d[5]),"+f"(d[6]),"+f"(d[7]),"+f"(d[8]),"+f"(d[9]),"+f"(d[10]),"+f"(d[11]),"+f"(d[12]),"+f"(d[13]),"+f"(d[14]),"+f"(d[15])
   :"r"(a[0]),"r"(a[1]),"r"(a[2]),"r"(a[3]),"r"(db));
}
__device__ __forceinline__ void wg32_rs0(float* d,const uint32_t* a,uint32_t db){
  asm volatile("{\n.reg .b64 xb;\nmov.b64 xb, {%20, 0x40000040};\nwgmma.mma_async.sync.aligned.m64n32k16.f32.bf16.bf16 {%0,%1,%2,%3,%4,%5,%6,%7,%8,%9,%10,%11,%12,%13,%14,%15}, {%16,%17,%18,%19}, xb, 0, 1, 1, 0;\n}"
   :"=f"(d[0]),"=f"(d[1]),"=f"(d[2]),"=f"(d[3]),"=f"(d[4]),"=f"(d[5]),"=f"(d[6]),"=f"(d[7]),"=f"(d[8]),"=f"(d[9]),"=f"(d[10]),"=f"(d[11]),"=f"(d[12]),"=f"(d[13]),"=f"(d[14]),"=f"(d[15])
   :"r"(a[0]),"r"(a[1]),"r"(a[2]),"r"(a[3]),"r"(db));
}
__device__ __forceinline__ void wg32_ss(float* d,uint32_t da,uint32_t db){
  asm volatile("{\n.reg .b64 xa, xb;\nmov.b64 xa, {%16, 0x00000180};\nmov.b64 xb, {%17, 0x40000040};\nwgmma.mma_async.sync.aligned.m64n32k16.f32.bf16.bf16 {%0,%1,%2,%3,%4,%5,%6,%7,%8,%9,%10,%11,%12,%13,%14,%15}, xa, xb, 1, 1, 1, 0, 0;\n}"
   :"+f"(d[0]),"+f"(d[1]),"+f"(d[2]),"+f"(d[3]),"+f"(d[4]),"+f"(d[5]),"+f"(d[6]),"+f"(d[7]),"+f"(d[8]),"+f"(d[9]),"+f"(d[10]),"+f"(d[11]),"+f"(d[12]),"+f"(d[13]),"+f"(d[14]),"+f"(d[15])
   :"r"(da),"r"(db));
}
__device__ __forceinline__ void wg32_ss0(float* d,uint32_t da,uint32_t db){
  asm volatile("{\n.reg .b64 xa, xb;\nmov.b64 xa, {%16, 0x00000180};\nmov.b64 xb, {%17, 0x40000040};\nwgmma.mma_async.sync.aligned.m64n32k16.f32.bf16.bf16 {%0,%1,%2,%3,%4,%5,%6,%7,%8,%9,%10,%11,%12,%13,%14,%15}, xa, xb, 0, 1, 1, 0, 0;\n}"
   :"=f"(d[0]),"=f"(d[1]),"=f"(d[2]),"=f"(d[3]),"=f"(d[4]),"=f"(d[5]),"=f"(d[6]),"=f"(d[7]),"=f"(d[8]),"=f"(d[9]),"=f"(d[10]),"=f"(d[11]),"=f"(d[12]),"=f"(d[13]),"=f"(d[14]),"=f"(d[15])
   :"r"(da),"r"(db));
}
template<int V> struct IC{ static constexpr int v=V; };
__device__ __forceinline__ uint32_t lds1(uint32_t a){ uint32_t v; asm volatile("ld.shared.u32 %0, [%1];":"=r"(v):"r"(a):"memory"); return v; }
__device__ __forceinline__ void sts1(uint32_t a,uint32_t x){ asm volatile("st.shared.u32 [%0], %1;"::"r"(a),"r"(x):"memory"); }

#define TS(i)
#define TSB(i)
#define PC(i) (void)np
#define TW(i)
#define TF(i)
#define TFP(i)

__device__ __forceinline__ void cp_commit(){ asm volatile("cp.async.commit_group;":::"memory"); }
template<int N> __device__ __forceinline__ void cp_wait(){ asm volatile("cp.async.wait_group %0;"::"n"(N):"memory"); }
__device__ __forceinline__ void tma2d(uint32_t dst,const CUtensorMap* tm,int c0,int c1,uint32_t mb){
  asm volatile("cp.async.bulk.tensor.2d.shared::cluster.global.mbarrier::complete_tx::bytes [%0], [%1, {%3, %4}], [%2];"::"r"(dst),"l"(tm),"r"(mb),"r"(c0),"r"(c1):"memory"); }
__device__ __forceinline__ void tma2d_pf(const CUtensorMap* tm,int c0,int c1){
  asm volatile("cp.async.bulk.prefetch.tensor.2d.L2.global [%0, {%1, %2}];"::"l"(tm),"r"(c0),"r"(c1):"memory"); }
constexpr unsigned long long PL_EF=0x12F0000000000000ull, PL_EN=0x1000000000000000ull;
__device__ __forceinline__ void tma2dh(uint32_t dst,const CUtensorMap* tm,int c0,int c1,uint32_t mb,unsigned long long pl){
  asm volatile("cp.async.bulk.tensor.2d.shared::cluster.global.mbarrier::complete_tx::bytes.L2::cache_hint [%0], [%1, {%3, %4}], [%2], %5;"::"r"(dst),"l"(tm),"r"(mb),"r"(c0),"r"(c1),"l"(pl):"memory"); }
__device__ __forceinline__ void tma2d_pfh(const CUtensorMap* tm,int c0,int c1,unsigned long long pl){
  asm volatile("cp.async.bulk.prefetch.tensor.2d.L2.global.L2::cache_hint [%0, {%1, %2}], %3;"::"l"(tm),"r"(c0),"r"(c1),"l"(pl):"memory"); }
#define HV 0
#define HK 0
#define HP 0
#define HUS 0
struct RParams { CUtensorMap k,v,w[4]; const char* wq; const char* wo; };
#define SO 0
#define SA 1
#define SEF 7
#define SPF 1
__global__ void __launch_bounds__(256,1) k_rec(const __grid_constant__ RParams P,const uint32_t zero){
  extern __shared__ __align__(1024) uint8_t sm[];
  const int tid=threadIdx.x, warp=__shfl_sync(~0u,tid>>5,0), lane=tid&31, g=lane>>2, t=lane&3;
  const int b=blockIdx.x, h=b/3, c=b-3*h;
  const uint32_t sb=(uint32_t)__cvta_generic_to_shared(sm);
  const int kq=warp&3, mg=warp>>2, wt=warp-mg;
  const uint32_t s16=sb+lane*16;
  const uint32_t qs=lane*16+__shfl_sync(~0u,sb+(mg?SM_KS+kq*20480:SM_QS+kq*12288),0), m5u=__shfl_sync(~0u,sb+SM_X5+(kq>>1)*4096+(kq&1)*256,0), mo=((lane>>3)&1), os=sb+SM_OS+kq*12288+mo*6144+(lane>>4)*128+(lane&7)*16, us=sb+SM_VX+wt*2048+mo*512+(lane>>4)*128+(lane&7)*16;
  const uint32_t XS=sb+SM_MB, KVB=sb+SM_MB+8, XV=sb+SM_MB+16, XL=sb+SM_MB+24;
  #define tmK P.k
  #define tmV P.v
  GT(0);
  asm volatile("griddepcontrol.launch_dependents;");
  const int ntile=c==0?14:13, tile0=c==0?0:(1+13*c);
  uint32_t pw[40][4];
#define SG(i)
  SG(0);
  {
    static_assert(KP==4,"setup");
    const uint32_t qb=qs-lane*16, SBR=sb+SM_NR+128+warp*32, ob=sb+(mg?SM_OS:SM_RED)+kq*12288;
    unsigned long long plf, pln;
    asm volatile("createpolicy.fractional.L2::evict_first.b64 %0, 1.0;":"=l"(plf)); asm volatile("createpolicy.fractional.L2::evict_normal.b64 %0, 1.0;":"=l"(pln));
    const unsigned long long plq=(mg?(SEF&4):(SEF&2))?plf:pln, plo=(SEF&1)?plf:pln;
    auto wbox=[&](int rd,int sl,int mode){
      const int kb=rd?(sl<6?sl:sl-6):(sl<4?sl+6:sl), k=mg?(kb+5)%10:kb;
      const CUtensorMap* tm=&P.w[mg?(sl<(rd?6:4)?1:2):0];
      const int c0=h*DH+64*c, c1=80*kq+8*k;
      if(mode) asm volatile("cp.async.bulk.prefetch.tensor.3d.L2.global.L2::cache_hint [%0, {%1, %2, 0}], %3;"::"l"(tm),"r"(c0),"r"(c1),"l"(plq):"memory");
      else asm volatile("cp.async.bulk.tensor.3d.shared::cluster.global.mbarrier::complete_tx::bytes.L2::cache_hint [%0], [%1, {%3, %4, 0}], [%2], %5;"::"r"(qb+sl*2048),"l"(tm),"r"(SBR+((rd||(!mg&&sl>=4))?8:0)),"r"(c0),"r"(c1),"l"(plq):"memory");
    };
    if(lane==0){
      mbar_init(SBR,1); mbar_init(SBR+8,1); mbar_init(SBR+16,1);
      asm volatile("fence.mbarrier_init.release.cluster;":::"memory");
      mbar_expect(SBR,mg?20480:8192); mbar_expect(SBR+8,mg?20480:12288); mbar_expect(SBR+16,12288);
    }
    __syncwarp();
    if(lane<(mg?10:6)) wbox(0,lane,0);
    if(lane<6) asm volatile("cp.async.bulk.tensor.2d.shared::cluster.global.mbarrier::complete_tx::bytes.L2::cache_hint [%0], [%1, {%3, %4}], [%2], %5;"::"r"(ob+(mg?(lane>>1)*2048+(lane&1)*6144:lane*2048)),"l"(&P.w[3]),"r"(SBR+16),"r"((tile0+2*wt)*16),"r"(h*DH+((2*c+lane)%6)*32),"l"(plo):"memory");
    if(SPF&&lane<(mg?(SPF>1?10:0):4)) wbox(1,lane,1);
    __syncwarp();
    SG(1);
    float nr[4][2][4];
    #pragma unroll
    for(int i=0;i<32;i++) nr[i>>3][(i>>2)&1][i&3]=0.f;
    auto sq=[&](int n,const uint32_t* r){ mma16816(nr[n][0],r,r[0],r[2]); mma16816(nr[n][1],r,r[1],r[3]); };
    auto dg=[&](const float* d,int o){ return g==2*t?d[o]:(g==2*t+1?d[o+1]:0.f); };
    auto swait=[&](uint32_t a){ int gd=0; while(!mbar_try(a,0)){ if(++gd>GUARD){ g_err=9; break; } } };
    const int p8=((lane>>1)&3)+4*(lane&1), r16=(lane&7)+(lane>>4)*8;
    uint32_t ak[4], av[4], ao[2];
    #pragma unroll
    for(int j=0;j<4;j++){ ak[j]=qb+(p8+(lane>>4)*8)*128+(((2*j+mo)^p8)<<4); av[j]=qb+(p8+(lane>>4)*8)*128+(((2*((j+kq)&3)+mo)^p8)<<4); }
    #pragma unroll
    for(int i=0;i<2;i++) ao[i]=ob+r16*64+(((2*i+mo)^((lane>>1)&3))<<4);
    swait(SBR);
    SG(2);
    #pragma unroll
    for(int u=0;u<16;u++) ldsm4t(pw[u],ak[u&3]+(u>>2)*2048);
    if(SA&&!mg){
      uint32_t d0=0;
      #pragma unroll
      for(int u=0;u<16;u+=2) d0^=pw[u][0]^pw[u+1][0];
      if(lane+(d0&zero)<4) wbox(1,lane,0);
      __syncwarp();
    }
    swait(SBR+(mg?0:16));
    SG(3);
    uint32_t dp=0;
    {
      uint32_t a2[4];
      #pragma unroll
      for(int j=0;j<4;j++) a2[j]=mg?av[j]+8192:ao[j&1]+(j>>1)*1024;
      #pragma unroll
      for(int u=0;u<24;u++){ ldsm4t(pw[16+u],a2[u&3]+(u>>2)*2048); if(!SA) sq((u&1)*2,pw[16+u]); }
      #pragma unroll
      for(int u=0;u<40;u+=2) dp^=pw[u][0]^pw[u+1][0];
      dp&=zero;
    }
    if(lane+dp<(mg?10:(SA?0:4))) wbox(1,lane,0);
    __syncwarp();
    if(SA){
      #pragma unroll
      for(int u=0;u<24;u++) sq((u&1)*2,pw[16+u]);
    }
    SG(4);
    if(mg){
      swait(SBR+16);
      #pragma unroll 1
      for(int y=0;y<3;y++){
        uint32_t r[8][4];
        #pragma unroll
        for(int f=0;f<8;f++){ ldsm4t(r[f],ao[f&1]+y*2048+((f>>1)&1)*1024+(f>>2)*6144); sq(1+(f&1)*2,r[f]); }
        __syncwarp();
        #pragma unroll
        for(int f=0;f<8;f++) stsm4(os+y*2048+f*256,r[f][0],r[f][1],r[f][2],r[f][3]);
      }
    } else {
      bar_sync(5+dp,128);
      if(tid==96){
        mbar_init(XS,5); mbar_init(KVB,1); mbar_init(XV,1); mbar_init(XL,4);
        asm volatile("fence.mbarrier_init.release.cluster;":::"memory");
        mbar_expect(XS,4096); mbar_expect(XV,2048);
        int gd=0; while(ld_acq(g_cnt+C_KV)<64){ if(++gd>GUARD){ g_err=7; break; } } fence_async_g();
        mbar_expect(KVB,32*512);
        tma2d(sb+SM_KX,&tmK,h*DH+64*c,0,KVB);
        #pragma unroll 1
        for(int i=0;i<3;i++) tma2d(sb+SM_VX+i*4096,&tmV,h*DH+64*i,0,KVB);
        tma2d_pf(&tmK,h*DH+64*c,32); tma2d_pf(&tmV,h*DH+64*c,32);
      }
      if(tid==32) sts1(sb+SM_SCL+8,g_nrm[NCTA*2]);
      __syncwarp();
    }
    SG(5);
    swait(SBR+8);
    SG(6);
    #pragma unroll 1
    for(int y=0;y<(mg?10:6);y+=2){
      uint32_t r[8][4];
      #pragma unroll
      for(int j=0;j<8;j++) ldsm4t(r[j],(y<6?ak[j&3]:av[j&3])+y*2048+(j>>2)*2048);
      __syncwarp();
      #pragma unroll
      for(int j=0;j<8;j++) sts4r(qs+y*2048+j*512,r[j]);
      if(y>=6){
        #pragma unroll
        for(int j=0;j<8;j++) sq((j&1)*2,r[j]);
      }
    }
    SG(7);
    float d4[4][2];
    #pragma unroll
    for(int i=0;i<4;i++){ d4[i][0]=dg(nr[i][0],0); d4[i][1]=dg(nr[i][1],2); }
    float nv=mg?(d4[0][0]+d4[0][1])+(d4[2][0]+d4[2][1]):0.f;
    #pragma unroll
    for(int o=16;o;o>>=1) nv+=__shfl_xor_sync(~0u,nv,o);
    const uint32_t no=__reduce_max_sync(~0u,__float_as_uint(mg?fmaxf(d4[1][0]+d4[3][0],d4[1][1]+d4[3][1]):fmaxf(d4[0][0]+d4[2][0],d4[0][1]+d4[2][1])));
    if(lane==0){
      sts2(sb+SM_NR+warp*8,__float_as_uint(nv),no);
      #pragma unroll
      for(int i=0;i<3;i++) asm volatile("mbarrier.inval.shared.b64 [%0];"::"r"(SBR+i*8):"memory");
    }
  }
  fence_async();
  __syncthreads();
  SG(8);
  {
    float a=0.f; uint32_t o=0;
    if(warp==0){
      #pragma unroll
      for(int w=0;w<8;w++){ const uint2 x=lds2(sb+SM_NR+w*8); a+=__uint_as_float(x.x); o=max(o,x.y); }
      o=min(o,0x7f800000u);
    }
    asm volatile("barrier.cluster.arrive.relaxed.aligned;"::"r"(o):"memory");
    if(tid==0) stg_rlx2(g_nrm+b*2,min(__float_as_uint(a),0x7f800000u),o);
    asm volatile("barrier.cluster.wait.acquire.aligned;":::"memory");
  }
  SG(9);
  uint32_t pd=PD;
  bool dead=false;
  const uint32_t qrd=sb+SM_RED+1024+((lane>>3)&1)*4096+(lane>>4)*128+(lane&7)*16+kq*256;
  uint32_t rsc[2];
  rsc[0]=mapa(sb,c==2?0:c+1); rsc[1]=mapa(sb,c==0?2:c-1);
  GT(1);
  auto loop=[&](auto MGc){
  constexpr int MG=decltype(MGc)::v;
  uint32_t buf[8][4], um[2][2]={{0,0},{0,0}}, ex0=0, ex1=0;
  uint32_t eo1=(uint32_t)((32+(h>>2))*40960+(tile0+2*wt)*1024+(h&3)*128+lane*4), eo2=(uint32_t)(h*3072+(4*c+kq)*256+lane*4);
  uint32_t so=(uint32_t)((kq*10+MG*5)*512+(g&1)*256+(g>>1)*64+t*16)^zero;
  bool kvok=false;
  #define EXPU { char* um_=(char*)g_u+eo1; _Pragma("unroll") for(int i=0;i<2;i++) if(i==0||2*wt+1<ntile){ stg1(um_+i*1024,um[i][0]); stg1(um_+i*1024+512,um[i][1]); } }
  #define EXPK { char* ep=(char*)g_km+eo2; stg1(ep,ex0); stg1(ep+128,ex1); }
  #define UBULK { const uint32_t o_=(us-sb)&~2047u; asm volatile("{\n.reg .pred p;\nelect.sync _|p, 0xffffffff;\n@p cp.async.bulk.global.shared::cta.bulk_group.L2::cache_hint [%0], [%1], %2, %3;\n@p cp.async.bulk.commit_group;\n}" \
      ::"l"((char*)g_u+(uint32_t)(s*1638400+h*40960+tile0*1024-SM_VX+o_)),"r"(sb+o_),"r"(2*wt+1<ntile?2048:1024),"l"(s<HUS?PL_EF:PL_EN):"memory"); }
  uint32_t t0; asm volatile("mov.u32 %0, %%clock;":"=r"(t0)); t0-=4096;
  #define MB0(k) mb[k][0]
  #define MB1(k) mb[k][1]
  #pragma unroll 1
  for(int s=0;s<NSEG;s++){
    const bool last=s==NSEG-1;
    float u[2][16];
    const char* src=(const char*)g_acc+so;
    uint4 m[5];
    #define SPIN(T,N) { uint32_t t1; do{ asm volatile("mov.u32 %0, %%clock;":"=r"(t1)); }while((int)(t1-(T))<(int)(N)); }
    #define PLD { SPIN(t0,pd) _Pragma("unroll") for(int p=0;p<5;p++) m[p]=ldg_rlx4((const uint32_t*)(src+p*512)); SPIN(t0,pd) TFP(21); }
    {
      if(!kvok){ int gd=0; while(!mbar_try(KVB,s&1)){ if(dead) break; if(++gd>GUARD){ dead=true; g_err=6; } } }
      TFP(16);
      const uint32_t da=(((sb+SM_OS)>>4)&0x3fff)|(8u<<16);
      const uint32_t dv=(((sb+SM_VX)>>4)&0x3fff)|(1u<<16);
      const uint32_t vb[3]={dv+c*256,dv+(c==2?0:c+1)*256,dv+(c==0?2:c-1)*256};
      asm volatile("wgmma.fence.sync.aligned;":::"memory");
      if constexpr(MG){
        #pragma unroll
        for(int y=0;y<24;y++){
          const int i=WGO?(y&1):(y>=12), x=WGO?(y>>1):(y%12);
          if(x==0) wg32_ss0(u[i],da+i*16,vb[0]); else wg32_ss(u[i],da+(x*2+i)*16,vb[x>>2]+(x&3)*2);
          if(y==WPB){ EXPU SPIN(t0,0) }
        }
      } else {
        #pragma unroll
        for(int y=0;y<24;y++){
          const int i=WGO?(y&1):(y>=12), x=WGO?(y>>1):(y%12);
          if(x==0) wg32_rs0(u[i],pw[16+i],vb[0]); else wg32_rs(u[i],pw[16+x*2+i],vb[x>>2]+(x&3)*2);
          if(y==WPA&&warp!=3){ EXPU EXPK }
        }
      }
      asm volatile("wgmma.commit_group.sync.aligned;":::"memory");
      TFP(18);
      if(!MG&&warp==3){
        EXPK
        if(lane==0&&s+2<NSEG){ tma2d_pfh(&tmK,h*DH+64*c,(s+2)*32,HP&1?PL_EF:PL_EN); tma2d_pfh(&tmV,h*DH+64*c,(s+2)*32,HP&2?PL_EF:PL_EN); }
        __syncwarp();
        if(b<80&&lane<2&&s+2<NSEG) asm volatile("prefetch.global.L2 [%0];"::"l"(g_acc+(size_t)(s+2)*2560+b*32+lane*16));
      }
      PLD
    }
    const uint32_t mx=s16+SM_RED+kq*4096, m5=m5u+lane*8;
    {
      asm volatile("wgmma.wait_group.sync.aligned 0;":::"memory");
      TFP(19);
      if(MG||warp!=3){
        if(UEX) asm volatile("cp.async.bulk.wait_group 0;":::"memory");
        bar_sync(7,256);
        TFP(20);
        #pragma unroll
        for(int i=0;i<2;i++)
          #pragma unroll
          for(int kk=0;kk<2;kk++)
            stsm4(us+i*1024+kk*256,pack_bf16(u[i][8*kk],u[i][8*kk+1]),pack_bf16(u[i][8*kk+2],u[i][8*kk+3]),pack_bf16(u[i][8*kk+4],u[i][8*kk+5]),pack_bf16(u[i][8*kk+6],u[i][8*kk+7]));
        if(UEX){ fence_async(); if(UBP==0) UBULK }
        #pragma unroll
        for(int i=0;i<8;i++) lds4r(buf[i],qs+i*512);
      } else {
        #pragma unroll
        for(int i=0;i<8;i++) lds4r(buf[i],qs+i*512);
        bar_sync(7,256);
        asm volatile("{\n.reg .pred p, q;\nsetp.eq.u32 p, %0, 0;\nsetp.eq.and.u32 q, %1, 0, p;\n@q fence.release.gpu;\n@p st.relaxed.gpu.global.u32 [%2], %3;\n}"::"r"(lane),"r"((s&3)|NOF),"l"(g_flag+b*32),"r"(s):"memory");
      }
      SPIN(t0,pd)
      TFP(17);
    }
    uint32_t mb[10][2];
    {
      auto okf=[&](const uint4& v){ return ((v.x|v.z)&63u)==0; };
      const int np=poll2<5>(m,[&](int i){ return ldg_rlx4((const uint32_t*)(src+i*512)); },okf,dead,1);
      TW(0); PC(0); TFP(14);
      if(ADP){ if(np) pd=min(pd+ADUP,2000u); else pd=max(pd-ADDN,(uint32_t)ADP); }
      #pragma unroll
      for(int p=0;p<5;p++){
        mb[p][0]=pack_bf16((float)(int)__funnelshift_r(m[p].x,m[p].y,3),(float)(int)m[p].y);
        mb[p][1]=pack_bf16((float)(int)__funnelshift_r(m[p].z,m[p].w,3),(float)(int)m[p].w);
        if(p==0) sts2(MG?m5:mx-lane*8+3072,mb[0][0],mb[0][1]);
        if(p==2||p==4) sts4(mx+((MG?0:4)+(p>>2))*512,make_uint4(mb[p-1][0],mb[p-1][1],mb[p][0],mb[p][1]));
      }
      bar_arrive((MG?12:8)+kq,64);
      if(UEX&&UBP==1&&(MG||warp!=3)) UBULK
    }
    #define XGET { bar_sync((MG?8:12)+kq,64); const uint2 x=lds2(MG?mx-lane*8+3072:m5); mb[5][0]=x.x; mb[5][1]=x.y; \
      _Pragma("unroll") for(int p=0;p<2;p++){ const uint4 y=lds4(mx+((MG?4:0)+p)*512); mb[6+2*p][0]=y.x; mb[6+2*p][1]=y.y; mb[7+2*p][0]=y.z; mb[7+2*p][1]=y.w; } }
    #define XMAX { uint32_t a=amax2(amax2(amax2(mb[0][0],mb[0][1]),amax2(mb[1][0],mb[1][1])),amax2(amax2(amax2(mb[2][0],mb[2][1]),amax2(mb[3][0],mb[3][1])),amax2(mb[4][0],mb[4][1]))); \
      a=__reduce_max_sync(~0u,max(a&0x7fff0000u,(a<<16)&0x7fff0000u)); if(lane==0) sts1(sb+SM_MX+warp*4,a); }
    TS(0); TF(0);
    float acc[4][4]; uint32_t ux[2][2][4];
    #pragma unroll
    for(int i=0;i<4;i++){ acc[i][0]=acc[i][1]=acc[i][2]=acc[i][3]=0.f; }
    #define UXDEP (((ux[0][0][0]^ux[0][1][0])^(ux[1][0][0]^ux[1][1][0]))&zero)
    if constexpr(MG){
      #pragma unroll
      for(int y=0;y<10;y++){
        const int k=KP==4?(y<2?y:(y<4?y+4:(y<6?y-2:(y<8?y+2:y-4)))):(y<2?y:(y<2+KP?y+8-KP:y-KP));
        #pragma unroll
        for(int j=0;j<4;j++){
          if(k<10-KP){ mma16816(acc[j],buf[(k&1)*4+j],MB0(k),MB1(k)); lds4r(buf[(k&1)*4+j],qs+(k*4+j+8)*512); }
          else mma16816(acc[j],pw[k>=10-KP?(k-10+KP)*4+j:0],MB0(k),MB1(k));
        }
        if(y==XGP) XGET
        if(y==5) XMAX
        if(UEX&&UBP==y+2) UBULK
      }
      TF(1);
      {
        const uint32_t ra=s16+SM_KRED+kq*2048;
        #pragma unroll
        for(int i=0;i<4;i++) sts4f(ra+i*512,acc[i]);
      }
      bar_arrive(1,256);
#define VK(u) ((u)>>2)
      #pragma unroll
      for(int i=0;i<4;i++){ acc[i][0]=acc[i][1]=acc[i][2]=acc[i][3]=0.f; }
      #pragma unroll
      for(int y=0;y<40;y++){
        constexpr int NS_=4*KP;
        const int u=y<8?y:(y<20?y-8+NS_:(y<12+NS_?y-12:y));
        const int sl=(u+40-NS_)&7;
        if(u<NS_){ mma16816(acc[u&3],buf[sl],MB0(VK(u)),MB1(VK(u))); if(u+8<NS_) lds4r(buf[sl],qs+(48-NS_+u)*512); }
        else mma16816(acc[u&3],pw[u],MB0(VK(u)),MB1(VK(u)));
        if(y>=OPF&&y<OPF+8) ldsm4(buf[(y-OPF)&7],os+((y-OPF)&7)*256);
        if(y>=UXP&&y<UXP+4) ldsm4(ux[(y-UXP)>>1][(y-UXP)&1],us+((y-UXP)>>1)*1024+((y-UXP)&1)*256);
      }
      TF(2);
      const uint32_t ra=s16+SM_RED+1536;
      #pragma unroll
      for(int i=1;i<4;i++) sts4f(ra+kq*4096+i*512,acc[i]);
      bar_sync(3,128);
      const float cs=__uint_as_float(lds1(sb+SM_SCL+8+(s&1)*4));
      float4 c1=lds4f(ra+((kq+3)&3)*4096+512), d2=lds4f(ra+((kq+2)&3)*4096+1024), e2=lds4f(ra+((kq+1)&3)*4096+1536);
      const uint32_t p0=pack_bf16(((acc[0][0]+c1.x)+(d2.x+e2.x))*cs,((acc[0][1]+c1.y)+(d2.y+e2.y))*cs), p1=pack_bf16(((acc[0][2]+c1.z)+(d2.z+e2.z))*cs,((acc[0][3]+c1.w)+(d2.w+e2.w))*cs);
      if(UEX) asm volatile("cp.async.bulk.wait_group.read 0;":::"memory");
      bar_arrive(2+UXDEP,256);
      const uint32_t v0=movm(p0), v1=movm(p1);
      const uint32_t off=SM_VMX+(kq>>1)*512+lane*16+(kq&1)*8;
      #pragma unroll
      for(int r=0;r<2;r++) st_async2(rsc[r]+off+(2-r)*1024,v0,v1,rsc[r]+SM_MB+16);
      sts2(sb+off,v0,v1); __syncwarp(); if(lane==0) mbar_arrive(XL);
      TF(5);
      if(OPF>=40){
        #pragma unroll
        for(int i=0;i<8;i++) ldsm4(buf[i],os+i*256);
      }
    } else {
      uint32_t kb[8];
      #pragma unroll
      for(int y=0;y<10;y++){
        const int k=y<2?y:(y<4?y+4:(y<6?y-2:(y<8?y+2:y-4)));
        #pragma unroll
        for(int j=0;j<4;j++){
          if(k<6){ mma16816(acc[j],buf[(k&1)*4+j],MB0(k),MB1(k)); if(k<4) lds4r(buf[(k&1)*4+j],qs+(k*4+j+8)*512); }
          else mma16816(acc[j],pw[k>=6?(k-6)*4+j:0],MB0(k),MB1(k));
        }
        if(y==7){
          const uint32_t ka=sb+SM_KX+(8*kq+(lane&7))*128+((((lane>>3)^(2*kq))^(lane&7))<<4);
          ldsm4(kb,ka); ldsm4(kb+4,ka^64);
        }
        if(y==XGP) XGET
        if(y==5) XMAX
        if(UEX&&UBP==y+2&&warp!=3) UBULK
      }
      TF(1);
      {
        const uint32_t qa=s16+SM_RED+kq*4096+1024;
        #pragma unroll
        for(int i=0;i<2;i++) stsm4(qa+i*512,pack_bf16(acc[2*i][0],acc[2*i][1]),pack_bf16(acc[2*i][2],acc[2*i][3]),pack_bf16(acc[2*i+1][0],acc[2*i+1][1]),pack_bf16(acc[2*i+1][2],acc[2*i+1][3]));
      }
      TF(2);
      bar_sync(1,256);
      TS(1); TF(3);
      const uint32_t ra=s16+SM_KRED+kq*512;
      const float cs=__uint_as_float(lds1(sb+SM_SCL+8+(s&1)*4));
      float4 a3=lds4f(ra), c3=lds4f(ra+2048), d3=lds4f(ra+4096), e3=lds4f(ra+6144);
      uint32_t q[4][2][4];
      #pragma unroll
      for(int i=0;i<4;i++){ ldsm4t(q[i][0],qrd^(i*256)); ldsm4t(q[i][1],(qrd^(i*256))+8192); }
      const uint32_t p2=pack_bf16(((a3.x+c3.x)+(d3.x+e3.x))*cs,((a3.y+c3.y)+(d3.y+e3.y))*cs), p3=pack_bf16(((a3.z+c3.z)+(d3.z+e3.z))*cs,((a3.w+c3.w)+(d3.w+e3.w))*cs);
      const uint32_t f2=movm(p2), f3=movm(p3);
      ex0=f2; ex1=f3;
      float sc[6][4];
      #pragma unroll
      for(int i=0;i<6;i++){ sc[i][0]=sc[i][1]=sc[i][2]=sc[i][3]=0.f; }
      #pragma unroll
      for(int i=0;i<4;i++)
        #pragma unroll
        for(int jp=0;jp<2;jp++){
          mma16816(sc[(i&1)*2+jp],q[i][jp],kb[2*i],kb[2*i+1]);
          if(i==1) mma16816(sc[4+jp],q[0][jp],f2,f3);
        }
      const uint32_t w0=__float_as_uint(((sc[0][0]+sc[0][2])+(sc[1][0]+sc[1][2]))+((sc[2][0]+sc[2][2])+(sc[3][0]+sc[3][2]))), w1=__float_as_uint(((sc[0][1]+sc[0][3])+(sc[1][1]+sc[1][3]))+((sc[2][1]+sc[2][3])+(sc[3][1]+sc[3][3])));
      const uint32_t w2=__float_as_uint((sc[4][0]+sc[4][2])+(sc[5][0]+sc[5][2])), w3=__float_as_uint((sc[4][1]+sc[4][3])+(sc[5][1]+sc[5][3]));
      const uint32_t off=SM_SCX+(c*4+kq)*512+lane*16;
      #pragma unroll
      for(int r=0;r<2;r++) st_async4(rsc[r]+off,w0,w1,w2,w3,rsc[r]+SM_MB);
      sts4(sb+off,make_uint4(w0,w1,w2,w3)); __syncwarp(); if(lane==0) mbar_arrive(XS);
      TS(2); TF(5);
    }
    if(!MG&&warp==3){
      bar_arrive(2,256);
      const float ssc=0.07216878364870322f*__uint_as_float(lds1(sb+SM_SCL+8+(s&1)*4));
      uint32_t kvc; asm volatile("ld.relaxed.gpu.global.u32 %0, [%1];":"=r"(kvc):"l"(g_cnt+C_KV+(((s>>2)+1)&15)):"memory");
      TF(6);
      { int gd=0; while(!mbar_try(XS,s&1)){ if(dead) break; if(++gd>GUARD){ dead=true; g_err=2; } } }
      TF(7);
      float sv[10];
      {
        float4 u[12];
        #pragma unroll
        for(int n=0;n<12;n++) u[n]=lds4f(s16+SM_SCX+n*512);
        uint32_t r[5];
        #pragma unroll
        for(int n=0;n<4;n++) r[n+1]=pack_bf16((u[n].x+u[4+n].x)+u[8+n].x,(u[n].y+u[4+n].y)+u[8+n].y);
        r[0]=pack_bf16((((u[0].z+u[1].z)+(u[2].z+u[3].z))+((u[4].z+u[5].z)+(u[6].z+u[7].z)))+((u[8].z+u[9].z)+(u[10].z+u[11].z)),
                       (((u[0].w+u[1].w)+(u[2].w+u[3].w))+((u[4].w+u[5].w)+(u[6].w+u[7].w)))+((u[8].w+u[9].w)+(u[10].w+u[11].w)));
        #pragma unroll
        for(int n=0;n<5;n++){
          const uint32_t w=pack_bf16(__uint_as_float(r[n]<<16)*ssc,__uint_as_float(r[n]&0xffff0000u)*ssc);
          sv[2*n]=__uint_as_float(w<<16); sv[2*n+1]=__uint_as_float(w&0xffff0000u);
        }
      }
      TF(8);
      float mx=fmaxf(fmaxf(fmaxf(sv[2],sv[3]),fmaxf(sv[4],sv[5])),fmaxf(fmaxf(fmaxf(sv[6],sv[7]),fmaxf(sv[8],sv[9])),fmaxf(sv[0],sv[1])));
      mx=fmaxf(mx,__shfl_xor_sync(~0u,mx,1)); mx=fmaxf(mx,__shfl_xor_sync(~0u,mx,2));
      mx*=-1.4426950408889634f;
      #pragma unroll
      for(int i=0;i<10;i++) sv[i]=ex2(fmaf(sv[i],1.4426950408889634f,mx));
      sts1(sb+SM_PM+lane*4,pack_bf16(sv[0],sv[1]));
      sts4(s16+SM_P,make_uint4(pack_bf16(sv[2],sv[3]),pack_bf16(sv[4],sv[5]),pack_bf16(sv[6],sv[7]),pack_bf16(sv[8],sv[9])));
      TF(9);
      bar_sync(4,256);
      asm volatile("mov.u32 %0, %%clock;":"=r"(t0)); t0+=W3O;
      TF(11);
      if(lane==0){
        mbar_expect(XS,4096); mbar_expect(XV,2048);
        if((s&3)==2){ int gd=0; while(kvc<64&&s<NSEG-4){ kvc=ld_acq(g_cnt+C_KV+(s>>2)+1); if(++gd>GUARD){ g_err=7; break; } } fence_acq(); fence_async_g(); }
      }
      __syncwarp();
      eo2=(uint32_t)(s*98304+h*3072+(4*c+kq)*256+((s16-sb)>>2))^zero;
      TF(13);
    } else {
      if constexpr(!MG){
        #pragma unroll
        for(int i=0;i<2;i++){ ldsm4(ux[i][0],us+i*1024); ldsm4(ux[i][1],us+i*1024+256); }
        if(s==0&&warp==2){
          int gd=0; uint32_t x[6];
          #pragma unroll 1
          while(true){
            bool ok=true;
            #pragma unroll
            for(int i=0;i<6;i++){ asm volatile("ld.relaxed.gpu.global.u32 %0, [%1];":"=r"(x[i]):"l"(g_nrm+lane*6+i):"memory"); ok=ok&&x[i]!=SENT; }
            if(__all_sync(~0u,ok)) break;
            if(++gd>GUARD){ g_err=8; break; }
          }
          const float cw=27.5f*sqrtf((__uint_as_float(x[0])+__uint_as_float(x[2]))+__uint_as_float(x[4]))*sqrtf(__uint_as_float(max(x[1],max(x[3],x[5]))));
          sts1(sb+SM_SCL+4,__reduce_max_sync(~0u,__float_as_uint(cw)&0x7fffffffu));
          __syncwarp();
        }
        {
          const uint4 x=lds4(sb+SM_MX), y=lds4(sb+SM_MX+16); const float cw=__uint_as_float(lds1(sb+SM_SCL+4)), cs=__uint_as_float(lds1(sb+SM_SCL+8+(s&1)*4));
          const float mm=__uint_as_float(max(max(max(x.x,x.y),max(x.z,x.w)),max(max(y.x,y.y),max(y.z,y.w))))*cs;
          const uint32_t eo=min(max((__float_as_uint(cw*fmaxf(mm,1.f))>>23)&255u,37u),254u)-21u;
          if(tid==64){ sts1(sb+SM_SCL,eo*0x00800080u); sts1(sb+SM_SCL+12-(s&1)*4,(eo-3u)<<23); }
        }
        TF(4);
        if(UEX) asm volatile("cp.async.bulk.wait_group.read 0;":::"memory");
        bar_sync(2+UXDEP,256);
        if(!last&&lane==0){
          tma2dh(sb+SM_VX+kq*4096,&tmV,h*DH+64*kq,(s+1)*32,KVB,HV?PL_EF:PL_EN);
          if(kq==0) mbar_expect(KVB,32*512);
          if(kq==1) tma2dh(sb+SM_KX,&tmK,h*DH+64*c,(s+1)*32,KVB,HK?PL_EF:PL_EN);
        }
        __syncwarp();
      }
      float ca[2][2][4];
      #pragma unroll
      for(int i=0;i<2;i++)
        #pragma unroll
        for(int j=0;j<2;j++){ ca[i][j][0]=ca[i][j][1]=ca[i][j][2]=ca[i][j][3]=0.f; }
      TF(6);
      { int gd=0; while(!mbar_try(XL,s&1)){ if(dead) break; if(++gd>GUARD){ dead=true; g_err=5; } } }
      TF(7);
      uint4 vm[6];
      vm[0]=lds4(s16+SM_VMX); vm[1]=lds4(s16+SM_VMX+512);
      #define VB0(x) (((x)&1)?vm[(x)>>1].z:vm[(x)>>1].x)
      #define VB1(x) (((x)&1)?vm[(x)>>1].w:vm[(x)>>1].y)
      if constexpr(MG){
        #pragma unroll
        for(int x=0;x<12;x++){
          if(x==4){
            TF(8);
            { int gd=0; while(!mbar_try(XV,s&1)){ if(dead) break; if(++gd>GUARD){ dead=true; g_err=3; } } }
            TF(9);
            #pragma unroll
            for(int i=2;i<6;i++) vm[i]=lds4(s16+SM_VMX+i*512);
          }
          #pragma unroll
          for(int i=0;i<2;i++){
            mma16816(ca[i][x&1],buf[(x*2+i)&7],VB0(x),VB1(x));
            if(x<8) ldsm4(buf[(x*2+i)&7],os+(x*2+i+8)*256);
          }
        }
      } else {
        #pragma unroll
        for(int x=0;x<12;x++){
          if(x==4){
            TF(8);
            { int gd=0; while(!mbar_try(XV,s&1)){ if(dead) break; if(++gd>GUARD){ dead=true; g_err=3; } } }
            TF(9);
            #pragma unroll
            for(int i=2;i<6;i++) vm[i]=lds4(s16+SM_VMX+i*512);
          }
          #pragma unroll
          for(int i=0;i<2;i++) mma16816(ca[i][x&1],pw[16+x*2+i],VB0(x),VB1(x));
        }
      }
      TF(10);
      bar_sync(4,256);
      TS(3); TF(11);
      const uint4 pq=lds4(s16+SM_P); const uint32_t pm=lds1(sb+SM_PM+lane*4), on=lds1(sb+SM_SCL);
      kvok=mbar_test(KVB,(s&1)^1);
      const uint32_t one[4]={on,on,on,on};
      float d[2][4], e[4];
      #pragma unroll
      for(int i=0;i<4;i++){ d[0][i]=0.f; d[1][i]=0.f; e[i]=0.f; }
      mma16816(e,one,pq.x,pq.y); mma16816(d[0],ux[0][0],pq.x,pq.y); mma16816(d[1],ux[1][0],pq.x,pq.y);
      mma16816(e,one,pq.z,pq.w); mma16816(d[0],ux[0][1],pq.z,pq.w); mma16816(d[1],ux[1][1],pq.z,pq.w);
      mma1688(e,one[0],one[0],pm);
      #pragma unroll
      for(int i=0;i<2;i++){ um[i][0]=pack_bf16(ca[i][0][0]+ca[i][1][0],ca[i][0][1]+ca[i][1][1]); um[i][1]=pack_bf16(ca[i][0][2]+ca[i][1][2],ca[i][0][3]+ca[i][1][3]); mma1688(d[i],um[i][0],um[i][1],pm); }
      const float i0=rcp(e[0]), i1=rcp(e[1]);
      TF(12);
      const uint32_t ro=(tile0+2*wt)*512+t*64+g*8;
      char* dst=(char*)g_acc+(uint32_t)((s+1)*20480+ro);
      #pragma unroll
      for(int i=0;i<2;i++){
        if(!last&&(i==0||2*wt+1<ntile)){
          red64(dst+i*512,(__float_as_uint(fmaf(d[i][0],i0,12582912.f))<<6)+1u,__float_as_uint(fmaf(d[i][2],i0,12582912.f))<<3);
          red64(dst+i*512+256,(__float_as_uint(fmaf(d[i][1],i1,12582912.f))<<6)+1u,__float_as_uint(fmaf(d[i][3],i1,12582912.f))<<3);
        }
      }
      asm volatile("mov.u32 %0, %%clock;":"=r"(t0));
      {
        const uint32_t z=t0&zero;
        eo1=(uint32_t)(s*1638400+(32+(h>>2))*40960+(tile0+2*wt)*1024+(h&3)*128+((s16-sb)>>2))^z;
        if(!MG) eo2=(uint32_t)(s*98304+h*3072+(4*c+kq)*256+((s16-sb)>>2))^z;
      }
      TW(1);
      TS(4); TF(13);
    }
    so+=20480;
  }
  if(MG||warp!=3) EXPU
  if(!MG) EXPK
  };
  { if(mg) loop(IC<1>{}); else loop(IC<0>{}); }
  asm volatile("cp.async.bulk.wait_group 0;":::"memory");
  __syncthreads();
  if(tid==FW*32){ fence_rel(); stg_rlx1(g_flag+b*32,NSEG); }
  GT(2);
  cluster_sync();
}

#define KLEAD 16
#define MLEAD 16
#define FAG fence_async_g
#define KVQ 1024
#define ROT 38
#define ROT0 3
#define FNS 40
#define CONT 1
enum { M_XN=0,M_WK,M_WV,M_K,M_V,M_Y,M_H,M_H2,M_GATE,M_WQ,M_W1,M_W2,M_W2B,M_U1,M_U2,M_U5,M_U10,M_NUM,M_OUT };
struct WParams { CUtensorMap m[M_NUM]; const bf16* x; const bf16* b1; const bf16* b2; bf16* out; int pair; };
enum { T_RED=0,T_OP=1,T_QA=2,T_M2=3,T_M1=4,T_KV=5,T_END=6 };
#define KVR 5
#define KVJ 32
constexpr int KVUP=128*KVR;
#define TRIG 10
#define SOV 1
#define LATE 15
#define E15 4
#define OPE 15
#define Q15 3
#define HB 1
#define EARLY 2
constexpr int NRB=16;
constexpr int STG=45056, NST=4, SLOT=24576, BOXS=8192;
constexpr int W_SLOT=NST*STG;
constexpr int W_BAR=W_SLOT+2*SLOT;
constexpr int W_TOTAL=W_BAR+1024;
static_assert(W_TOTAL<=232448,"smem");
#define ST(i)
#define QT(i)
__device__ __forceinline__ void stsm4n(uint32_t a,uint32_t r0,uint32_t r1,uint32_t r2,uint32_t r3){ asm volatile("stmatrix.sync.aligned.m8n8.x4.shared.b16 [%0], {%1,%2,%3,%4};"::"r"(a),"r"(r0),"r"(r1),"r"(r2),"r"(r3)); }
#define WGUARD 2000000
__host__ __device__ constexpr int n_uns(){ int n=0; while(n<16&&nsp(n)==1) n++; return n; }
__host__ __device__ constexpr int n_op(){ int n=0; for(int r=0;r<NRB;r++) n+=4*nsp(r); return n; }
__host__ __device__ constexpr int n_red(){ return 0; }
__host__ __device__ constexpr int pu_st(int ns){ return ns==1?40:(ns==2?20:(ns==5?10:8)); }

__device__ __forceinline__ void wg_arrive(){ asm volatile("wgmma.fence.sync.aligned;":::"memory"); }
__device__ __forceinline__ void wg_commit(){ asm volatile("wgmma.commit_group.sync.aligned;":::"memory"); }
template<int N> __device__ __forceinline__ void wg_wait(){ asm volatile("wgmma.wait_group.sync.aligned %0;"::"n"(N):"memory"); }
__device__ __forceinline__ void mbar_wait(uint32_t a,uint32_t par){ int gd=0; while(!mbar_try(a,par)){ if(++gd>WGUARD){ g_err=20; break; } } }
__device__ __forceinline__ uint32_t ld_rlx(const uint32_t* p){ uint32_t v; asm volatile("ld.relaxed.gpu.global.u32 %0, [%1];":"=r"(v):"l"(p):"memory"); return v; }
__device__ __forceinline__ float4 ld_rlx4f(const float4* p){ float4 v; asm volatile("ld.relaxed.gpu.global.v4.f32 {%0,%1,%2,%3}, [%4];":"=f"(v.x),"=f"(v.y),"=f"(v.z),"=f"(v.w):"l"(p):"memory"); return v; }
__device__ __forceinline__ void red_rel(uint32_t* p){ asm volatile("red.release.gpu.global.add.u32 [%0], 1;"::"l"(p):"memory"); }
__device__ __forceinline__ void tma_st(const CUtensorMap* tm,uint32_t src,int c0,int c1){
  asm volatile("cp.async.bulk.tensor.2d.global.shared::cta.bulk_group [%0, {%2, %3}], [%1];"::"l"(tm),"r"(src),"r"(c0),"r"(c1):"memory"); }
#define KEF 4
__device__ __forceinline__ void tma_st_ef(const CUtensorMap* tm,uint32_t src,int c0,int c1){
  asm volatile("{\n.reg .b64 pl;\ncreatepolicy.fractional.L2::evict_first.b64 pl, 1.0;\ncp.async.bulk.tensor.2d.global.shared::cta.bulk_group.L2::cache_hint [%0, {%2, %3}], [%1], pl;\n}"::"l"(tm),"r"(src),"r"(c0),"r"(c1):"memory"); }
__device__ __forceinline__ void bulk_commit(){ asm volatile("cp.async.bulk.commit_group;":::"memory"); }
__device__ __forceinline__ void bulk_wait_rd(){ asm volatile("cp.async.bulk.wait_group.read 0;":::"memory"); }
__device__ __forceinline__ void bulk_wait(){ asm volatile("cp.async.bulk.wait_group 0;":::"memory"); }
__device__ __forceinline__ void mbar_arrive_cl(uint32_t a){ asm volatile("mbarrier.arrive.shared::cluster.b64 _, [%0];"::"r"(a):"memory"); }
__device__ __forceinline__ void tma4d(uint32_t dst,const CUtensorMap* tm,int c2,int c3,uint32_t mb){
  asm volatile("cp.async.bulk.tensor.4d.shared::cluster.global.mbarrier::complete_tx::bytes [%0], [%1, {0, 0, %3, %4}], [%2];"::"r"(dst),"l"(tm),"r"(mb),"r"(c2),"r"(c3):"memory"); }
__device__ __forceinline__ void tma4dm(uint32_t dst,const CUtensorMap* tm,int c2,int c3,uint32_t mb){
  asm volatile("cp.async.bulk.tensor.4d.shared::cluster.global.mbarrier::complete_tx::bytes.multicast::cluster [%0], [%1, {0, 0, %3, %4}], [%2], %5;"::"r"(dst),"l"(tm),"r"(mb),"r"(c2),"r"(c3),"h"((uint16_t)3):"memory"); }

template<int N> __device__ __forceinline__ void mainloop(float* acc,int nkb,uint32_t sb,int lane,uint32_t pos,uint32_t eb){
  uint32_t pst=0;
  #pragma unroll
  for(int i=0;i<N/2;i++){ acc[i]=0.f; acc[96+i]=0.f; }
  #pragma unroll 1
  for(int kb=0;kb<nkb;kb++,pos++){
    const uint32_t st=pos&3;
    mbar_wait(sb+W_BAR+st*8,(pos>>2)&1);
    if(kb==nkb-1&&(threadIdx.x&127)==0) mbar_arrive(sb+W_BAR+144);
    const uint32_t a=sb+st*STG;
    const uint32_t da=((a>>4)&0x3fff)|(1u<<16);
    const uint32_t db=da+1024+(255u<<16);
    wg_arrive();
    #pragma unroll
    for(int k=0;k<4;k++){ wgmma<N>(acc,da+2*k,db+(k>>1)*N*4+(k&1)*128,kb|k); wgmma<N>(acc+96,da+512+2*k,db+(k>>1)*N*4+(k&1)*128,kb|k); }
    wg_commit();
    if(kb>0){ wg_wait<1>(); if(lane<2) mbar_arrive_cl(eb+pst*8); }
    pst=st;
  }
  wg_wait<0>();
  if(lane<2) mbar_arrive_cl(eb+pst*8);
}
__device__ __forceinline__ uint32_t act2(uint32_t u,uint32_t bb,float c1,float c3){
  uint32_t s; asm("add.rn.bf16x2 %0, %1, %2;":"=r"(s):"r"(u),"r"(bb));
  float r[2]={__uint_as_float(s<<16), __uint_as_float(s&0xffff0000u)};
  #pragma unroll
  for(int i=0;i<2;i++){
    const float z=r[i]*fmaf(r[i]*r[i],c3,c1);
    r[i]=r[i]*rcp(1.f+ex2(z));
  }
  return pack_bf16(r[0],r[1]);
}
__device__ __forceinline__ uint32_t fin1(uint32_t s,uint32_t x,uint32_t gq){
  const uint32_t p=pack_bf16(__uint_as_float(s<<16)*__uint_as_float(gq<<16),__uint_as_float(s&0xffff0000u)*__uint_as_float(gq&0xffff0000u));
  return pack_bf16(__uint_as_float(x<<16)+__uint_as_float(p<<16),__uint_as_float(x&0xffff0000u)+__uint_as_float(p&0xffff0000u));
}
template<int NT> __device__ __forceinline__ void stage_pk(const uint32_t* p,uint32_t ra,int lane){
  const int sw=lane&7, hi=lane>>4;
  #pragma unroll
  for(int T=0;T<NT;T++) stsm4n(ra+(T>>2)*BOXS+((((2*T+hi)&7)^sw)<<4),p[4*T],p[4*T+1],p[4*T+2],p[4*T+3]);
}
__device__ __noinline__ void post_pass(uint32_t sl,int nbox,uint32_t ba,float c1,float c3){
  const int lane=threadIdx.x&31, r=lane>>3, c=lane&7;
  __syncwarp();
  #pragma unroll 1
  for(int j=0;j<nbox;j++){
    uint4 u[4]; uint32_t a[4];
    #pragma unroll
    for(int i=0;i<4;i++){ const int rr=4*i+r; a[i]=sl+j*BOXS+rr*128+((c^(rr&7))<<4); u[i]=lds4(a[i]); }
    const uint4 bb=lds4(ba+j*128+c*16);
    #pragma unroll
    for(int i=0;i<4;i++){
      uint4& v=u[i];
      v.x=act2(v.x,bb.x,c1,c3); v.y=act2(v.y,bb.y,c1,c3); v.z=act2(v.z,bb.z,c1,c3); v.w=act2(v.w,bb.w,c1,c3);
      sts4(a[i],v);
    }
  }
}
__device__ __forceinline__ void wg32_pu(float* d,uint32_t da,uint32_t db,int sc){
  asm volatile("{\n.reg .pred p;\n.reg .b64 xa, xb;\nmov.b64 xa, {%16, 32};\nmov.b64 xb, {%17, 8};\nsetp.ne.b32 p, %18, 0;\nwgmma.mma_async.sync.aligned.m64n32k16.f32.bf16.bf16 {%0,%1,%2,%3,%4,%5,%6,%7,%8,%9,%10,%11,%12,%13,%14,%15}, xa, xb, p, 1, 1, 0, 0;\n}"
   :"+f"(d[0]),"+f"(d[1]),"+f"(d[2]),"+f"(d[3]),"+f"(d[4]),"+f"(d[5]),"+f"(d[6]),"+f"(d[7]),"+f"(d[8]),"+f"(d[9]),"+f"(d[10]),"+f"(d[11]),"+f"(d[12]),"+f"(d[13]),"+f"(d[14]),"+f"(d[15])
   :"r"(da),"r"(db),"r"(sc));
}
__device__ __forceinline__ void wg16_rs(float* d,const uint32_t* a,uint32_t db,int sc){
  asm volatile("{\n.reg .pred p;\n.reg .b64 xb;\nmov.b64 xb, {%12, 192};\nsetp.ne.b32 p, %13, 0;\nwgmma.mma_async.sync.aligned.m64n16k16.f32.bf16.bf16 {%0,%1,%2,%3,%4,%5,%6,%7}, {%8,%9,%10,%11}, xb, p, 1, 1, 0;\n}"
   :"+f"(d[0]),"+f"(d[1]),"+f"(d[2]),"+f"(d[3]),"+f"(d[4]),"+f"(d[5]),"+f"(d[6]),"+f"(d[7]):"r"(a[0]),"r"(a[1]),"r"(a[2]),"r"(a[3]),"r"(db),"r"(sc));
}
__device__ __forceinline__ void stsm4t(uint32_t a,uint32_t r0,uint32_t r1,uint32_t r2,uint32_t r3){ asm volatile("stmatrix.sync.aligned.m8n8.x4.trans.shared.b16 [%0], {%1,%2,%3,%4};"::"r"(a),"r"(r0),"r"(r1),"r"(r2),"r"(r3):"memory"); }
template<int NS> __device__ __forceinline__ void pu_item(const WParams& P,int rbk,int a,uint32_t pos,uint32_t sb,int tid,uint32_t& e0,int& sq){
  constexpr int MT=10/NS, NKB=pu_st(NS), BPS=40/NKB, H0=(MT+1)/2;
  const int lane=tid&31, wg=tid>>7, wq=(tid>>5)&3;
  const int seg=rbk*4+a/NS, part=a%NS;
  const uint32_t go=(uint32_t)((seg*32+wq*8+(lane>>3))*D+part*MT*64+(lane&7)*8);
  uint4 xx[MT][2], gg[MT][2];
  auto ldx=[&](int m){
    #pragma unroll
    for(int j=m*H0;j<m*H0+H0&&j<MT;j++)
      #pragma unroll
      for(int i=0;i<2;i++){ const uint32_t o=go+i*4*D+j*64; xx[j][i]=ldg_rlx4((const uint32_t*)(P.x+o)); gg[j][i]=ldg_rlx4((const uint32_t*)(g_gate+o)); }
  };
  if(NS>1){ ldx(0); ldx(1); }
  float acc[MT][16];
  #pragma unroll
  for(int i=0;i<MT*16;i++) acc[i>>4][i&15]=0.f;
  uint32_t pst=0;
  #pragma unroll 1
  for(int kb=0;kb<NKB;kb++,pos++){
    const uint32_t st=pos&3;
    mbar_wait(sb+W_BAR+st*8,(pos>>2)&1);
    if(kb==NKB-1&&(tid&127)==0) mbar_arrive(sb+W_BAR+144);
    const uint32_t sa=((sb+st*STG)>>4)&0x3fff, da=sa|(8u<<16), db=(sa+BPS*MT*256)|(32u<<16);
    wg_arrive();
    #pragma unroll
    for(int j=0;j<BPS;j++)
      #pragma unroll
      for(int k=0;k<2;k++)
        #pragma unroll
        for(int m=0;m<MT;m++) wg32_pu(acc[m],da+(j*MT+m)*256+k*16,db+j*128+k*64,kb|j|k);
    wg_commit();
    if(kb>0){ wg_wait<1>(); if(lane<2) mbar_arrive(sb+W_BAR+32+pst*8); }
    pst=st;
  }
  wg_wait<0>();
  if(lane<2) mbar_arrive(sb+W_BAR+32+pst*8);
  const uint32_t wa=sb+W_SLOT+((lane>>4)*8+(lane&7))*128+(((2*wq+((lane>>3)&1))^(lane&7))<<4);
  const uint32_t rd=sb+W_SLOT+(wq*8+(lane>>3))*128+(((lane&7)^(lane>>3))<<4);
  #pragma unroll
  for(int m=0;m<2;m++){
    mbar_wait(sb+W_BAR+96+wg*16+m*8,e0);
    if(m*H0<MT){
      #pragma unroll
      for(int j=0;j<H0&&m*H0+j<MT;j++){ const float* q=acc[m*H0+j<MT?m*H0+j:0];
        #pragma unroll
        for(int i=0;i<2;i++) stsm4t(wa+m*SLOT+j*4096+i*2048,pack_bf16(q[8*i],q[8*i+1]),pack_bf16(q[8*i+2],q[8*i+3]),pack_bf16(q[8*i+4],q[8*i+5]),pack_bf16(q[8*i+6],q[8*i+7])); }
      if(NS==1) ldx(m);
      bar_sync(8+wg,128);
      #pragma unroll
      for(int j=0;j<H0&&m*H0+j<MT;j++)
        #pragma unroll
        for(int i=0;i<2;i++){
          const uint4 u=lds4((rd^(i*64))+m*SLOT+j*4096+i*512), x=xx[m*H0+j<MT?m*H0+j:0][i], g=gg[m*H0+j<MT?m*H0+j:0][i];
          *(uint4*)(P.out+go+i*4*D+(m*H0+j)*64)=make_uint4(fin1(u.x,x.x,g.x),fin1(u.y,x.y,g.y),fin1(u.z,x.z,g.z),fin1(u.w,x.w,g.w));
        }
    }
    bar_arrive(sq,160); sq^=1;
  }
  e0^=1;
}
template<int N> __device__ __forceinline__ void gemm_item(int type,uint32_t pos,uint32_t sb,int tid,uint32_t ra,uint32_t& e0,uint32_t& eb,int& sq,uint32_t em){
  const int lane=tid&31, wg=tid>>7;
  const uint32_t E0=sb+W_BAR+96+wg*16;
  float acc[192];
  mainloop<N>(acc,type==T_M2?24:10,sb,lane,pos,em);
  uint32_t p[2][N/4];
  #pragma unroll
  for(int m=0;m<2;m++)
    #pragma unroll
    for(int i=0;i<N/4;i++) p[m][i]=pack_bf16(acc[96*m+2*i],acc[96*m+2*i+1]);
  const float c1=type==T_M1?-2.302208198144325f:-1.4426950408889634f, c3=type==T_M1?-0.10294323958f:0.f;
  const int wq=(tid>>5)&3;
  if(type!=T_KV){ mbar_wait(sb+W_BAR+224+wg*8,eb); eb^=1; }
  #pragma unroll
  for(int m=0;m<2;m++){
    mbar_wait(E0+m*8,e0);
    stage_pk<N/16>(p[m],ra+m*SLOT,lane);
    if(type!=T_KV) post_pass(sb+W_SLOT+m*SLOT+wq*2048,N/64,sb+W_BAR+256+wg*384,c1,c3);
    fence_async();
    bar_arrive(sq,160); sq^=1;
  }
  e0^=1;
}
__device__ __forceinline__ int n_it(int c,int r){ return c==T_OP?4*nsp(r):(c==T_QA?32:(c==T_M2?4:(r?0:(c==T_M1?128:(c==T_KV?(1024-KVUP)/2:0))))); }
__device__ __forceinline__ void flag_wait(int rbk,int a,int lane){
  const uint32_t need=4*rbk+4; const uint32_t* f=g_flag+a*96+(lane%3)*32; int gd=0;
  while(!__all_sync(~0u,lane>2||ld_acq(f)>=need)){ __nanosleep(FNS); if(++gd>WGUARD){ g_err=22; break; } }
}
__device__ __forceinline__ void cnt_wait(int c,uint32_t thr){
  int gd=0;
  while(ld_acq(g_cnt+c)<thr){ __nanosleep(40); if(++gd>WGUARD){ g_err=23; break; } }
}
__global__ void __launch_bounds__(384,1) k_work(const __grid_constant__ WParams P){
  extern __shared__ __align__(1024) uint8_t sm[];
  const uint32_t sb=(uint32_t)__cvta_generic_to_shared(sm);
  const int tid=threadIdx.x, warp=__shfl_sync(~0u,tid>>5,0), lane=tid&31;
  const uint32_t FULL=sb+W_BAR, EMPTY=sb+W_BAR+32, IFULL=sb+W_BAR+64, IEMPTY=sb+W_BAR+80, EF=sb+W_BAR+96, REQ=sb+W_BAR+128, TOK=sb+W_BAR+136;
  volatile int* idesc=(volatile int*)(sm+W_BAR+160);
  if(tid==352) ST(0);
  if(tid==0){
    for(int i=0;i<NST;i++){ mbar_init(FULL+i*8,1); mbar_init(EMPTY+i*8,8); mbar_init(EF+i*8,1); }
    for(int i=0;i<2;i++){ mbar_init(IFULL+i*8,1); mbar_init(IEMPTY+i*8,6); mbar_init(sb+W_BAR+224+i*8,1); }
    mbar_init(REQ,1); mbar_init(TOK,1); mbar_init(sb+W_BAR+144,1);
    { mbar_init(sb+W_BAR+240,1); mbar_init(sb+W_BAR+248,1); uint32_t sm_; asm volatile("mov.u32 %0, %%smid;":"=r"(sm_)); idesc[6]=sm_; }
    asm volatile("fence.mbarrier_init.release.cluster;":::"memory");
  }
  __syncthreads();
  #define S0(i)
  S0(0)
  if(P.pair) cluster_sync();
  S0(1)
  S0(2)
  if(warp>=8){
    asm volatile("setmaxnreg.dec.sync.aligned.u32 40;");
    if(warp==11){
      uint32_t it=0, pos=0;
      auto publish=[&](int type,int rbk,int a,int erl){
        if(lane==0){
          const uint32_t sl=it&1;
          int idx=0;
          if(type==T_KV){ rbk=2*(a>>7)+(a&1); a=(a>>1)&63; }
          if(type==T_M1){ rbk=a>>3; a&=7; }
          mbar_wait(IEMPTY+sl*8,((it>>1)&1)^1);
          idesc[sl*8]=type; idesc[sl*8+1]=rbk; idesc[sl*8+2]=a; idesc[sl*8+3]=pos; idesc[sl*8+4]=idx; idesc[sl*8+5]=erl;
          mbar_arrive(IFULL+sl*8);
          pos+=type==T_M2?24:(type==T_OP?pu_st(nsp(rbk)):10);
        }
        __syncwarp();
        it++;
      };
      bool fin=false, rq=false;
      if(P.pair){
        const uint32_t i0=blockIdx.x<128?KVR:0;
        int quota=0, tk;
        while(true){
          if(it) mbar_wait(REQ,(it&1)^1);
          if(it<i0) tk=it*128+((blockIdx.x+(it>=ROT0?(it-ROT0+1)*ROT:0))&127);
          else {
            const uint32_t mb=sb+W_BAR+240+(it&1)*8;
            tk=4096;
            if(blockIdx.x&1){
              int gd=0; while(!mbar_try_cl(mb,((it-i0)>>1)&1)){ if(++gd>WGUARD){ g_err=24; break; } }
              tk=idesc[(it&1)*8+7];
            } else {
              if(it==i0){
                asm volatile("griddepcontrol.wait;":::"memory");
                uint32_t o; asm volatile("ld.shared::cluster.u32 %0, [%1];":"=r"(o):"r"(mapa(sb+W_BAR+160+24,1)):"memory");
                const uint32_t m=idesc[6]; uint32_t q=KVQ+KVR-i0;
                #pragma unroll
                for(int i=0;i<3;i++){ const uint32_t v=ld_rlx(g_sml+lane+32*i); if(v==m||v==o) q=min(q,KVR-i0+(lane+32*i<3*KVJ?0:1)); }
                quota=__reduce_min_sync(~0u,q);
              }
              if(lane==0){
                if(quota--){ tk=(int)atomicAdd(g_cnt+C_NEXT+T_KV*32,1u); if(tk>=n_it(T_KV,0)) tk=CONT&&quota>512&&ld_rlx(g_flag)>1?4097:4096; }
                asm volatile("st.shared::cluster.u32 [%0], %1;\nmbarrier.arrive.release.cluster.shared::cluster.b64 _, [%2];"::"r"(mapa(sb+W_BAR+160+(it&1)*32+28,1)),"r"(tk),"r"(mapa(mb,1)):"memory");
              }
              tk=__shfl_sync(~0u,tk,0);
            }
            if(tk>=4096) break;
            tk=KVUP+2*tk+(blockIdx.x&1);
          }
          publish(T_KV,0,tk,2);
        }
        if(tk==4096){ publish(T_END,0,0,0); fin=true; }
      }
      int guard=0;
      const int cl=lane>>2, cj=lane&3;
      int sidx=-1, nit=0;
      if(lane==0) ST(1);
      while(true){
        int type=T_END, rbk=0, a=0, erl=0;
        if(!fin){
          if(rq) mbar_wait(REQ,(it&1)^1);
          rq=true;
          if(sidx>=0){ type=T_KV; a=sidx; sidx=-1; }
          else {
            while(true){
              const uint4 nx=ldg_rlx4(g_cnt+C_NEXT+cl*32+cj*4);
              int cand=(int)nx.x<n_it(cl,4*cj)?4*cj*4096+nx.x:((int)nx.y<n_it(cl,4*cj+1)?(4*cj+1)*4096+nx.y:((int)nx.z<n_it(cl,4*cj+2)?(4*cj+2)*4096+nx.z:((int)nx.w<n_it(cl,4*cj+3)?(4*cj+3)*4096+nx.w:65536)));
              cand=min(cand,__shfl_xor_sync(~0u,cand,1)); cand=min(cand,__shfl_xor_sync(~0u,cand,2));
              const int cr=cand>>12, ca=cand&4095, qr=__shfl_sync(~0u,cr,4*T_QA);
              const bool has=cr<NRB;
              if(lane==0&&nit==0) ST(5);
              const uint32_t* fp=nullptr; uint32_t thr=0, sl1=0; bool only1=false, no1=cl>=T_M2;
              if(has&&cl<=T_M2){
                if(cl==T_QA){ if(cj<3){ fp=g_flag+ca*96+cj*32; thr=4*cr+4; sl1=cr==NRB-1?E15:EARLY; } else { fp=g_cnt+C_KV+min(cr+1,NRB-1); thr=64; only1=true; } }
                else if(cj==0){ fp=g_cnt+(cl==T_OP?C_QA:C_M1)+cr; thr=cl==T_OP?32:8; sl1=thr; }
                else if(cj==1){ if(cl==T_OP){ fp=g_cnt+C_M2+cr; thr=4; } if(cr<OPE||qr<=cr) no1=true; }
              }
              __syncwarp();
              if(lane==0&&nit==0) ST(2);
              uint32_t v=0; if(fp) v=ld_acq(fp);
              __syncwarp();
              if(lane==0&&nit==0) ST(3+(v&0));
              nit++;
              uint32_t b2=__ballot_sync(~0u,has&&(v>=thr||only1)), b1=__ballot_sync(~0u,has&&!no1&&v+sl1>=thr);
              b2&=b2>>1; b2&=b2>>2; b1&=b1>>1; b1&=b1>>2;
              b2&=0x111111u; b1&=0x111u;
              if(!__ballot_sync(~0u,has)) break;
              if(b2|b1){
                const int rs=(int)__shfl_sync(~0u,v,4*T_QA);
                const uint32_t bu=__ballot_sync(~0u,cl<=T_QA||qr>=NRB||(cl==T_KV?2*((2*ca+KVUP)>>7)<=(rs>>2)+KLEAD:(cl==T_M1?ca>>3:cr)<=qr+MLEAD));
                int got=-1;
                while(got<0&&(b2|b1)){
                  uint32_t bb=(b2&bu)?(b2&bu):(b1?b1:b2);
                  if(Q15&&(((b1|b2)>>(4*T_QA))&1)&&qr>=NRB-Q15) bb=1u<<(4*T_QA);
                  #define RD(c) ((bb>>(4*(c)))&1)
                  const int w=RD(T_KV)?T_KV:(RD(T_M2)?T_M2:(RD(T_M1)?T_M1:(RD(T_OP)?T_OP:T_QA)));
                  if(lane==4*w){ const int tk=(int)atomicAdd(g_cnt+C_NEXT+cl*32+cr,1u); if(tk<n_it(cl,cr)) got=cr*4096+(cl==T_KV?KVUP+2*tk:tk)+(tk!=ca?65536:0); }
                  got=__shfl_sync(~0u,got,4*w);
                  if(got>=0){ type=w; rbk=(got>>12)&15; a=got&4095; if(w==T_KV) sidx=a+1; erl=!((b2>>(4*w))&1)||(w==T_QA&&got>=65536); }
                  b2&=~(1u<<(4*w)); b1&=~(1u<<(4*w));
                }
                if(got>=0) break;
              } else {
                __nanosleep(100);
                if(++guard>WGUARD){ g_err=21; break; }
              }
            }
          }
        }
        __syncwarp();
        publish(type,rbk,a,erl);
        if(type==T_END){ if(fin) break; fin=true; }
      }
    } else if(warp==8){
      if(lane==0){
        uint32_t st=0, ph=1;
        for(uint32_t it=0;;it++){
          const uint32_t sl=it&1;
          mbar_wait(IFULL+sl*8,(it>>1)&1);
          const int type=idesc[sl*8], rbk=idesc[sl*8+1], a=idesc[sl*8+2], erl=idesc[sl*8+5];
          mbar_arrive(IEMPTY+sl*8);
          if(type==T_END) break;
          if(type==T_OP){
            const int ns=nsp(rbk), nkb=pu_st(ns), bps=40/nkb, ub=40960/ns, seg=rbk*4+a/ns, trig=rbk>=LATE?nkb-1:max(nkb-TRIG,0);
            const uint8_t* pp=g_p+seg*81920; const CUtensorMap* um=&P.m[ns==1?M_U1:(ns==2?M_U2:(ns==5?M_U5:M_U10))]; const int c1=(a%ns)*(20/ns);
            if(erl) cnt_wait(C_QA+rbk,32);
            FAG();
            for(int kb=0;kb<nkb;kb++){
              mbar_wait(EMPTY+st*8,ph);
              const uint32_t d=sb+st*STG, fb=FULL+st*8;
              mbar_expect(fb,bps*(ub+2048));
              asm volatile("cp.async.bulk.tensor.3d.shared::cluster.global.mbarrier::complete_tx::bytes.L2::cache_hint [%0], [%1, {0, %3, %4}], [%2], %5;"::"r"(d),"l"(um),"r"(fb),"r"(c1),"r"(seg*40+kb*bps),"l"(PL_EF):"memory");
              bulk_g2s(d+bps*ub,pp,bps*2048,fb); pp+=bps*2048;
              if(kb==trig) mbar_arrive(REQ);
              if(++st==NST){ st=0; ph^=1; }
            }
            continue;
          }
          int ma=M_XN,mb,cg=a*3,nkb=10,nbox=3; const int row0=rbk*128;
          if(type==T_KV){ mb=a<32?M_WK:M_WV; cg=(a&31)*3; }
          else if(type==T_M1){ ma=M_Y; mb=M_W1; }
          else if(type==T_QA){ mb=M_WQ; }
          else {
            const int nt=a&3; cg=nt<2?nt*3:2+nt*2; nbox=nt<2?3:2;
            ma=M_H2; mb=nt<2?M_W2:M_W2B; nkb=24;
          }
          if(erl!=2) FAG();
          const CUtensorMap* A=&P.m[ma]; const CUtensorMap* B=&P.m[mb];
          const int trig=(type<=T_QA&&rbk>=LATE)?nkb-1:max(nkb-TRIG,0), r=rbk&1, f0=(erl==2&&it==0)?NST:0;
          for(int kb=0;kb<nkb;kb++){
            mbar_wait(EMPTY+st*8,ph);
            const uint32_t d=sb+st*STG, fb=FULL+st*8;
            mbar_expect(fb,16384+nbox*8192);
            if(kb>=f0) tma2d(d,A,kb*64,row0,fb);
            if(erl==2) tma4dm(d+16384+r*12288,B,cg,2*kb+r,fb);
            else { tma4d(d+16384,B,cg,2*kb,fb); if(type==T_KV) tma4d(d+28672,B,cg,2*kb+1,fb); }
            if(kb==trig) mbar_arrive(REQ);
            if(kb==f0-1){
              asm volatile("griddepcontrol.wait;":::"memory"); asm volatile("griddepcontrol.launch_dependents;");
              for(int i=0;i<NST;i++) tma2d(sb+i*STG,A,i*64,row0,FULL+i*8);
            }
            if(++st==NST){ st=0; ph^=1; }
          }
        }
      }
      __syncwarp();
    } else if(warp<11){
      const int wg=warp-9;
      const uint32_t S0=sb+W_SLOT, E0=EF+wg*16; int sq=4+2*wg;
      for(uint32_t it=wg;;it+=2){
        mbar_wait(IFULL+wg*8,(it>>1)&1);
        const int type=idesc[wg*8], rbk=idesc[wg*8+1], a=idesc[wg*8+2], erl=idesc[wg*8+5];
        __syncwarp();
        if(lane==0) mbar_arrive(IEMPTY+wg*8);
        if(type==T_END) break;
        const int row0=rbk*128;
        int map=-1,col0=a*192,nbox=3,cnt=-1;
        if(type==T_KV){ map=a<32?M_K:M_V; col0=(a&31)*192; cnt=C_KV+rbk; }
        else if(type==T_M1){ map=M_H; cnt=C_M1+rbk; }
        else if(type==T_M2){ const int nt=a&3; col0=nt<2?nt*192:128+nt*128; nbox=nt<2?3:2; map=M_GATE; cnt=C_M2+rbk; }
        else if(type==T_OP) map=M_OUT;
        if((type==T_M1||type==T_M2)&&lane==0){ const uint32_t bb=sb+W_BAR+224+wg*8; mbar_expect(bb,nbox*128); bulk_g2s(sb+W_BAR+256+wg*384,(type==T_M1?P.b1:P.b2)+col0,nbox*128,bb); }
        const char* kp=(const char*)g_km+(uint32_t)(rbk*393216+a*3072);
        if(it&&lane==0) mbar_wait(TOK,(it&1)^1);
        if(map<0){
          if(lane==0){
            FAG();
            for(int m=0;m<2;m++){
              mbar_expect(E0+m*8,SLOT);
              for(int j=0;j<3;j++) tma2dh(S0+m*SLOT+j*BOXS,&P.m[M_K],col0+j*64,row0+m*64,E0+m*8,PL_EF);
            }
            mbar_expect(sb+W_BAR+224+wg*8,12288);
          }
          if(erl){ __syncwarp(); flag_wait(rbk,a,lane); FAG(); }
          { __syncwarp(); bar_sync(sq,160); sq^=1; }
          if(lane==0){ for(int j=0;j<4;j++) bulk_g2s(S0+j*3072,kp+j*98304,3072,sb+W_BAR+224+wg*8); }
          { __syncwarp(); bar_sync(sq,160); sq^=1; }
          if(lane==0) mbar_arrive(TOK);
          { __syncwarp(); bar_sync(sq,160); sq^=1; } if(lane==0) red_rel(g_cnt+C_QA+rbk);
        } else if(map==M_OUT){
          if(lane==0){ mbar_arrive(E0); mbar_arrive(E0+8); }
          { __syncwarp(); bar_sync(sq,160); sq^=1; }
          { __syncwarp(); bar_sync(sq,160); sq^=1; }
          if(lane==0) mbar_arrive(TOK);
        } else {
          if(lane==0){ mbar_arrive(E0); mbar_arrive(E0+8); }
          for(int m=0;m<2;m++){
            { __syncwarp(); bar_sync(sq,160); sq^=1; }
            if(lane==0){
              if(type==T_KV&&rbk>=KEF){ for(int j=0;j<nbox;j++) tma_st_ef(&P.m[map],S0+m*SLOT+j*BOXS,col0+j*64,row0+m*64); }
              else for(int j=0;j<nbox;j++) tma_st(&P.m[map],S0+m*SLOT+j*BOXS,col0+j*64,row0+m*64);
              bulk_commit();
            }
          }
          if(lane==0){
            bulk_wait_rd(); mbar_arrive(TOK);
            bulk_wait(); FAG(); red_rel(g_cnt+cnt);
          }
        }
        __syncwarp();
      }
      if(lane==0) bulk_wait();
    }
  } else {
    asm volatile("setmaxnreg.inc.sync.aligned.u32 232;");
    const int wg=warp>>2, wq=warp&3, g=lane>>2, t=lane&3;
    const uint32_t E0=EF+wg*16;
    const uint32_t ra=sb+W_SLOT+(16*wq+(lane&7)+((lane>>3)&1)*8)*128;
    uint32_t e0=0, eb=0; int sq=4+2*wg;
    const uint32_t rank=blockIdx.x&P.pair;
    #pragma unroll 1
    for(uint32_t it=0;;it++){
      mbar_wait(IFULL+wg*8,it&1);
      const int type=idesc[wg*8], rbk=idesc[wg*8+1], a=idesc[wg*8+2]; const uint32_t pos=idesc[wg*8+3], em=mapa(EMPTY,idesc[wg*8+5]==2?lane&1:rank);
      __syncwarp();
      if(lane==0) mbar_arrive(IEMPTY+wg*8);
      if(type==T_END) break;
      mbar_wait(sb+W_BAR+144,wg^1);
      if(type==T_OP){
        const int ns=nsp(rbk);
        if(ns_used(1)&&ns==1) pu_item<1>(P,rbk,a,pos,sb,tid,e0,sq);
        if(ns_used(2)&&ns==2) pu_item<2>(P,rbk,a,pos,sb,tid,e0,sq);
        if(ns_used(5)&&ns==5) pu_item<5>(P,rbk,a,pos,sb,tid,e0,sq);
        if(ns_used(10)&&ns==10) pu_item<10>(P,rbk,a,pos,sb,tid,e0,sq);
      } else {
        if(type!=T_QA){
          if(type>=T_M1||(a&3)<2) gemm_item<192>(type,pos,sb,tid,ra,e0,eb,sq,em); else gemm_item<128>(type,pos,sb,tid,ra,e0,eb,sq,em);
        } else {
          float acc[192];
          QT(0);
          mainloop<192>(acc,10,sb,lane,pos,em);
          QT(1);
          const int sgl=wq>>1, rh=wq&1;
          {
            uint32_t q[96];
            float s[2][16], sm[2][8];
            #pragma unroll
            for(int i=95;i>=0;i--) q[i]=pack_bf16(acc[2*i],acc[2*i+1]);
            QT(2);
            #pragma unroll
            for(int m=0;m<2;m++){
              const uint32_t dk=(((sb+W_SLOT+m*SLOT)>>4)&0x3fff)|(1u<<16);
              float u[32];
              mbar_wait(E0+m*8,e0);
              #pragma unroll
              for(int i=0;i<32;i++) u[i]=0.f;
              wg_arrive();
              #pragma unroll
              for(int T=0;T<12;T++) wgmma_rs<64>(u,q+48*m+4*T,dk+(T>>2)*(BOXS/16)+(T&3)*2,T);
              wg_commit();
              wg_wait<0>();
              if(m==0){ bar_arrive(sq,160); sq^=1; }
              #pragma unroll
              for(int i=0;i<16;i++) s[m][i]=sgl?u[16+i]:u[i];
            }
            QT(3);
            mbar_wait(sb+W_BAR+224+wg*8,eb); eb^=1;
            #pragma unroll
            for(int i=0;i<16;i++) sm[i>>3][i&7]=0.f;
            wg_arrive();
            #pragma unroll
            for(int T=0;T<12;T++)
              #pragma unroll
              for(int m=0;m<2;m++) wg16_rs(sm[m],q+48*m+4*T,((((sb+W_SLOT)>>4)&0x3fff)|(8u<<16))+m*384+T*16,T);
            wg_commit();
            wg_wait<0>();
            bar_arrive(sq,160); sq^=1;
            QT(4);
            const float NEG=rb(-1e9f);
            #pragma unroll
            for(int m=0;m<2;m++){
              float sc[5][4];
              float mx[2]={-3.4e38f,-3.4e38f};
              #pragma unroll
              for(int n=0;n<5;n++)
                #pragma unroll
                for(int i=0;i<4;i+=2){
                  const float u0=n?s[m][n?4*n-4+i:0]:(sgl?sm[m][4+i]:sm[m][i]);
                  const float u1=n?s[m][n?4*n-3+i:0]:(sgl?sm[m][5+i]:sm[m][i+1]);
                  const uint32_t r=pack_bf16(u0,u1);
                  const uint32_t w=pack_bf16(__uint_as_float(r<<16)*0.07216878364870322f,__uint_as_float(r&0xffff0000u)*0.07216878364870322f);
                  float v0=__uint_as_float(w<<16), v1=__uint_as_float(w&0xffff0000u);
                  if(n>0){ const int key=8*(n-1)+2*t, row=16*rh+g+4*i; if(key>row) v0=NEG; if(key+1>row) v1=NEG; }
                  sc[n][i]=v0; sc[n][i+1]=v1; mx[i>>1]=fmaxf(mx[i>>1],fmaxf(v0,v1));
                }
              float sum[2]={0.f,0.f};
              #pragma unroll
              for(int r=0;r<2;r++){ mx[r]=fmaxf(mx[r],__shfl_xor_sync(~0u,mx[r],1)); mx[r]=fmaxf(mx[r],__shfl_xor_sync(~0u,mx[r],2)); }
              #pragma unroll
              for(int n=0;n<5;n++)
                #pragma unroll
                for(int i=0;i<4;i++){ const float e=ex2((sc[n][i]-mx[i>>1])*1.4426950408889634f); sc[n][i]=e; sum[i>>1]+=e; }
              #pragma unroll
              for(int r=0;r<2;r++){ sum[r]+=__shfl_xor_sync(~0u,sum[r],1); sum[r]+=__shfl_xor_sync(~0u,sum[r],2); sum[r]=rcp(sum[r]); }
              uint8_t* pd=g_p+(uint32_t)((rbk*4+m*2+sgl)*81920+rh*256+lane*4);
              #pragma unroll
              for(int n=0;n<5;n++){
                uint8_t* q=pd+(n?a*2048+(n-1)*512:(32+(a>>2))*2048+(a&3)*512);
                stg1(q,pack_bf16(sc[n][0]*sum[0],sc[n][1]*sum[0])); stg1(q+128,pack_bf16(sc[n][2]*sum[1],sc[n][3]*sum[1]));
              }
            }
          }
          QT(5);
          bar_arrive(sq,160); sq^=1;
          e0^=1;
        }
      }
    }
  }
  if(P.pair) cluster_sync();
}
typedef CUresult (*EncFn)(CUtensorMap*,CUtensorMapDataType,cuuint32_t,void*,const cuuint64_t*,const cuuint64_t*,const cuuint32_t*,const cuuint32_t*,CUtensorMapInterleave,CUtensorMapSwizzle,CUtensorMapL2promotion,CUtensorMapFloatOOBfill);
static EncFn enc(){
  static EncFn fn=nullptr;
  if(!fn){ void* p=nullptr; cudaDriverEntryPointQueryResult qr; cudaGetDriverEntryPoint("cuTensorMapEncodeTiled",&p,cudaEnableDefault,&qr); fn=(EncFn)p; }
  return fn;
}
static CUtensorMap mku(const void* base,uint32_t b1,uint32_t b2){
  CUtensorMap m; cuuint64_t gd[3]={256,20,NSEG*40}; cuuint64_t gs[2]={2048,40960}; cuuint32_t bd[3]={256,b1,b2}; cuuint32_t es[3]={1,1,1};
  enc()(&m,CU_TENSOR_MAP_DATA_TYPE_FLOAT64,3,(void*)base,gd,gs,bd,es,CU_TENSOR_MAP_INTERLEAVE_NONE,CU_TENSOR_MAP_SWIZZLE_NONE,CU_TENSOR_MAP_L2_PROMOTION_L2_128B,CU_TENSOR_MAP_FLOAT_OOB_FILL_NONE);
  return m;
}
static CUtensorMap mk2d(const void* base,uint64_t cols,uint64_t rows,uint32_t bc,uint32_t br){
  EncFn fn=enc();
  CUtensorMap m; cuuint64_t gd[2]={cols,rows}; cuuint64_t gs[1]={cols*2}; cuuint32_t bd[2]={bc,br}; cuuint32_t es[2]={1,1};
  fn(&m,CU_TENSOR_MAP_DATA_TYPE_BFLOAT16,2,(void*)base,gd,gs,bd,es,CU_TENSOR_MAP_INTERLEAVE_NONE,bc==32?CU_TENSOR_MAP_SWIZZLE_64B:CU_TENSOR_MAP_SWIZZLE_128B,CU_TENSOR_MAP_L2_PROMOTION_L2_128B,CU_TENSOR_MAP_FLOAT_OOB_FILL_NONE);
  return m;
}
static CUtensorMap mkw(const void* base){
  CUtensorMap m; cuuint64_t gd[3]={HD,D/2,2}; cuuint64_t gs[2]={HD*4,HD*2}; cuuint32_t bd[3]={64,8,2}; cuuint32_t es[3]={1,1,1};
  enc()(&m,CU_TENSOR_MAP_DATA_TYPE_BFLOAT16,3,(void*)base,gd,gs,bd,es,CU_TENSOR_MAP_INTERLEAVE_NONE,CU_TENSOR_MAP_SWIZZLE_128B,CU_TENSOR_MAP_L2_PROMOTION_L2_128B,CU_TENSOR_MAP_FLOAT_OOB_FILL_NONE);
  return m;
}
static CUtensorMap mk4(const void* base,uint64_t cols,uint64_t rows,uint32_t ng,uint32_t nh){
  CUtensorMap m; cuuint64_t gd[4]={64,32,cols/64,rows/32}; cuuint64_t gs[3]={cols*2,128,cols*64}; cuuint32_t bd[4]={64,32,ng,nh}; cuuint32_t es[4]={1,1,1,1};
  enc()(&m,CU_TENSOR_MAP_DATA_TYPE_BFLOAT16,4,(void*)base,gd,gs,bd,es,CU_TENSOR_MAP_INTERLEAVE_NONE,CU_TENSOR_MAP_SWIZZLE_128B,CU_TENSOR_MAP_L2_PROMOTION_L2_128B,CU_TENSOR_MAP_FLOAT_OOB_FILL_NONE);
  return m;
}
template<class T> static T* sym(T& s){ void* p; cudaGetSymbolAddress(&p,s); return (T*)p; }
}

#define G2 96
#define XPQ Wq
#define XPO Wo
int g_reconly=0; int g_kvgrid=132;
extern "C" void kernel_launch(void* const* d_in, const int* in_sizes, int n_in, void* d_out, int out_size) {
  using namespace rk;
  const bf16* x=(const bf16*)d_in[0]; const bf16* mem0=(const bf16*)d_in[1];
  const bf16* Wq=(const bf16*)d_in[2]; const bf16* Wk=(const bf16*)d_in[3]; const bf16* Wv=(const bf16*)d_in[4]; const bf16* Wo=(const bf16*)d_in[5];
  const bf16* w1=(const bf16*)d_in[8]; const bf16* b1=(const bf16*)d_in[9]; const bf16* w2=(const bf16*)d_in[10]; const bf16* b2=(const bf16*)d_in[11];
  cudaStream_t st=cudaStreamPerThread;
  cudaFuncSetAttribute(k_rec,cudaFuncAttributeMaxDynamicSharedMemorySize,SM_TOTAL);
  cudaFuncSetAttribute(k_work,cudaFuncAttributeMaxDynamicSharedMemorySize,W_TOTAL);
  bf16* k=(bf16*)sym(g_k); bf16* v=(bf16*)sym(g_v);
  WParams P;
  P.m[M_XN]=mk2d(sym(g_xn),D,S,64,128); P.m[M_Y]=mk2d(sym(g_y),D,S,64,128); P.m[M_H]=mk2d(sym(g_h),F,S,64,64); P.m[M_H2]=mk2d(sym(g_h),F,S,64,128);
  P.m[M_K]=mk2d(k,HD,S,64,64); P.m[M_V]=mk2d(v,HD,S,64,64); P.m[M_GATE]=mk2d(sym(g_gate),D,S,64,64);
  P.m[M_WQ]=mk4(Wq,HD,D,3,2); P.m[M_WK]=mk4(Wk,HD,D,3,1); P.m[M_WV]=mk4(Wv,HD,D,3,1);
  P.m[M_W1]=mk4(w1,F,D,3,2); P.m[M_W2]=mk4(w2,D,F,3,2); P.m[M_W2B]=mk4(w2,D,F,2,2);
  P.m[M_U1]=mku(sym(g_u),20,1); P.m[M_U2]=mku(sym(g_u),10,2); P.m[M_U5]=mku(sym(g_u),4,4); P.m[M_U10]=mku(sym(g_u),2,5);
  P.x=x; P.b1=b1; P.b2=b2; P.out=(bf16*)d_out; P.pair=1;
  cudaFuncSetAttribute(k_pre,cudaFuncAttributeMaxDynamicSharedMemorySize,SM_TOTAL);
  {
    cudaLaunchConfig_t cfg={}; cfg.gridDim=dim3(NCTA); cfg.blockDim=dim3(PRE_T); cfg.dynamicSmemBytes=SM_TOTAL; cfg.stream=st;
    cudaLaunchAttribute at[1]; at[0].id=cudaLaunchAttributeClusterDimension; at[0].val.clusterDim.x=3; at[0].val.clusterDim.y=1; at[0].val.clusterDim.z=1; cfg.attrs=at; cfg.numAttrs=1;
    cudaLaunchKernelEx(&cfg,k_pre,x,mem0,(const char*)Wk,(const char*)Wv);
  }
  if(!(g_reconly&1)){
    cudaLaunchConfig_t cfg={}; cfg.gridDim=dim3(g_kvgrid); cfg.blockDim=dim3(384); cfg.dynamicSmemBytes=W_TOTAL; cfg.stream=st;
    cudaLaunchAttribute at[2]; at[0].id=cudaLaunchAttributeClusterDimension; at[0].val.clusterDim.x=2; at[0].val.clusterDim.y=1; at[0].val.clusterDim.z=1;
    at[1].id=cudaLaunchAttributeProgrammaticStreamSerialization; at[1].val.programmaticStreamSerializationAllowed=1; cfg.attrs=at; cfg.numAttrs=2;
    cudaLaunchKernelEx(&cfg,k_work,P);
  }
  if(!(g_reconly&4)){
    cudaLaunchConfig_t cfg={}; cfg.gridDim=dim3(NCTA); cfg.blockDim=dim3(256); cfg.dynamicSmemBytes=SM_TOTAL; cfg.stream=st;
    cudaLaunchAttribute at[2]; at[0].id=cudaLaunchAttributeClusterDimension; at[0].val.clusterDim.x=3; at[0].val.clusterDim.y=1; at[0].val.clusterDim.z=1;
    at[1].id=cudaLaunchAttributeProgrammaticStreamSerialization; at[1].val.programmaticStreamSerializationAllowed=1; cfg.attrs=at; cfg.numAttrs=2;
    RParams R; R.k=mk2d(k,HD,S,64,32); R.v=mk2d(v,HD,S,64,32); R.w[0]=mkw(XPQ); R.w[1]=mkw(Wk); R.w[2]=mkw(Wv); R.w[3]=mk2d(XPO,D,HD,32,32); R.wq=(const char*)XPQ; R.wo=(const char*)XPO;
    cudaLaunchKernelEx(&cfg,k_rec,R,0u);
  }
  if(!(g_reconly&2)){
    cudaLaunchConfig_t cfg={}; cfg.gridDim=dim3(G2); cfg.blockDim=dim3(384); cfg.dynamicSmemBytes=W_TOTAL; cfg.stream=st; P.pair=0;
    cudaLaunchAttribute at[1]; at[0].id=cudaLaunchAttributeProgrammaticStreamSerialization; at[0].val.programmaticStreamSerializationAllowed=1; cfg.attrs=at; cfg.numAttrs=PDL;
    cudaLaunchKernelEx(&cfg,k_work,P);
  }
}
```

```cpp
#include <cuda_runtime.h>
#include <cuda_bf16.h>
#include <stdint.h>
#include <cuda.h>

namespace rk {
typedef __nv_bfloat16 bf16;
constexpr int S=2048, D=640, H=32, DH=192, HD=6144, NSEG=64, F=1536;
constexpr uint32_t SENT=0xFFFFFFFFu;
#define GUARDN 400000
constexpr int GUARD=GUARDN;
constexpr int NCTA=96;

__device__ __align__(128) bf16 g_xn[S*D];
__device__ __align__(128) bf16 g_y[S*D];
__device__ __align__(128) bf16 g_h[S*F];
__device__ __align__(128) bf16 g_gate[S*D];
__device__ __align__(128) bf16 g_k[(size_t)S*HD];
__device__ __align__(128) bf16 g_v[(size_t)S*HD];
__device__ __align__(128) bf16 g_km[NSEG*8*HD];
__device__ __align__(128) uint32_t g_flag[NCTA*32];
__device__ __align__(1024) uint8_t g_u[(size_t)NSEG*40*40960];
__device__ __align__(1024) uint8_t g_p[(size_t)NSEG*40*2048];
#define NSTAB 0xAA55522222222222ull
#define EKM 0
#define RTB 14
__host__ __device__ constexpr int nsp(int rb){ return rb>=RTB?0:(int)((NSTAB>>(4*rb))&15); }
__host__ __device__ constexpr bool ns_used(int n){ for(int r=0;r<16;r++) if(nsp(r)==n) return true; return false; }
constexpr int C_NEXT=0, C_KV=256, C_M1=272, C_M2=288, C_RD=304, C_QA=320, C_NUM=384;
__device__ __align__(128) uint32_t g_cnt[C_NUM];
#define PDL 1
__device__ __align__(1024) unsigned long long g_acc[NSEG*2560];
constexpr unsigned long long ACC_INIT=0ull-32ull*((0x5A000000ull<<32)+0xD0000000ull+1ull);
__device__ __align__(128) uint32_t g_nrm[NCTA*2+32];
__device__ int g_err;
__device__ unsigned long long g_gt[128*4];
#define GT(i) do{ if(threadIdx.x==0){ unsigned long long g0; asm volatile("mov.u64 %0, %%globaltimer;":"=l"(g0)); g_gt[blockIdx.x*4+(i)]=g0; } }while(0)

__device__ __forceinline__ float rb(float x){ return __bfloat162float(__float2bfloat16(x)); }
__device__ __forceinline__ uint32_t pack_bf16(float lo,float hi){ uint32_t r; asm("cvt.rn.bf16x2.f32 %0, %1, %2;":"=r"(r):"f"(hi),"f"(lo)); return r; }
__device__ __forceinline__ uint32_t movm(uint32_t a){ uint32_t d; asm volatile("movmatrix.sync.aligned.m8n8.trans.b16 %0, %1;":"=r"(d):"r"(a)); return d; }
__device__ __forceinline__ uint4 ldg_rlx4(const uint32_t* p){ uint4 v; asm volatile("ld.relaxed.gpu.global.v4.u32 {%0,%1,%2,%3}, [%4];":"=r"(v.x),"=r"(v.y),"=r"(v.z),"=r"(v.w):"l"(p):"memory"); return v; }
__device__ __forceinline__ void stg_rlx1(uint32_t* p,uint32_t a){ asm volatile("st.relaxed.gpu.global.u32 [%0], %1;"::"l"(p),"r"(a):"memory"); }
__device__ __forceinline__ void stg_rlx2(uint32_t* p,uint32_t a,uint32_t b){ asm volatile("st.relaxed.gpu.global.v2.u32 [%0], {%1,%2};"::"l"(p),"r"(a),"r"(b):"memory"); }
__device__ __forceinline__ void stg1(void* p,uint32_t a){ asm volatile("st.global.u32 [%0], %1;"::"l"(p),"r"(a):"memory"); }
__device__ __forceinline__ void stg4(void* p,uint32_t a,uint32_t b,uint32_t c,uint32_t d){ asm volatile("st.global.v4.u32 [%0], {%1,%2,%3,%4};"::"l"(p),"r"(a),"r"(b),"r"(c),"r"(d):"memory"); }
__device__ __forceinline__ void bar_sync(int id,int n){ asm volatile("bar.sync %0, %1;"::"r"(id),"r"(n):"memory"); }
__device__ __forceinline__ void bar_arrive(int id,int n){ asm volatile("bar.arrive %0, %1;"::"r"(id),"r"(n):"memory"); }
__device__ __forceinline__ void mma16816(float* d,const uint32_t* a,uint32_t b0,uint32_t b1){
  asm volatile("mma.sync.aligned.m16n8k16.row.col.f32.bf16.bf16.f32 {%0,%1,%2,%3},{%4,%5,%6,%7},{%8,%9},{%0,%1,%2,%3};"
   :"+f"(d[0]),"+f"(d[1]),"+f"(d[2]),"+f"(d[3]):"r"(a[0]),"r"(a[1]),"r"(a[2]),"r"(a[3]),"r"(b0),"r"(b1));
}
__device__ __forceinline__ void mma1688(float* d,uint32_t a0,uint32_t a1,uint32_t b0){
  asm volatile("mma.sync.aligned.m16n8k8.row.col.f32.bf16.bf16.f32 {%0,%1,%2,%3},{%4,%5},{%6},{%0,%1,%2,%3};"
   :"+f"(d[0]),"+f"(d[1]),"+f"(d[2]),"+f"(d[3]):"r"(a0),"r"(a1),"r"(b0));
}
__device__ __forceinline__ void ldsm4t(uint32_t* r,uint32_t addr){ asm volatile("ldmatrix.sync.aligned.m8n8.x4.trans.shared.b16 {%0,%1,%2,%3}, [%4];":"=r"(r[0]),"=r"(r[1]),"=r"(r[2]),"=r"(r[3]):"r"(addr):"memory"); }
__device__ __forceinline__ void ldsm4(uint32_t* r,uint32_t addr){ asm volatile("ldmatrix.sync.aligned.m8n8.x4.shared.b16 {%0,%1,%2,%3}, [%4];":"=r"(r[0]),"=r"(r[1]),"=r"(r[2]),"=r"(r[3]):"r"(addr):"memory"); }
__device__ __forceinline__ void stsm4(uint32_t a,uint32_t r0,uint32_t r1,uint32_t r2,uint32_t r3){ asm volatile("stmatrix.sync.aligned.m8n8.x4.shared.b16 [%0], {%1,%2,%3,%4};"::"r"(a),"r"(r0),"r"(r1),"r"(r2),"r"(r3):"memory"); }
__device__ __forceinline__ void stsm2(uint32_t a,uint32_t r0,uint32_t r1){ asm volatile("stmatrix.sync.aligned.m8n8.x2.shared.b16 [%0], {%1,%2};"::"r"(a),"r"(r0),"r"(r1):"memory"); }
__device__ __forceinline__ void cp16(uint32_t dst,const void* src){ asm volatile("cp.async.cg.shared.global [%0], [%1], 16;"::"r"(dst),"l"(src):"memory"); }
__device__ __forceinline__ void cp_wait_all(){ asm volatile("cp.async.wait_all;":::"memory"); }
__device__ __forceinline__ void fence_async(){ asm volatile("fence.proxy.async.shared::cta;":::"memory"); }
__device__ __forceinline__ void sts4f(uint32_t a,const float* v){ asm volatile("st.shared.v4.f32 [%0], {%1,%2,%3,%4};"::"r"(a),"f"(v[0]),"f"(v[1]),"f"(v[2]),"f"(v[3]):"memory"); }
__device__ __forceinline__ void sts4(uint32_t a,uint4 v){ asm volatile("st.shared.v4.u32 [%0], {%1,%2,%3,%4};"::"r"(a),"r"(v.x),"r"(v.y),"r"(v.z),"r"(v.w):"memory"); }
__device__ __forceinline__ void sts4r(uint32_t a,const uint32_t* v){ asm volatile("st.shared.v4.u32 [%0], {%1,%2,%3,%4};"::"r"(a),"r"(v[0]),"r"(v[1]),"r"(v[2]),"r"(v[3]):"memory"); }
__device__ __forceinline__ void sts2(uint32_t a,uint32_t x,uint32_t y){ asm volatile("st.shared.v2.u32 [%0], {%1,%2};"::"r"(a),"r"(x),"r"(y):"memory"); }
__device__ __forceinline__ float4 lds4f(uint32_t a){ float4 v; asm volatile("ld.shared.v4.f32 {%0,%1,%2,%3}, [%4];":"=f"(v.x),"=f"(v.y),"=f"(v.z),"=f"(v.w):"r"(a):"memory"); return v; }
__device__ __forceinline__ float2 lds2f(uint32_t a){ float2 v; asm volatile("ld.shared.v2.f32 {%0,%1}, [%2];":"=f"(v.x),"=f"(v.y):"r"(a):"memory"); return v; }
__device__ __forceinline__ uint4 lds4(uint32_t a){ uint4 v; asm volatile("ld.shared.v4.u32 {%0,%1,%2,%3}, [%4];":"=r"(v.x),"=r"(v.y),"=r"(v.z),"=r"(v.w):"r"(a):"memory"); return v; }
__device__ __forceinline__ void lds4r(uint32_t* r,uint32_t a){ asm volatile("ld.shared.v4.u32 {%0,%1,%2,%3}, [%4];":"=r"(r[0]),"=r"(r[1]),"=r"(r[2]),"=r"(r[3]):"r"(a):"memory"); }
__device__ __forceinline__ uint2 lds2(uint32_t a){ uint2 v; asm volatile("ld.shared.v2.u32 {%0,%1}, [%2];":"=r"(v.x),"=r"(v.y):"r"(a):"memory"); return v; }
__device__ __forceinline__ float ex2(float x){ float r; asm("ex2.approx.ftz.f32 %0, %1;":"=f"(r):"f"(x)); return r; }
__device__ __forceinline__ float rcp(float x){ float r; asm("rcp.approx.ftz.f32 %0, %1;":"=f"(r):"f"(x)); return r; }
__device__ __forceinline__ void mbar_init(uint32_t a,int n){ asm volatile("mbarrier.init.shared.b64 [%0], %1;"::"r"(a),"r"(n):"memory"); }
__device__ __forceinline__ void mbar_expect(uint32_t a,int bytes){ asm volatile("mbarrier.arrive.expect_tx.shared.b64 _, [%0], %1;"::"r"(a),"r"(bytes):"memory"); }
__device__ __forceinline__ void mbar_arrive(uint32_t a){ asm volatile("mbarrier.arrive.shared.b64 _, [%0];"::"r"(a):"memory"); }
__device__ __forceinline__ bool mbar_try(uint32_t a,uint32_t par){ uint32_t ok; asm volatile("{\n.reg .pred p;\nmbarrier.try_wait.parity.shared.b64 p, [%1], %2;\nselp.u32 %0,1,0,p;\n}":"=r"(ok):"r"(a),"r"(par):"memory"); return ok; }
__device__ __forceinline__ bool mbar_test(uint32_t a,uint32_t par){ uint32_t ok; asm volatile("{\n.reg .pred p;\nmbarrier.test_wait.parity.shared.b64 p, [%1], %2;\nselp.u32 %0,1,0,p;\n}":"=r"(ok):"r"(a),"r"(par):"memory"); return ok; }
__device__ __forceinline__ bool mbar_try_cl(uint32_t a,uint32_t par){ uint32_t ok; asm volatile("{\n.reg .pred p;\nmbarrier.try_wait.parity.acquire.cluster.shared::cta.b64 p, [%1], %2;\nselp.u32 %0,1,0,p;\n}":"=r"(ok):"r"(a),"r"(par):"memory"); return ok; }
__device__ __forceinline__ void bulk_g2s(uint32_t dst,const void* src,int bytes,uint32_t mb){ asm volatile("cp.async.bulk.shared::cluster.global.mbarrier::complete_tx::bytes [%0], [%1], %2, [%3];"::"r"(dst),"l"(src),"r"(bytes),"r"(mb):"memory"); }
__device__ __forceinline__ uint32_t mapa(uint32_t a,uint32_t r){ uint32_t d; asm("mapa.shared::cluster.u32 %0, %1, %2;":"=r"(d):"r"(a),"r"(r)); return d; }
__device__ __forceinline__ void st_async2(uint32_t ra,uint32_t x,uint32_t y,uint32_t rmb){ asm volatile("st.async.weak.shared::cluster.mbarrier::complete_tx::bytes.v2.b32 [%0], {%1,%2}, [%3];"::"r"(ra),"r"(x),"r"(y),"r"(rmb):"memory"); }
__device__ __forceinline__ void st_async4(uint32_t ra,uint32_t x,uint32_t y,uint32_t z,uint32_t w,uint32_t rmb){ asm volatile("st.async.weak.shared::cluster.mbarrier::complete_tx::bytes.v4.b32 [%0], {%1,%2,%3,%4}, [%5];"::"r"(ra),"r"(x),"r"(y),"r"(z),"r"(w),"r"(rmb):"memory"); }
__device__ __forceinline__ void stg_rlx4(uint32_t* p,uint32_t a,uint32_t b,uint32_t c,uint32_t d){ asm volatile("st.relaxed.gpu.global.v4.u32 [%0], {%1,%2,%3,%4};"::"l"(p),"r"(a),"r"(b),"r"(c),"r"(d):"memory"); }
__device__ __forceinline__ void red64(void* p,uint32_t lo,uint32_t hi){ asm volatile("{\n.reg .b64 v;\nmov.b64 v, {%1,%2};\nred.relaxed.gpu.global.add.u64 [%0], v;\n}"::"l"(p),"r"(lo),"r"(hi):"memory"); }
__device__ __forceinline__ uint32_t amax2(uint32_t a,uint32_t b){ uint32_t r; asm("max.xorsign.abs.bf16x2 %0, %1, %2;":"=r"(r):"r"(a),"r"(b)); return r; }
__device__ __forceinline__ void cluster_sync(){ asm volatile("barrier.cluster.arrive.release.aligned;\nbarrier.cluster.wait.acquire.aligned;":::"memory"); }
__device__ __forceinline__ uint32_t ld_acq(const uint32_t* p){ uint32_t v; asm volatile("ld.acquire.gpu.global.u32 %0, [%1];":"=r"(v):"l"(p):"memory"); return v; }
__device__ __forceinline__ void fence_async_all(){ asm volatile("fence.proxy.async;":::"memory"); }
__device__ __forceinline__ void fence_async_g(){ asm volatile("fence.proxy.async.global;":::"memory"); }
__device__ __forceinline__ void fence_rel(){ asm volatile("fence.release.gpu;":::"memory"); }
__device__ __forceinline__ void fence_acq(){ asm volatile("fence.acquire.gpu;":::"memory"); }
__device__ __forceinline__ void fence_gpu(){ asm volatile("fence.acq_rel.gpu;":::"memory"); }

template<int NL,class V,class LDF,class OKF>
__device__ __forceinline__ int poll1(V* u,LDF ld,OKF ok,bool& dead,int code){
  #pragma unroll
  for(int i=0;i<NL;i++) u[i]=ld(i);
  int guard=0;
  while(true){
    bool f[NL]; bool a=true;
    #pragma unroll
    for(int i=0;i<NL;i++){ f[i]=ok(u[i]); a=a&&f[i]; }
    if(__all_sync(~0u,a)||dead) break;
    #pragma unroll
    for(int i=0;i<NL;i++) if(!f[i]) u[i]=ld(i);
    if(++guard>GUARD){ dead=true; g_err=code; }
  }
  return guard;
}
template<int NL,class V,class LDF,class OKF>
__device__ __forceinline__ int poll2(V* u,LDF ld,OKF ok,bool& dead,int code){
  int guard=0;
  while(true){
    bool f[NL]; bool a=true;
    #pragma unroll
    for(int i=0;i<NL;i++){ f[i]=ok(u[i]); a=a&&f[i]; }
    if(__all_sync(~0u,a)||dead) break;
    #pragma unroll
    for(int i=0;i<NL;i++) if(!f[i]) u[i]=ld(i);
    if(++guard>GUARD){ dead=true; g_err=code; }
  }
  return guard;
}
__device__ __forceinline__ void spin(uint32_t n){ uint32_t t0,t1; asm volatile("mov.u32 %0, %%clock;":"=r"(t0)); do{ asm volatile("mov.u32 %0, %%clock;":"=r"(t1)); }while(t1-t0<n); }
static_assert(!EKM||RTB<16,"final items wait for the recurrence");
template<int N> __device__ __forceinline__ void wgmma(float* d,uint32_t da,uint32_t db,int sc);
template<int N> __device__ __forceinline__ void wgmma_rs(float* d,const uint32_t* a,uint32_t db,int sc);
template<> __device__ __forceinline__ void wgmma<128>(float* d,uint32_t da,uint32_t db,int sc){
  asm volatile("{\n.reg .pred p;\n.reg .b64 xa, xb;\nmov.b64 xa, {%64, 0x40000040};\nmov.b64 xb, {%65, 0x40000040};\nsetp.ne.b32 p, %66, 0;\nwgmma.mma_async.sync.aligned.m64n128k16.f32.bf16.bf16 {%0,%1,%2,%3,%4,%5,%6,%7,%8,%9,%10,%11,%12,%13,%14,%15,%16,%17,%18,%19,%20,%21,%22,%23,%24,%25,%26,%27,%28,%29,%30,%31,%32,%33,%34,%35,%36,%37,%38,%39,%40,%41,%42,%43,%44,%45,%46,%47,%48,%49,%50,%51,%52,%53,%54,%55,%56,%57,%58,%59,%60,%61,%62,%63}, xa, xb, p, 1, 1, 0, 1;\n}"
   :"+f"(d[0]),"+f"(d[1]),"+f"(d[2]),"+f"(d[3]),"+f"(d[4]),"+f"(d[5]),"+f"(d[6]),"+f"(d[7]),"+f"(d[8]),"+f"(d[9]),"+f"(d[10]),"+f"(d[11]),"+f"(d[12]),"+f"(d[13]),"+f"(d[14]),"+f"(d[15]),"+f"(d[16]),"+f"(d[17]),"+f"(d[18]),"+f"(d[19]),"+f"(d[20]),"+f"(d[21]),"+f"(d[22]),"+f"(d[23]),"+f"(d[24]),"+f"(d[25]),"+f"(d[26]),"+f"(d[27]),"+f"(d[28]),"+f"(d[29]),"+f"(d[30]),"+f"(d[31]),"+f"(d[32]),"+f"(d[33]),"+f"(d[34]),"+f"(d[35]),"+f"(d[36]),"+f"(d[37]),"+f"(d[38]),"+f"(d[39]),"+f"(d[40]),"+f"(d[41]),"+f"(d[42]),"+f"(d[43]),"+f"(d[44]),"+f"(d[45]),"+f"(d[46]),"+f"(d[47]),"+f"(d[48]),"+f"(d[49]),"+f"(d[50]),"+f"(d[51]),"+f"(d[52]),"+f"(d[53]),"+f"(d[54]),"+f"(d[55]),"+f"(d[56]),"+f"(d[57]),"+f"(d[58]),"+f"(d[59]),"+f"(d[60]),"+f"(d[61]),"+f"(d[62]),"+f"(d[63]):"r"(da),"r"(db),"r"(sc));
}
template<> __device__ __forceinline__ void wgmma<192>(float* d,uint32_t da,uint32_t db,int sc){
  asm volatile("{\n.reg .pred p;\n.reg .b64 xa, xb;\nmov.b64 xa, {%96, 0x40000040};\nmov.b64 xb, {%97, 0x40000040};\nsetp.ne.b32 p, %98, 0;\nwgmma.mma_async.sync.aligned.m64n192k16.f32.bf16.bf16 {%0,%1,%2,%3,%4,%5,%6,%7,%8,%9,%10,%11,%12,%13,%14,%15,%16,%17,%18,%19,%20,%21,%22,%23,%24,%25,%26,%27,%28,%29,%30,%31,%32,%33,%34,%35,%36,%37,%38,%39,%40,%41,%42,%43,%44,%45,%46,%47,%48,%49,%50,%51,%52,%53,%54,%55,%56,%57,%58,%59,%60,%61,%62,%63,%64,%65,%66,%67,%68,%69,%70,%71,%72,%73,%74,%75,%76,%77,%78,%79,%80,%81,%82,%83,%84,%85,%86,%87,%88,%89,%90,%91,%92,%93,%94,%95}, xa, xb, p, 1, 1, 0, 1;\n}"
   :"+f"(d[0]),"+f"(d[1]),"+f"(d[2]),"+f"(d[3]),"+f"(d[4]),"+f"(d[5]),"+f"(d[6]),"+f"(d[7]),"+f"(d[8]),"+f"(d[9]),"+f"(d[10]),"+f"(d[11]),"+f"(d[12]),"+f"(d[13]),"+f"(d[14]),"+f"(d[15]),"+f"(d[16]),"+f"(d[17]),"+f"(d[18]),"+f"(d[19]),"+f"(d[20]),"+f"(d[21]),"+f"(d[22]),"+f"(d[23]),"+f"(d[24]),"+f"(d[25]),"+f"(d[26]),"+f"(d[27]),"+f"(d[28]),"+f"(d[29]),"+f"(d[30]),"+f"(d[31]),"+f"(d[32]),"+f"(d[33]),"+f"(d[34]),"+f"(d[35]),"+f"(d[36]),"+f"(d[37]),"+f"(d[38]),"+f"(d[39]),"+f"(d[40]),"+f"(d[41]),"+f"(d[42]),"+f"(d[43]),"+f"(d[44]),"+f"(d[45]),"+f"(d[46]),"+f"(d[47]),"+f"(d[48]),"+f"(d[49]),"+f"(d[50]),"+f"(d[51]),"+f"(d[52]),"+f"(d[53]),"+f"(d[54]),"+f"(d[55]),"+f"(d[56]),"+f"(d[57]),"+f"(d[58]),"+f"(d[59]),"+f"(d[60]),"+f"(d[61]),"+f"(d[62]),"+f"(d[63]),"+f"(d[64]),"+f"(d[65]),"+f"(d[66]),"+f"(d[67]),"+f"(d[68]),"+f"(d[69]),"+f"(d[70]),"+f"(d[71]),"+f"(d[72]),"+f"(d[73]),"+f"(d[74]),"+f"(d[75]),"+f"(d[76]),"+f"(d[77]),"+f"(d[78]),"+f"(d[79]),"+f"(d[80]),"+f"(d[81]),"+f"(d[82]),"+f"(d[83]),"+f"(d[84]),"+f"(d[85]),"+f"(d[86]),"+f"(d[87]),"+f"(d[88]),"+f"(d[89]),"+f"(d[90]),"+f"(d[91]),"+f"(d[92]),"+f"(d[93]),"+f"(d[94]),"+f"(d[95]):"r"(da),"r"(db),"r"(sc));
}
template<> __device__ __forceinline__ void wgmma_rs<64>(float* d,const uint32_t* a,uint32_t db,int sc){
  asm volatile("{\n.reg .pred p;\n.reg .b64 xb;\nmov.b64 xb, {%36, 0x40000040};\nsetp.ne.b32 p, %37, 0;\nwgmma.mma_async.sync.aligned.m64n64k16.f32.bf16.bf16 {%0,%1,%2,%3,%4,%5,%6,%7,%8,%9,%10,%11,%12,%13,%14,%15,%16,%17,%18,%19,%20,%21,%22,%23,%24,%25,%26,%27,%28,%29,%30,%31}, {%32,%33,%34,%35}, xb, p, 1, 1, 0;\n}"
   :"+f"(d[0]),"+f"(d[1]),"+f"(d[2]),"+f"(d[3]),"+f"(d[4]),"+f"(d[5]),"+f"(d[6]),"+f"(d[7]),"+f"(d[8]),"+f"(d[9]),"+f"(d[10]),"+f"(d[11]),"+f"(d[12]),"+f"(d[13]),"+f"(d[14]),"+f"(d[15]),"+f"(d[16]),"+f"(d[17]),"+f"(d[18]),"+f"(d[19]),"+f"(d[20]),"+f"(d[21]),"+f"(d[22]),"+f"(d[23]),"+f"(d[24]),"+f"(d[25]),"+f"(d[26]),"+f"(d[27]),"+f"(d[28]),"+f"(d[29]),"+f"(d[30]),"+f"(d[31]):"r"(a[0]),"r"(a[1]),"r"(a[2]),"r"(a[3]),"r"(db),"r"(sc));
}
#define PPF 0
#define PPN 61440
#define PPFA(i) (size_t)(i)
__device__ __align__(128) uint32_t g_sml[NCTA];
constexpr int PRE_T=704;
__global__ void __launch_bounds__(PRE_T) k_pre(const bf16* __restrict__ x,const bf16* __restrict__ mem0,const char* wk,const char* wv){
  const int warp=threadIdx.x>>5, lane=threadIdx.x&31;
  const int row=blockIdx.x*(PRE_T/32)+warp;
  asm volatile("griddepcontrol.launch_dependents;");
  if(threadIdx.x==0){ uint32_t sm_; asm volatile("mov.u32 %0, %%smid;":"=r"(sm_)); g_sml[blockIdx.x]=sm_; }
  uint2 u[5];
  static_assert(2*(NCTA-1)*PRE_T>=(NSEG-1)*1280,"init");
  {
    int i=blockIdx.x*PRE_T+threadIdx.x; constexpr int n=(NCTA-1)*PRE_T;
    if(blockIdx.x==NCTA-1){
      if(warp>=8) return;
      extern __shared__ uint32_t smx[];
      uint32_t w[10], mx=0;
      #pragma unroll
      for(int j=0;j<10;j++){ const int k=threadIdx.x+256*j; const uint16_t* mp=(const uint16_t*)mem0+(((k>>3)&3)*2+((k>>5)&1))*D+(k>>6)*16+(k&7);
        w[j]=mp[0]|((uint32_t)mp[8]<<16); mx=max(mx,max(w[j]&0x7fffu,(w[j]>>16)&0x7fffu)); }
      mx=__reduce_max_sync(~0u,mx); if(lane==0) smx[warp]=mx;
      bar_sync(1,256);
      #pragma unroll
      for(int j=0;j<8;j++) mx=max(mx,smx[j]);
      const uint32_t eb=min(max(mx>>7,40u),254u); const float sc=__uint_as_float((280u-eb)<<23);
      #pragma unroll
      for(int j=0;j<10;j++) g_acc[threadIdx.x+256*j]=((unsigned long long)(long long)__float2int_rn(__uint_as_float(w[j]&0xffff0000u)*sc)<<35)+((unsigned long long)(long long)__float2int_rn(__uint_as_float(w[j]<<16)*sc)<<6);
      if(threadIdx.x<NCTA*2) g_nrm[threadIdx.x]=SENT;
      if(threadIdx.x==0) g_nrm[NCTA*2]=(eb-29u)<<23;
      return;
    }
    const uint2* p=(const uint2*)(x+(size_t)min(row,S-1)*D);
    #pragma unroll
    for(int j=0;j<5;j++) asm volatile("ld.global.nc.v2.u32 {%0,%1}, [%2];":"=r"(u[j].x),"=r"(u[j].y):"l"(p+lane+32*j));
    #pragma unroll
    for(int j=0;j<2;j++){ const int k=1280+i+j*n; if(k<NSEG*1280) ((ulonglong2*)g_acc)[k]=make_ulonglong2(ACC_INIT,ACC_INIT); }
    if(i==0) g_err=0;
    if(i<NCTA*32) g_flag[i]=0;
    if(i<C_NUM) g_cnt[i]=0;
  }
  #define PFW { const int i=blockIdx.x*PRE_T+threadIdx.x; if(i<PPN){ asm volatile("prefetch.global.L2 [%0];"::"l"(wk+(size_t)i*128+(u[4].y&zr)):"memory"); asm volatile("prefetch.global.L2 [%0];"::"l"(wv+(size_t)i*128+(u[4].y&zr)):"memory"); } }
  const uint32_t zr=PPF==2?(uint32_t)((size_t)wk&1):0u;
  if(PPF) PFW
  if(row>=S) return;
  float v[20];
  #pragma unroll
  for(int i=0;i<5;i++){ v[4*i]=__uint_as_float(u[i].x<<16); v[4*i+1]=__uint_as_float(u[i].x&0xffff0000u); v[4*i+2]=__uint_as_float(u[i].y<<16); v[4*i+3]=__uint_as_float(u[i].y&0xffff0000u); }
  #pragma unroll
  for(int pass=0;pass<2;pass++){
    float s=0;
    #pragma unroll
    for(int i=0;i<20;i++) s+=v[i];
    #pragma unroll
    for(int o=16;o;o>>=1) s+=__shfl_xor_sync(~0u,s,o);
    float mean=s*(1.f/D);
    float q=0;
    #pragma unroll
    for(int i=0;i<20;i++){ float d=v[i]-mean; q+=d*d; }
    #pragma unroll
    for(int o=16;o;o>>=1) q+=__shfl_xor_sync(~0u,q,o);
    float var=rb(q*(1.f/D)), mb=rb(mean);
    float den=rb(sqrtf(rb(var+1e-5f)));
    const float id=1.f/den;
    uint2* o=(uint2*)((pass?g_y:g_xn)+(size_t)row*D);
    #pragma unroll
    for(int i=0;i<5;i++){
      uint32_t w[2];
      #pragma unroll
      for(int j=0;j<2;j++){
        const uint32_t d=pack_bf16(v[4*i+2*j]-mb,v[4*i+2*j+1]-mb);
        w[j]=pack_bf16(__uint_as_float(d<<16)*id,__uint_as_float(d&0xffff0000u)*id);
        v[4*i+2*j]=__uint_as_float(w[j]<<16); v[4*i+2*j+1]=__uint_as_float(w[j]&0xffff0000u);
      }
      o[lane+32*i]=make_uint2(w[0],w[1]);
    }
  }
}

#define IL 0
#define LBF 0
#define KORD 0x5498327610ull
__host__ __device__ constexpr int kord(int y){ return (int)((KORD>>(4*y))&15); }
#define LTID 2
#define TQ2 1
#define TPF 60
#define ULAY 0
#define WGO 1
#define UBP 4
#define URM 63
#define UEB 24
#define NOF 0
#define EXD 0
#define UEX 1
#define ADELAY 0
#define KP 4
#define UXP 16
#define OPF 99
#define XGP 0
#define W3O 250
#define FW 3
#define WPA 1
#define WPB 1
#define PD 1200
#define PPOS 2
#define ADP 0
#define ADUP 64
#define ADDN 4
constexpr int SM_QS=0;
constexpr int SM_KS=49152;
constexpr int SM_OS=131072;
constexpr int SM_RED=180224;
constexpr int SM_P=SM_RED+3584;
constexpr int SM_PM=SM_RED+4096+3584;
constexpr int SM_MB=SM_PM+128;
constexpr int SM_MX=SM_PM+192, SM_SCL=SM_PM+224;
constexpr int SM_X5=SM_RED+8192+3584;
constexpr int SM_KX=SM_RED+16384;
constexpr int SM_VX=SM_KX+4096;
constexpr int SM_SCX=SM_VX+14336;
constexpr int SM_KRED=SM_SCX+6144;
constexpr int SM_VMX=SM_KRED+8192;
constexpr int SM_TOTAL=SM_VMX+3072, SM_NR=SM_VMX;
static_assert(SM_TOTAL<=232448,"smem");
__device__ __forceinline__ void wg32_rs(float* d,const uint32_t* a,uint32_t db){
  asm volatile("{\n.reg .b64 xb;\nmov.b64 xb, {%20, 0x40000040};\nwgmma.mma_async.sync.aligned.m64n32k16.f32.bf16.bf16 {%0,%1,%2,%3,%4,%5,%6,%7,%8,%9,%10,%11,%12,%13,%14,%15}, {%16,%17,%18,%19}, xb, 1, 1, 1, 0;\n}"
   :"+f"(d[0]),"+f"(d[1]),"+f"(d[2]),"+f"(d[3]),"+f"(d[4]),"+f"(d[5]),"+f"(d[6]),"+f"(d[7]),"+f"(d[8]),"+f"(d[9]),"+f"(d[10]),"+f"(d[11]),"+f"(d[12]),"+f"(d[13]),"+f"(d[14]),"+f"(d[15])
   :"r"(a[0]),"r"(a[1]),"r"(a[2]),"r"(a[3]),"r"(db));
}
__device__ __forceinline__ void wg32_rs0(float* d,const uint32_t* a,uint32_t db){
  asm volatile("{\n.reg .b64 xb;\nmov.b64 xb, {%20, 0x40000040};\nwgmma.mma_async.sync.aligned.m64n32k16.f32.bf16.bf16 {%0,%1,%2,%3,%4,%5,%6,%7,%8,%9,%10,%11,%12,%13,%14,%15}, {%16,%17,%18,%19}, xb, 0, 1, 1, 0;\n}"
   :"=f"(d[0]),"=f"(d[1]),"=f"(d[2]),"=f"(d[3]),"=f"(d[4]),"=f"(d[5]),"=f"(d[6]),"=f"(d[7]),"=f"(d[8]),"=f"(d[9]),"=f"(d[10]),"=f"(d[11]),"=f"(d[12]),"=f"(d[13]),"=f"(d[14]),"=f"(d[15])
   :"r"(a[0]),"r"(a[1]),"r"(a[2]),"r"(a[3]),"r"(db));
}
__device__ __forceinline__ void wg32_ss(float* d,uint32_t da,uint32_t db){
  asm volatile("{\n.reg .b64 xa, xb;\nmov.b64 xa, {%16, 0x00000180};\nmov.b64 xb, {%17, 0x40000040};\nwgmma.mma_async.sync.aligned.m64n32k16.f32.bf16.bf16 {%0,%1,%2,%3,%4,%5,%6,%7,%8,%9,%10,%11,%12,%13,%14,%15}, xa, xb, 1, 1, 1, 0, 0;\n}"
   :"+f"(d[0]),"+f"(d[1]),"+f"(d[2]),"+f"(d[3]),"+f"(d[4]),"+f"(d[5]),"+f"(d[6]),"+f"(d[7]),"+f"(d[8]),"+f"(d[9]),"+f"(d[10]),"+f"(d[11]),"+f"(d[12]),"+f"(d[13]),"+f"(d[14]),"+f"(d[15])
   :"r"(da),"r"(db));
}
__device__ __forceinline__ void wg32_ss0(float* d,uint32_t da,uint32_t db){
  asm volatile("{\n.reg .b64 xa, xb;\nmov.b64 xa, {%16, 0x00000180};\nmov.b64 xb, {%17, 0x40000040};\nwgmma.mma_async.sync.aligned.m64n32k16.f32.bf16.bf16 {%0,%1,%2,%3,%4,%5,%6,%7,%8,%9,%10,%11,%12,%13,%14,%15}, xa, xb, 0, 1, 1, 0, 0;\n}"
   :"=f"(d[0]),"=f"(d[1]),"=f"(d[2]),"=f"(d[3]),"=f"(d[4]),"=f"(d[5]),"=f"(d[6]),"=f"(d[7]),"=f"(d[8]),"=f"(d[9]),"=f"(d[10]),"=f"(d[11]),"=f"(d[12]),"=f"(d[13]),"=f"(d[14]),"=f"(d[15])
   :"r"(da),"r"(db));
}
#define TT(i)
template<int V> struct IC{ static constexpr int v=V; };
__device__ __forceinline__ uint32_t lds1(uint32_t a){ uint32_t v; asm volatile("ld.shared.u32 %0, [%1];":"=r"(v):"r"(a):"memory"); return v; }
__device__ __forceinline__ void sts1(uint32_t a,uint32_t x){ asm volatile("st.shared.u32 [%0], %1;"::"r"(a),"r"(x):"memory"); }

#define TS(i)
#define TSB(i)
#define PC(i) (void)np
#define TW(i)
#define TF(i)
#define TFP(i)

__device__ __forceinline__ void cp_commit(){ asm volatile("cp.async.commit_group;":::"memory"); }
template<int N> __device__ __forceinline__ void cp_wait(){ asm volatile("cp.async.wait_group %0;"::"n"(N):"memory"); }
__device__ __forceinline__ void tma2d(uint32_t dst,const CUtensorMap* tm,int c0,int c1,uint32_t mb){
  asm volatile("cp.async.bulk.tensor.2d.shared::cluster.global.mbarrier::complete_tx::bytes [%0], [%1, {%3, %4}], [%2];"::"r"(dst),"l"(tm),"r"(mb),"r"(c0),"r"(c1):"memory"); }
__device__ __forceinline__ void tma2d_pf(const CUtensorMap* tm,int c0,int c1){
  asm volatile("cp.async.bulk.prefetch.tensor.2d.L2.global [%0, {%1, %2}];"::"l"(tm),"r"(c0),"r"(c1):"memory"); }
constexpr unsigned long long PL_EF=0x12F0000000000000ull, PL_EN=0x1000000000000000ull;
__device__ __forceinline__ void tma2dh(uint32_t dst,const CUtensorMap* tm,int c0,int c1,uint32_t mb,unsigned long long pl){
  asm volatile("cp.async.bulk.tensor.2d.shared::cluster.global.mbarrier::complete_tx::bytes.L2::cache_hint [%0], [%1, {%3, %4}], [%2], %5;"::"r"(dst),"l"(tm),"r"(mb),"r"(c0),"r"(c1),"l"(pl):"memory"); }
__device__ __forceinline__ void tma2d_pfh(const CUtensorMap* tm,int c0,int c1,unsigned long long pl){
  asm volatile("cp.async.bulk.prefetch.tensor.2d.L2.global.L2::cache_hint [%0, {%1, %2}], %3;"::"l"(tm),"r"(c0),"r"(c1),"l"(pl):"memory"); }
#define HV 0
#define HK 0
#define HP 0
#define HUS 0
__device__ __forceinline__ uint32_t fin1(uint32_t s,uint32_t x,uint32_t gq){
  const uint32_t p=pack_bf16(__uint_as_float(s<<16)*__uint_as_float(gq<<16),__uint_as_float(s&0xffff0000u)*__uint_as_float(gq&0xffff0000u));
  return pack_bf16(__uint_as_float(x<<16)+__uint_as_float(p<<16),__uint_as_float(x&0xffff0000u)+__uint_as_float(p&0xffff0000u));
}
__device__ __forceinline__ void wg32_pu(float* d,uint32_t da,uint32_t db,int sc){
  asm volatile("{\n.reg .pred p;\n.reg .b64 xa, xb;\nmov.b64 xa, {%16, 32};\nmov.b64 xb, {%17, 8};\nsetp.ne.b32 p, %18, 0;\nwgmma.mma_async.sync.aligned.m64n32k16.f32.bf16.bf16 {%0,%1,%2,%3,%4,%5,%6,%7,%8,%9,%10,%11,%12,%13,%14,%15}, xa, xb, p, 1, 1, 0, 0;\n}"
   :"+f"(d[0]),"+f"(d[1]),"+f"(d[2]),"+f"(d[3]),"+f"(d[4]),"+f"(d[5]),"+f"(d[6]),"+f"(d[7]),"+f"(d[8]),"+f"(d[9]),"+f"(d[10]),"+f"(d[11]),"+f"(d[12]),"+f"(d[13]),"+f"(d[14]),"+f"(d[15])
   :"r"(da),"r"(db),"r"(sc));
}
__device__ __forceinline__ void stsm4t(uint32_t a,uint32_t r0,uint32_t r1,uint32_t r2,uint32_t r3){ asm volatile("stmatrix.sync.aligned.m8n8.x4.trans.shared.b16 [%0], {%1,%2,%3,%4};"::"r"(a),"r"(r0),"r"(r1),"r"(r2),"r"(r3):"memory"); }
__device__ __forceinline__ void red_rel(uint32_t* p){ asm volatile("red.release.gpu.global.add.u32 [%0], 1;"::"l"(p):"memory"); }
struct RParams { CUtensorMap k,v,w[4],u; const char* wq; const char* wo; const bf16* x; bf16* out; };
#define SO 0
#define SA 1
#define SEF 7
#define SPF 1
__global__ void __launch_bounds__(256,1) k_rec(const __grid_constant__ RParams P,const uint32_t zero){
  extern __shared__ __align__(1024) uint8_t sm[];
  int tid; asm volatile("mov.u32 %0, %%tid.x;":"=r"(tid));
  if(LTID>1) tid=__shfl_sync(~0u,tid,tid&31);
  __builtin_assume(tid>=0&&tid<256);
  const int warp=__shfl_sync(~0u,tid>>5,0), lane=tid&31, g=lane>>2, t=lane&3;
  const int b=blockIdx.x, h=b/3, c=b-3*h;
  const uint32_t sb=(uint32_t)__cvta_generic_to_shared(sm);
  const int kq=warp&3, mg=warp>>2, wt=warp-mg;
  const uint32_t s16=sb+lane*16;
  const uint32_t qs=lane*16+__shfl_sync(~0u,sb+(mg?SM_KS+kq*20480:SM_QS+kq*12288),0), m5u=__shfl_sync(~0u,sb+SM_X5+(kq>>1)*4096+(kq&1)*256,0), mo=((lane>>3)&1), os=sb+SM_OS+kq*12288+mo*6144+(lane>>4)*128+(lane&7)*16, us=sb+SM_VX+wt*2048+mo*512+(lane>>4)*128+(lane&7)*16;
  const uint32_t XS=sb+SM_MB, KVB=sb+SM_MB+8, XV=sb+SM_MB+16, XL=sb+SM_MB+24;
  #define tmK P.k
  #define tmV P.v
  GT(0);
  asm volatile("griddepcontrol.launch_dependents;");
  const int ntile=c==0?14:13, tile0=c==0?0:(1+13*c);
  uint32_t pw[40][4];
#define SG(i)
  SG(0);
  {
    static_assert(KP==4,"setup");
    const uint32_t qb=qs-lane*16, SBR=sb+SM_NR+128+warp*32, ob=sb+(mg?SM_OS:SM_RED)+kq*12288;
    unsigned long long plf, pln;
    asm volatile("createpolicy.fractional.L2::evict_first.b64 %0, 1.0;":"=l"(plf)); asm volatile("createpolicy.fractional.L2::evict_normal.b64 %0, 1.0;":"=l"(pln));
    const unsigned long long plq=(mg?(SEF&4):(SEF&2))?plf:pln, plo=(SEF&1)?plf:pln;
    auto wbox=[&](int rd,int sl,int mode){
      const int kb=rd?(sl<6?sl:sl-6):(sl<4?sl+6:sl), k=mg?(kb+5)%10:kb;
      const CUtensorMap* tm=&P.w[mg?(sl<(rd?6:4)?1:2):0];
      const int c0=h*DH+64*c, c1=80*kq+8*k;
      if(mode) asm volatile("cp.async.bulk.prefetch.tensor.3d.L2.global.L2::cache_hint [%0, {%1, %2, 0}], %3;"::"l"(tm),"r"(c0),"r"(c1),"l"(plq):"memory");
      else asm volatile("cp.async.bulk.tensor.3d.shared::cluster.global.mbarrier::complete_tx::bytes.L2::cache_hint [%0], [%1, {%3, %4, 0}], [%2], %5;"::"r"(qb+sl*2048),"l"(tm),"r"(SBR+((rd||(!mg&&sl>=4))?8:0)),"r"(c0),"r"(c1),"l"(plq):"memory");
    };
    if(lane==0){
      mbar_init(SBR,1); mbar_init(SBR+8,1); mbar_init(SBR+16,1);
      asm volatile("fence.mbarrier_init.release.cluster;":::"memory");
      mbar_expect(SBR,mg?20480:8192); mbar_expect(SBR+8,mg?20480:12288); mbar_expect(SBR+16,12288);
    }
    __syncwarp();
    if(lane<(mg?10:6)) wbox(0,lane,0);
    if(lane<6) asm volatile("cp.async.bulk.tensor.2d.shared::cluster.global.mbarrier::complete_tx::bytes.L2::cache_hint [%0], [%1, {%3, %4}], [%2], %5;"::"r"(ob+(mg?(lane>>1)*2048+(lane&1)*6144:lane*2048)),"l"(&P.w[3]),"r"(SBR+16),"r"((tile0+2*wt)*16),"r"(h*DH+((2*c+lane)%6)*32),"l"(plo):"memory");
    if(SPF&&lane<(mg?(SPF>1?10:0):4)) wbox(1,lane,1);
    __syncwarp();
    SG(1);
    float nr[4][2][4];
    #pragma unroll
    for(int i=0;i<32;i++) nr[i>>3][(i>>2)&1][i&3]=0.f;
    auto sq=[&](int n,const uint32_t* r){ mma16816(nr[n][0],r,r[0],r[2]); mma16816(nr[n][1],r,r[1],r[3]); };
    auto dg=[&](const float* d,int o){ return g==2*t?d[o]:(g==2*t+1?d[o+1]:0.f); };
    auto swait=[&](uint32_t a){ int gd=0; while(!mbar_try(a,0)){ if(++gd>GUARD){ g_err=9; break; } } };
    const int p8=((lane>>1)&3)+4*(lane&1), r16=(lane&7)+(lane>>4)*8;
    uint32_t ak[4], av[4], ao[2];
    #pragma unroll
    for(int j=0;j<4;j++){ ak[j]=qb+(p8+(lane>>4)*8)*128+(((2*j+mo)^p8)<<4); av[j]=qb+(p8+(lane>>4)*8)*128+(((2*((j+kq)&3)+mo)^p8)<<4); }
    #pragma unroll
    for(int i=0;i<2;i++) ao[i]=ob+r16*64+(((2*i+mo)^((lane>>1)&3))<<4);
    swait(SBR);
    SG(2);
    #pragma unroll
    for(int u=0;u<16;u++) ldsm4t(pw[u],ak[u&3]+(u>>2)*2048);
    if(SA&&!mg){
      uint32_t d0=0;
      #pragma unroll
      for(int u=0;u<16;u+=2) d0^=pw[u][0]^pw[u+1][0];
      if(lane+(d0&zero)<4) wbox(1,lane,0);
      __syncwarp();
    }
    swait(SBR+(mg?0:16));
    SG(3);
    uint32_t dp=0;
    {
      uint32_t a2[4];
      #pragma unroll
      for(int j=0;j<4;j++) a2[j]=mg?av[j]+8192:ao[j&1]+(j>>1)*1024;
      #pragma unroll
      for(int u=0;u<24;u++){ ldsm4t(pw[16+u],a2[u&3]+(u>>2)*2048); if(!SA) sq((u&1)*2,pw[16+u]); }
      #pragma unroll
      for(int u=0;u<40;u+=2) dp^=pw[u][0]^pw[u+1][0];
      dp&=zero;
    }
    if(lane+dp<(mg?10:(SA?0:4))) wbox(1,lane,0);
    __syncwarp();
    if(SA){
      #pragma unroll
      for(int u=0;u<24;u++) sq((u&1)*2,pw[16+u]);
    }
    SG(4);
    if(mg){
      swait(SBR+16);
      #pragma unroll 1
      for(int y=0;y<3;y++){
        uint32_t r[8][4];
        #pragma unroll
        for(int f=0;f<8;f++){ ldsm4t(r[f],ao[f&1]+y*2048+((f>>1)&1)*1024+(f>>2)*6144); sq(1+(f&1)*2,r[f]); }
        __syncwarp();
        #pragma unroll
        for(int f=0;f<8;f++) stsm4(os+y*2048+f*256,r[f][0],r[f][1],r[f][2],r[f][3]);
      }
    } else {
      bar_sync(5+dp,128);
      if(tid==96){
        mbar_init(XS,5); mbar_init(KVB,1); mbar_init(XV,1); mbar_init(XL,4);
        for(int i=0;i<4;i++){ mbar_init(sb+SM_PM+256+i*8,2); mbar_init(sb+SM_PM+288+i*8,4); }
        asm volatile("fence.mbarrier_init.release.cluster;":::"memory");
        mbar_expect(XS,4096); mbar_expect(XV,2048);
        int gd=0; while(ld_acq(g_cnt+C_KV)<64){ if(++gd>GUARD){ g_err=7; break; } } fence_async_g();
        mbar_expect(KVB,32*512);
        tma2d(sb+SM_KX,&tmK,h*DH+64*c,0,KVB);
        #pragma unroll 1
        for(int i=0;i<3;i++) tma2d(sb+SM_VX+i*4096,&tmV,h*DH+64*i,0,KVB);
        tma2d_pf(&tmK,h*DH+64*c,32); tma2d_pf(&tmV,h*DH+64*c,32);
      }
      if(tid==32) sts1(sb+SM_SCL+8,g_nrm[NCTA*2]);
      __syncwarp();
    }
    SG(5);
    swait(SBR+8);
    SG(6);
    #pragma unroll 1
    for(int y=0;y<(mg?10:6);y+=2){
      uint32_t r[8][4];
      #pragma unroll
      for(int j=0;j<8;j++) ldsm4t(r[j],(y<6?ak[j&3]:av[j&3])+y*2048+(j>>2)*2048);
      __syncwarp();
      #pragma unroll
      for(int j=0;j<8;j++) sts4r(qs+y*2048+j*512,r[j]);
      if(y>=6){
        #pragma unroll
        for(int j=0;j<8;j++) sq((j&1)*2,r[j]);
      }
    }
    SG(7);
    float d4[4][2];
    #pragma unroll
    for(int i=0;i<4;i++){ d4[i][0]=dg(nr[i][0],0); d4[i][1]=dg(nr[i][1],2); }
    float nv=mg?(d4[0][0]+d4[0][1])+(d4[2][0]+d4[2][1]):0.f;
    #pragma unroll
    for(int o=16;o;o>>=1) nv+=__shfl_xor_sync(~0u,nv,o);
    const uint32_t no=__reduce_max_sync(~0u,__float_as_uint(mg?fmaxf(d4[1][0]+d4[3][0],d4[1][1]+d4[3][1]):fmaxf(d4[0][0]+d4[2][0],d4[0][1]+d4[2][1])));
    if(lane==0){
      sts2(sb+SM_NR+warp*8,__float_as_uint(nv),no);
      #pragma unroll
      for(int i=0;i<3;i++) asm volatile("mbarrier.inval.shared.b64 [%0];"::"r"(SBR+i*8):"memory");
    }
  }
  fence_async();
  __syncthreads();
  SG(8);
  {
    float a=0.f; uint32_t o=0;
    if(warp==0){
      #pragma unroll
      for(int w=0;w<8;w++){ const uint2 x=lds2(sb+SM_NR+w*8); a+=__uint_as_float(x.x); o=max(o,x.y); }
      o=min(o,0x7f800000u);
    }
    asm volatile("barrier.cluster.arrive.relaxed.aligned;"::"r"(o):"memory");
    if(tid==0) stg_rlx2(g_nrm+b*2,min(__float_as_uint(a),0x7f800000u),o);
    asm volatile("barrier.cluster.wait.acquire.aligned;":::"memory");
  }
  SG(9);
  uint32_t pd=PD;
  bool dead=false;
  const uint32_t qrd=sb+SM_RED+1024+((lane>>3)&1)*4096+(lane>>4)*128+(lane&7)*16+kq*256;
  uint32_t rsc[2];
  rsc[0]=mapa(sb,c==2?0:c+1); rsc[1]=mapa(sb,c==0?2:c-1);
  GT(1);
  auto loop=[&](auto MGc){
  constexpr int MG=decltype(MGc)::v;
  uint32_t buf[8][4], um[2][2]={{0,0},{0,0}}, ex0=0, ex1=0;
  uint32_t eo1=(uint32_t)((32+(h>>2))*40960+(tile0+2*wt)*1024+(h&3)*128+lane*4), eo2=(uint32_t)(h*3072+(4*c+kq)*256+lane*4);
  uint32_t so=(uint32_t)((kq*10+MG*5)*512+(g&1)*256+(g>>1)*64+t*16)^zero;
  bool kvok=false;
  #define EXPU { char* um_=(char*)g_u+eo1; _Pragma("unroll") for(int i=0;i<2;i++) if(i==0||2*wt+1<ntile){ stg1(um_+i*1024,um[i][0]); stg1(um_+i*1024+512,um[i][1]); } }
  #define EXPK { char* ep=(char*)g_km+eo2; stg1(ep,ex0); stg1(ep+128,ex1); }
  #define UBULK { const uint32_t o_=(us-sb)&~2047u; asm volatile("{\n.reg .pred p;\nelect.sync _|p, 0xffffffff;\n@p cp.async.bulk.global.shared::cta.bulk_group.L2::cache_hint [%0], [%1], %2, %3;\n@p cp.async.bulk.commit_group;\n}" \
      ::"l"((char*)g_u+(uint32_t)(s*1638400+h*40960+tile0*1024-SM_VX+o_)),"r"(sb+o_),"r"(2*wt+1<ntile?2048:1024),"l"(s<HUS?PL_EF:PL_EN):"memory"); }
  uint32_t t0; asm volatile("mov.u32 %0, %%clock;":"=r"(t0)); t0-=4096;
  #define MB0(k) mb[k][0]
  #define MB1(k) mb[k][1]
  #pragma unroll 1
  for(int s=0;s<NSEG;s++){
    const bool last=s==NSEG-1;
    float u[2][16];
    const char* src=(const char*)g_acc+so;
    uint4 m[5];
    #define SPIN(T,N) { uint32_t t1; do{ asm volatile("mov.u32 %0, %%clock;":"=r"(t1)); }while((int)(t1-(T))<(int)(N)); }
    #define PLD { SPIN(t0,pd) _Pragma("unroll") for(int p=0;p<5;p++) m[p]=ldg_rlx4((const uint32_t*)(src+p*512)); SPIN(t0,pd) TFP(21); }
    {
      if(!kvok){ int gd=0; while(!mbar_try(KVB,s&1)){ if(dead) break; if(++gd>GUARD){ dead=true; g_err=6; } } }
      TFP(16);
      const uint32_t da=(((sb+SM_OS)>>4)&0x3fff)|(8u<<16);
      const uint32_t dv=(((sb+SM_VX)>>4)&0x3fff)|(1u<<16);
      const uint32_t vb[3]={dv+c*256,dv+(c==2?0:c+1)*256,dv+(c==0?2:c-1)*256};
      asm volatile("wgmma.fence.sync.aligned;":::"memory");
      if constexpr(MG){
        #pragma unroll
        for(int y=0;y<24;y++){
          const int i=WGO?(y&1):(y>=12), x=WGO?(y>>1):(y%12);
          if(x==0) wg32_ss0(u[i],da+i*16,vb[0]); else wg32_ss(u[i],da+(x*2+i)*16,vb[x>>2]+(x&3)*2);
          if(y==WPB){ EXPU SPIN(t0,0) }
        }
      } else {
        #pragma unroll
        for(int y=0;y<24;y++){
          const int i=WGO?(y&1):(y>=12), x=WGO?(y>>1):(y%12);
          if(x==0) wg32_rs0(u[i],pw[16+i],vb[0]); else wg32_rs(u[i],pw[16+x*2+i],vb[x>>2]+(x&3)*2);
          if(y==WPA&&warp!=3){ EXPU EXPK }
        }
      }
      asm volatile("wgmma.commit_group.sync.aligned;":::"memory");
      TFP(18);
      if(!MG&&warp==3){
        EXPK
        if(lane==0&&s+2<NSEG){ tma2d_pfh(&tmK,h*DH+64*c,(s+2)*32,HP&1?PL_EF:PL_EN); tma2d_pfh(&tmV,h*DH+64*c,(s+2)*32,HP&2?PL_EF:PL_EN); }
        if(TPF&&lane==0&&b<80&&(uint32_t)(s-TPF)<4u) asm volatile("cp.async.bulk.prefetch.tensor.3d.L2.global [%0, {0, %1, %2}];"::"l"(&P.u),"r"(b%20),"r"((RTB*4+b/20)*40+(s-TPF)*10):"memory");
        __syncwarp();
        if(b<80&&lane<2&&s+2<NSEG) asm volatile("prefetch.global.L2 [%0];"::"l"(g_acc+(size_t)(s+2)*2560+b*32+lane*16));
      }
      PLD
    }
    const uint32_t mx=s16+SM_RED+kq*4096, m5=m5u+lane*8;
    {
      asm volatile("wgmma.wait_group.sync.aligned 0;":::"memory");
      TFP(19);
      if(MG||warp!=3){
        if(UEX) asm volatile("cp.async.bulk.wait_group 0;":::"memory");
        bar_sync(7,256);
        TFP(20);
        #pragma unroll
        for(int i=0;i<2;i++)
          #pragma unroll
          for(int kk=0;kk<2;kk++)
            stsm4(us+i*1024+kk*256,pack_bf16(u[i][8*kk],u[i][8*kk+1]),pack_bf16(u[i][8*kk+2],u[i][8*kk+3]),pack_bf16(u[i][8*kk+4],u[i][8*kk+5]),pack_bf16(u[i][8*kk+6],u[i][8*kk+7]));
        if(!LBF) fence_async();
        #pragma unroll
        for(int i=0;i<8;i++) lds4r(buf[i],qs+i*512);
        if(LBF) fence_async();
      } else {
        #pragma unroll
        for(int i=0;i<8;i++) lds4r(buf[i],qs+i*512);
        bar_sync(7,256);
        asm volatile("{\n.reg .pred p, q;\nsetp.eq.u32 p, %0, 0;\nsetp.eq.and.u32 q, %1, 0, p;\n@q fence.release.gpu;\n@p st.relaxed.gpu.global.u32 [%2], %3;\n}"::"r"(lane),"r"((s&3)|NOF),"l"(g_flag+b*32),"r"(s):"memory");
      }
      SPIN(t0,pd)
      TFP(17);
    }
    uint32_t mb[10][2];
    float acc[4][4];
    #pragma unroll
    for(int i=0;i<4;i++){ acc[i][0]=acc[i][1]=acc[i][2]=acc[i][3]=0.f; }
    #define KST(k) { _Pragma("unroll") for(int j=0;j<4;j++){ \
      if((k)<6){ mma16816(acc[j],buf[((k)&1)*4+j],MB0(k),MB1(k)); if(MG||(k)<4) lds4r(buf[((k)&1)*4+j],qs+((k)*4+j+8)*512); } \
      else mma16816(acc[j],pw[(k)>=6?((k)-6)*4+j:0],MB0(k),MB1(k)); } }
    {
      auto okf=[&](const uint4& v){ return ((v.x|v.z)&63u)==0; };
      const int np=poll2<5>(m,[&](int i){ return ldg_rlx4((const uint32_t*)(src+i*512)); },okf,dead,1);
      TW(0); PC(0); TFP(14);
      if(ADP){ if(np) pd=min(pd+ADUP,2000u); else pd=max(pd-ADDN,(uint32_t)ADP); }
      #pragma unroll
      for(int p=0;p<5;p++){
        mb[p][0]=pack_bf16((float)(int)__funnelshift_r(m[p].x,m[p].y,3),(float)(int)m[p].y);
        mb[p][1]=pack_bf16((float)(int)__funnelshift_r(m[p].z,m[p].w,3),(float)(int)m[p].w);
        if(p==0) sts2(MG?m5:mx-lane*8+3072,mb[0][0],mb[0][1]);
        if(p==2||p==4) sts4(mx+((MG?0:4)+(p>>2))*512,make_uint4(mb[p-1][0],mb[p-1][1],mb[p][0],mb[p][1]));
        if(p<IL) KST(p)
      }
      bar_arrive((MG?12:8)+kq,64);
      if(UEX&&UBP==1&&(MG||warp!=3)) UBULK
    }
    #define XGET { bar_sync((MG?8:12)+kq,64); const uint2 x=lds2(MG?mx-lane*8+3072:m5); mb[5][0]=x.x; mb[5][1]=x.y; \
      _Pragma("unroll") for(int p=0;p<2;p++){ const uint4 y=lds4(mx+((MG?4:0)+p)*512); mb[6+2*p][0]=y.x; mb[6+2*p][1]=y.y; mb[7+2*p][0]=y.z; mb[7+2*p][1]=y.w; } }
    #define XMAX { uint32_t a=amax2(amax2(amax2(mb[0][0],mb[0][1]),amax2(mb[1][0],mb[1][1])),amax2(amax2(amax2(mb[2][0],mb[2][1]),amax2(mb[3][0],mb[3][1])),amax2(mb[4][0],mb[4][1]))); \
      a=__reduce_max_sync(~0u,max(a&0x7fff0000u,(a<<16)&0x7fff0000u)); if(lane==0) sts1(sb+SM_MX+warp*4,a); }
    TS(0); TF(0);
    uint32_t ux[2][2][4];
    #define UXDEP (((ux[0][0][0]^ux[0][1][0])^(ux[1][0][0]^ux[1][1][0]))&zero)
    if constexpr(MG){
      #pragma unroll
      for(int y=IL;y<10;y++){
        KST(kord(y))
        if(y==XGP) XGET
        if(y==5) XMAX
        if(UEX&&UBP==y+2) UBULK
      }
      TF(1);
      {
        const uint32_t ra=s16+SM_KRED+kq*2048;
        #pragma unroll
        for(int i=0;i<4;i++) sts4f(ra+i*512,acc[i]);
      }
      bar_arrive(1,256);
#define VK(u) ((u)>>2)
      #pragma unroll
      for(int i=0;i<4;i++){ acc[i][0]=acc[i][1]=acc[i][2]=acc[i][3]=0.f; }
      #pragma unroll
      for(int y=0;y<40;y++){
        constexpr int NS_=4*KP;
        const int u=y<8?y:(y<20?y-8+NS_:(y<12+NS_?y-12:y));
        const int sl=(u+40-NS_)&7;
        if(u<NS_){ mma16816(acc[u&3],buf[sl],MB0(VK(u)),MB1(VK(u))); if(u+8<NS_) lds4r(buf[sl],qs+(48-NS_+u)*512); }
        else mma16816(acc[u&3],pw[u],MB0(VK(u)),MB1(VK(u)));
        if(y>=OPF&&y<OPF+8) ldsm4(buf[(y-OPF)&7],os+((y-OPF)&7)*256);
        if(y>=UXP&&y<UXP+4) ldsm4(ux[(y-UXP)>>1][(y-UXP)&1],us+((y-UXP)>>1)*1024+((y-UXP)&1)*256);
      }
      TF(2);
      const uint32_t ra=s16+SM_RED+1536;
      #pragma unroll
      for(int i=1;i<4;i++) sts4f(ra+kq*4096+i*512,acc[i]);
      bar_sync(3,128);
      const float cs=__uint_as_float(lds1(sb+SM_SCL+8+(s&1)*4));
      float4 c1=lds4f(ra+((kq+3)&3)*4096+512), d2=lds4f(ra+((kq+2)&3)*4096+1024), e2=lds4f(ra+((kq+1)&3)*4096+1536);
      const uint32_t p0=pack_bf16(((acc[0][0]+c1.x)+(d2.x+e2.x))*cs,((acc[0][1]+c1.y)+(d2.y+e2.y))*cs), p1=pack_bf16(((acc[0][2]+c1.z)+(d2.z+e2.z))*cs,((acc[0][3]+c1.w)+(d2.w+e2.w))*cs);
      if(UEX) asm volatile("cp.async.bulk.wait_group.read 0;":::"memory");
      bar_arrive(2+UXDEP,256);
      const uint32_t v0=movm(p0), v1=movm(p1);
      const uint32_t off=SM_VMX+(kq>>1)*512+lane*16+(kq&1)*8;
      #pragma unroll
      for(int r=0;r<2;r++) st_async2(rsc[r]+off+(2-r)*1024,v0,v1,rsc[r]+SM_MB+16);
      sts2(sb+off,v0,v1); __syncwarp(); if(lane==0) mbar_arrive(XL);
      TF(5);
      if(OPF>=40){
        #pragma unroll
        for(int i=0;i<8;i++) ldsm4(buf[i],os+i*256);
      }
    } else {
      uint32_t kb[8];
      #pragma unroll
      for(int y=IL;y<10;y++){
        KST(kord(y))
        if(y==7){
          const uint32_t ka=sb+SM_KX+(8*kq+(lane&7))*128+((((lane>>3)^(2*kq))^(lane&7))<<4);
          ldsm4(kb,ka); ldsm4(kb+4,ka^64);
        }
        if(y==XGP) XGET
        if(y==5) XMAX
        if(UEX&&UBP==y+2&&warp!=3) UBULK
      }
      TF(1);
      {
        const uint32_t qa=s16+SM_RED+kq*4096+1024;
        #pragma unroll
        for(int i=0;i<2;i++) stsm4(qa+i*512,pack_bf16(acc[2*i][0],acc[2*i][1]),pack_bf16(acc[2*i][2],acc[2*i][3]),pack_bf16(acc[2*i+1][0],acc[2*i+1][1]),pack_bf16(acc[2*i+1][2],acc[2*i+1][3]));
      }
      TF(2);
      bar_sync(1,256);
      TS(1); TF(3);
      const uint32_t ra=s16+SM_KRED+kq*512;
      const float cs=__uint_as_float(lds1(sb+SM_SCL+8+(s&1)*4));
      float4 a3=lds4f(ra), c3=lds4f(ra+2048), d3=lds4f(ra+4096), e3=lds4f(ra+6144);
      uint32_t q[4][2][4];
      #pragma unroll
      for(int i=0;i<4;i++){ ldsm4t(q[i][0],qrd^(i*256)); ldsm4t(q[i][1],(qrd^(i*256))+8192); }
      const uint32_t p2=pack_bf16(((a3.x+c3.x)+(d3.x+e3.x))*cs,((a3.y+c3.y)+(d3.y+e3.y))*cs), p3=pack_bf16(((a3.z+c3.z)+(d3.z+e3.z))*cs,((a3.w+c3.w)+(d3.w+e3.w))*cs);
      const uint32_t f2=movm(p2), f3=movm(p3);
      ex0=f2; ex1=f3;
      float sc[6][4];
      #pragma unroll
      for(int i=0;i<6;i++){ sc[i][0]=sc[i][1]=sc[i][2]=sc[i][3]=0.f; }
      #pragma unroll
      for(int i=0;i<4;i++)
        #pragma unroll
        for(int jp=0;jp<2;jp++){
          mma16816(sc[(i&1)*2+jp],q[i][jp],kb[2*i],kb[2*i+1]);
          if(i==1) mma16816(sc[4+jp],q[0][jp],f2,f3);
        }
      const uint32_t w0=__float_as_uint(((sc[0][0]+sc[0][2])+(sc[1][0]+sc[1][2]))+((sc[2][0]+sc[2][2])+(sc[3][0]+sc[3][2]))), w1=__float_as_uint(((sc[0][1]+sc[0][3])+(sc[1][1]+sc[1][3]))+((sc[2][1]+sc[2][3])+(sc[3][1]+sc[3][3])));
      const uint32_t w2=__float_as_uint((sc[4][0]+sc[4][2])+(sc[5][0]+sc[5][2])), w3=__float_as_uint((sc[4][1]+sc[4][3])+(sc[5][1]+sc[5][3]));
      const uint32_t off=SM_SCX+(c*4+kq)*512+lane*16;
      #pragma unroll
      for(int r=0;r<2;r++) st_async4(rsc[r]+off,w0,w1,w2,w3,rsc[r]+SM_MB);
      sts4(sb+off,make_uint4(w0,w1,w2,w3)); __syncwarp(); if(lane==0) mbar_arrive(XS);
      if(EKM&&last){
        { char* ep=(char*)g_km+(uint32_t)((NSEG-1)*98304+h*3072+(4*c+kq)*256+((s16-sb)>>2)); stg1(ep,f2); stg1(ep+128,f3); }
        __syncwarp();
        if(lane==0){ fence_rel(); stg_rlx1(g_flag+b*32+1+kq,1); }
      }
      TS(2); TF(5);
    }
    if(!MG&&warp==3){
      bar_arrive(2,256);
      const float ssc=0.07216878364870322f*__uint_as_float(lds1(sb+SM_SCL+8+(s&1)*4));
      uint32_t kvc; asm volatile("ld.relaxed.gpu.global.u32 %0, [%1];":"=r"(kvc):"l"(g_cnt+C_KV+(((s>>2)+1)&15)):"memory");
      TF(6);
      { int gd=0; while(!mbar_try(XS,s&1)){ if(dead) break; if(++gd>GUARD){ dead=true; g_err=2; } } }
      TF(7);
      float sv[10];
      {
        float4 u[12];
        #pragma unroll
        for(int n=0;n<12;n++) u[n]=lds4f(s16+SM_SCX+n*512);
        uint32_t r[5];
        #pragma unroll
        for(int n=0;n<4;n++) r[n+1]=pack_bf16((u[n].x+u[4+n].x)+u[8+n].x,(u[n].y+u[4+n].y)+u[8+n].y);
        r[0]=pack_bf16((((u[0].z+u[1].z)+(u[2].z+u[3].z))+((u[4].z+u[5].z)+(u[6].z+u[7].z)))+((u[8].z+u[9].z)+(u[10].z+u[11].z)),
                       (((u[0].w+u[1].w)+(u[2].w+u[3].w))+((u[4].w+u[5].w)+(u[6].w+u[7].w)))+((u[8].w+u[9].w)+(u[10].w+u[11].w)));
        #pragma unroll
        for(int n=0;n<5;n++){
          const uint32_t w=pack_bf16(__uint_as_float(r[n]<<16)*ssc,__uint_as_float(r[n]&0xffff0000u)*ssc);
          sv[2*n]=__uint_as_float(w<<16); sv[2*n+1]=__uint_as_float(w&0xffff0000u);
        }
      }
      TF(8);
      float mx=fmaxf(fmaxf(fmaxf(sv[2],sv[3]),fmaxf(sv[4],sv[5])),fmaxf(fmaxf(fmaxf(sv[6],sv[7]),fmaxf(sv[8],sv[9])),fmaxf(sv[0],sv[1])));
      mx=fmaxf(mx,__shfl_xor_sync(~0u,mx,1)); mx=fmaxf(mx,__shfl_xor_sync(~0u,mx,2));
      mx*=-1.4426950408889634f;
      #pragma unroll
      for(int i=0;i<10;i++) sv[i]=ex2(fmaf(sv[i],1.4426950408889634f,mx));
      sts1(sb+SM_PM+lane*4,pack_bf16(sv[0],sv[1]));
      sts4(s16+SM_P,make_uint4(pack_bf16(sv[2],sv[3]),pack_bf16(sv[4],sv[5]),pack_bf16(sv[6],sv[7]),pack_bf16(sv[8],sv[9])));
      TF(9);
      bar_sync(4,256);
      asm volatile("mov.u32 %0, %%clock;":"=r"(t0)); t0+=W3O;
      TF(11);
      if(lane==0){
        mbar_expect(XS,4096); mbar_expect(XV,2048);
        if((s&3)==2){ int gd=0; while(kvc<64&&s<NSEG-4){ kvc=ld_acq(g_cnt+C_KV+(s>>2)+1); if(++gd>GUARD){ g_err=7; break; } } fence_acq(); fence_async_g(); }
      }
      __syncwarp();
      eo2=(uint32_t)(s*98304+h*3072+(4*c+kq)*256+((s16-sb)>>2))^zero;
      TF(13);
    } else {
      if constexpr(!MG){
        #pragma unroll
        for(int i=0;i<2;i++){ ldsm4(ux[i][0],us+i*1024); ldsm4(ux[i][1],us+i*1024+256); }
        if(s==0&&warp==2){
          int gd=0; uint32_t x[6];
          #pragma unroll 1
          while(true){
            bool ok=true;
            #pragma unroll
            for(int i=0;i<6;i++){ asm volatile("ld.relaxed.gpu.global.u32 %0, [%1];":"=r"(x[i]):"l"(g_nrm+lane*6+i):"memory"); ok=ok&&x[i]!=SENT; }
            if(__all_sync(~0u,ok)) break;
            if(++gd>GUARD){ g_err=8; break; }
          }
          const float cw=27.5f*sqrtf((__uint_as_float(x[0])+__uint_as_float(x[2]))+__uint_as_float(x[4]))*sqrtf(__uint_as_float(max(x[1],max(x[3],x[5]))));
          sts1(sb+SM_SCL+4,__reduce_max_sync(~0u,__float_as_uint(cw)&0x7fffffffu));
          __syncwarp();
        }
        {
          const uint4 x=lds4(sb+SM_MX), y=lds4(sb+SM_MX+16); const float cw=__uint_as_float(lds1(sb+SM_SCL+4)), cs=__uint_as_float(lds1(sb+SM_SCL+8+(s&1)*4));
          const float mm=__uint_as_float(max(max(max(x.x,x.y),max(x.z,x.w)),max(max(y.x,y.y),max(y.z,y.w))))*cs;
          const uint32_t eo=min(max((__float_as_uint(cw*fmaxf(mm,1.f))>>23)&255u,37u),254u)-21u;
          if(tid==64){ sts1(sb+SM_SCL,eo*0x00800080u); sts1(sb+SM_SCL+12-(s&1)*4,(eo-3u)<<23); }
        }
        TF(4);
        if(UEX) asm volatile("cp.async.bulk.wait_group.read 0;":::"memory");
        bar_sync(2+UXDEP,256);
        if(!last&&lane==0){
          tma2dh(sb+SM_VX+kq*4096,&tmV,h*DH+64*kq,(s+1)*32,KVB,HV?PL_EF:PL_EN);
          if(kq==0) mbar_expect(KVB,32*512);
          if(kq==1) tma2dh(sb+SM_KX,&tmK,h*DH+64*c,(s+1)*32,KVB,HK?PL_EF:PL_EN);
        }
        __syncwarp();
      }
      float ca[2][2][4];
      #pragma unroll
      for(int i=0;i<2;i++)
        #pragma unroll
        for(int j=0;j<2;j++){ ca[i][j][0]=ca[i][j][1]=ca[i][j][2]=ca[i][j][3]=0.f; }
      TF(6);
      { int gd=0; while(!mbar_try(XL,s&1)){ if(dead) break; if(++gd>GUARD){ dead=true; g_err=5; } } }
      TF(7);
      uint4 vm[6];
      vm[0]=lds4(s16+SM_VMX); vm[1]=lds4(s16+SM_VMX+512);
      #define VB0(x) (((x)&1)?vm[(x)>>1].z:vm[(x)>>1].x)
      #define VB1(x) (((x)&1)?vm[(x)>>1].w:vm[(x)>>1].y)
      if constexpr(MG){
        #pragma unroll
        for(int x=0;x<12;x++){
          if(x==4){
            TF(8);
            { int gd=0; while(!mbar_try(XV,s&1)){ if(dead) break; if(++gd>GUARD){ dead=true; g_err=3; } } }
            TF(9);
            #pragma unroll
            for(int i=2;i<6;i++) vm[i]=lds4(s16+SM_VMX+i*512);
          }
          #pragma unroll
          for(int i=0;i<2;i++){
            mma16816(ca[i][x&1],buf[(x*2+i)&7],VB0(x),VB1(x));
            if(x<8) ldsm4(buf[(x*2+i)&7],os+(x*2+i+8)*256);
          }
        }
      } else {
        #pragma unroll
        for(int x=0;x<12;x++){
          if(x==4){
            TF(8);
            { int gd=0; while(!mbar_try(XV,s&1)){ if(dead) break; if(++gd>GUARD){ dead=true; g_err=3; } } }
            TF(9);
            #pragma unroll
            for(int i=2;i<6;i++) vm[i]=lds4(s16+SM_VMX+i*512);
          }
          #pragma unroll
          for(int i=0;i<2;i++) mma16816(ca[i][x&1],pw[16+x*2+i],VB0(x),VB1(x));
        }
      }
      TF(10);
      bar_sync(4,256);
      TS(3); TF(11);
      const uint4 pq=lds4(s16+SM_P); const uint32_t pm=lds1(sb+SM_PM+lane*4), on=lds1(sb+SM_SCL);
      kvok=mbar_test(KVB,(s&1)^1);
      const uint32_t one[4]={on,on,on,on};
      float d[2][4], e[4];
      #pragma unroll
      for(int i=0;i<4;i++){ d[0][i]=0.f; d[1][i]=0.f; e[i]=0.f; }
      mma16816(e,one,pq.x,pq.y); mma16816(d[0],ux[0][0],pq.x,pq.y); mma16816(d[1],ux[1][0],pq.x,pq.y);
      mma16816(e,one,pq.z,pq.w); mma16816(d[0],ux[0][1],pq.z,pq.w); mma16816(d[1],ux[1][1],pq.z,pq.w);
      mma1688(e,one[0],one[0],pm);
      #pragma unroll
      for(int i=0;i<2;i++){ um[i][0]=pack_bf16(ca[i][0][0]+ca[i][1][0],ca[i][0][1]+ca[i][1][1]); um[i][1]=pack_bf16(ca[i][0][2]+ca[i][1][2],ca[i][0][3]+ca[i][1][3]); mma1688(d[i],um[i][0],um[i][1],pm); }
      const float i0=rcp(e[0]), i1=rcp(e[1]);
      TF(12);
      const uint32_t ro=(tile0+2*wt)*512+t*64+g*8;
      char* dst=(char*)g_acc+(uint32_t)((s+1)*20480+ro);
      #pragma unroll
      for(int i=0;i<2;i++){
        if(!last&&(i==0||2*wt+1<ntile)){
          red64(dst+i*512,(__float_as_uint(fmaf(d[i][0],i0,12582912.f))<<6)+1u,__float_as_uint(fmaf(d[i][2],i0,12582912.f))<<3);
          red64(dst+i*512+256,(__float_as_uint(fmaf(d[i][1],i1,12582912.f))<<6)+1u,__float_as_uint(fmaf(d[i][3],i1,12582912.f))<<3);
        }
      }
      asm volatile("mov.u32 %0, %%clock;":"=r"(t0));
      {
        const uint32_t z=t0&zero;
        eo1=(uint32_t)(s*1638400+(32+(h>>2))*40960+(tile0+2*wt)*1024+(h&3)*128+((s16-sb)>>2))^z;
        if(!MG) eo2=(uint32_t)(s*98304+h*3072+(4*c+kq)*256+((s16-sb)>>2))^z;
      }
      TW(1);
      TS(4); TF(13);
    }
    so+=20480;
  }
  if(MG||warp!=3) EXPU
  if(!MG&&!EKM) EXPK
  };
  { if(mg) loop(IC<1>{}); else loop(IC<0>{}); }
  asm volatile("cp.async.bulk.wait_group 0;":::"memory");
  __syncthreads();
  if(tid==FW*32){ fence_rel(); stg_rlx1(g_flag+b*32,NSEG); if(RTB<16) asm volatile("red.relaxed.gpu.global.add.u32 [%0], 1;"::"l"(g_cnt+C_RD):"memory"); }
  GT(2);
  asm volatile("barrier.cluster.arrive.release.aligned;":::"memory");
  if(RTB<16&&b<80){
    const uint32_t TF_=sb+SM_PM+256, TE=TF_+32;
    const int sq=b/20, part=b-20*sq;
    auto cw=[&](int c_,uint32_t thr){ int gd=0; while(ld_acq(g_cnt+c_)<thr){ __nanosleep(20); if(++gd>GUARD){ g_err=10; break; } } };
    auto bw=[&](uint32_t a,uint32_t par){ int gd=0; while(!mbar_try(a,par)){ if(++gd>GUARD){ g_err=11; break; } } };
    if(warp==4||warp==5){
      if(lane==0){
        #pragma unroll 1
        for(int n=0;n<4*(16-RTB);n++){
          const int rbk=RTB+(n>>2), seg=rbk*4+sq, sl=n&3;
          if(sl==0){ if(warp==4&&rbk==15) cw(C_RD,NCTA); else cw(C_QA+rbk,32); fence_async_all(); TT((warp-4)*2+(rbk&1)); }
          if(n>=4) bw(TE+sl*8,((n>>2)&1)^1);
          mbar_expect(TF_+sl*8,20480);
          if(warp==4) asm volatile("cp.async.bulk.tensor.3d.shared::cluster.global.mbarrier::complete_tx::bytes.L2::cache_hint [%0], [%1, {0, %3, %4}], [%2], %5;"::"r"(sb+sl*40960),"l"(&P.u),"r"(TF_+sl*8),"r"(part),"r"(seg*40+sl*10),"l"(PL_EF):"memory");
          else bulk_g2s(sb+sl*40960+20480,g_p+seg*81920+sl*20480,20480,TF_+sl*8);
        }
      }
      __syncwarp();
    } else if(warp<4){
      #pragma unroll 1
      for(int it=0;it<16-RTB;it++){
        const int rbk=RTB+it;
        const uint32_t go=(uint32_t)(((rbk*4+sq)*32+(tid>>2))*D+part*32+(tid&3)*8);
        cw(C_M2+rbk,4);
        const uint4 x=ldg_rlx4((const uint32_t*)(P.x+go)), gt=ldg_rlx4((const uint32_t*)(g_gate+go));
        float q[16], q2[16];
        #pragma unroll
        for(int i=0;i<16;i++){ q[i]=0.f; q2[i]=0.f; }
        #pragma unroll 1
        for(int sl=0;sl<4;sl++){
          bw(TF_+sl*8,it&1);
          if(tid==0&&(sl==0||sl==3)) TT(4+(rbk&1)*2+(sl&1));
          const uint32_t sa=((sb+sl*40960)>>4)&0x3fff, da=sa|(8u<<16), db=(sa+1280)|(32u<<16);
          asm volatile("wgmma.fence.sync.aligned;":::"memory");
          #pragma unroll
          for(int j=0;j<20;j++) wg32_pu((TQ2&&(j&1))?q2:q,da+(j>>1)*128+(j&1)*16,db+j*64,TQ2?sl|(j>>1):sl|j);
          asm volatile("wgmma.commit_group.sync.aligned;":::"memory");
          asm volatile("wgmma.wait_group.sync.aligned 0;":::"memory");
          if(lane==0) mbar_arrive(TE+sl*8);
        }
        if(TQ2){
          #pragma unroll
          for(int i=0;i<16;i++) q[i]+=q2[i];
        }
        const uint32_t sg=sb+SM_KRED+(it&1)*4096;
        if(warp<2){
          const uint32_t wa=sg+((lane>>4)*8+(lane&7))*128+(((2*warp+((lane>>3)&1))^(lane&7))<<4);
          #pragma unroll
          for(int i=0;i<2;i++) stsm4t(wa+i*2048,pack_bf16(q[8*i],q[8*i+1]),pack_bf16(q[8*i+2],q[8*i+3]),pack_bf16(q[8*i+4],q[8*i+5]),pack_bf16(q[8*i+6],q[8*i+7]));
        }
        bar_sync(1,128);
        const uint4 u=lds4(sg+(tid>>2)*128+(((tid&3)^((tid>>2)&7))<<4));
        *(uint4*)(P.out+go)=make_uint4(fin1(u.x,x.x,gt.x),fin1(u.y,x.y,gt.y),fin1(u.z,x.z,gt.z),fin1(u.w,x.w,gt.w));
      }
    }
  }
  GT(3);
  asm volatile("barrier.cluster.wait.acquire.aligned;":::"memory");
}
#define WMJ 1
#define WMW 1
#define KVX 500
#define NUO 0
#define KLEAD 16
#define MLEAD 16
#define FAG fence_async_g
#define KVQ 1024
#define ROT 38
#define ROT0 3
#define FNS 40
#define CONT 1
enum { M_XN=0,M_WK,M_WV,M_K,M_V,M_Y,M_H,M_H2,M_GATE,M_WQ,M_W1,M_W2,M_W2B,M_U1,M_U2,M_U5,M_U10,M_NUM,M_OUT };
struct WParams { CUtensorMap m[M_NUM]; const bf16* x; const bf16* b1; const bf16* b2; bf16* out; int pair; };
enum { T_RED=0,T_OP=1,T_QA=2,T_M2=3,T_M1=4,T_KV=5,T_END=6 };
#define KVR 5
#define KVJ 32
constexpr int KVUP=128*KVR;
#define TRIG 10
#define SOV 1
#define LATE 15
#define E15 4
#define OPE 15
#define Q15 3
#define HB 1
#define EARLY 2
constexpr int NRB=16;
constexpr int STG=45056, NST=4, SLOT=24576, BOXS=8192;
constexpr int W_SLOT=NST*STG;
constexpr int W_BAR=W_SLOT+2*SLOT;
constexpr int W_TOTAL=W_BAR+1024;
static_assert(W_TOTAL<=232448,"smem");
#define ST(i)
#define QT(i)
__device__ __forceinline__ void stsm4n(uint32_t a,uint32_t r0,uint32_t r1,uint32_t r2,uint32_t r3){ asm volatile("stmatrix.sync.aligned.m8n8.x4.shared.b16 [%0], {%1,%2,%3,%4};"::"r"(a),"r"(r0),"r"(r1),"r"(r2),"r"(r3)); }
#define WGUARD 2000000
__host__ __device__ constexpr int n_uns(){ int n=0; while(n<16&&nsp(n)==1) n++; return n; }
__host__ __device__ constexpr int n_op(){ int n=0; for(int r=0;r<NRB;r++) n+=4*nsp(r); return n; }
__host__ __device__ constexpr int n_red(){ return 0; }
__host__ __device__ constexpr int pu_st(int ns){ return ns==1?40:(ns==2?20:(ns==5?10:8)); }

__device__ __forceinline__ void wg_arrive(){ asm volatile("wgmma.fence.sync.aligned;":::"memory"); }
__device__ __forceinline__ void wg_commit(){ asm volatile("wgmma.commit_group.sync.aligned;":::"memory"); }
template<int N> __device__ __forceinline__ void wg_wait(){ asm volatile("wgmma.wait_group.sync.aligned %0;"::"n"(N):"memory"); }
__device__ __forceinline__ void mbar_wait(uint32_t a,uint32_t par){ int gd=0; while(!mbar_try(a,par)){ if(++gd>WGUARD){ g_err=20; break; } } }
__device__ __forceinline__ uint32_t ld_rlx(const uint32_t* p){ uint32_t v; asm volatile("ld.relaxed.gpu.global.u32 %0, [%1];":"=r"(v):"l"(p):"memory"); return v; }
__device__ __forceinline__ float4 ld_rlx4f(const float4* p){ float4 v; asm volatile("ld.relaxed.gpu.global.v4.f32 {%0,%1,%2,%3}, [%4];":"=f"(v.x),"=f"(v.y),"=f"(v.z),"=f"(v.w):"l"(p):"memory"); return v; }
__device__ __forceinline__ void tma_st(const CUtensorMap* tm,uint32_t src,int c0,int c1){
  asm volatile("cp.async.bulk.tensor.2d.global.shared::cta.bulk_group [%0, {%2, %3}], [%1];"::"l"(tm),"r"(src),"r"(c0),"r"(c1):"memory"); }
#define KEF 4
__device__ __forceinline__ void tma_st_ef(const CUtensorMap* tm,uint32_t src,int c0,int c1){
  asm volatile("{\n.reg .b64 pl;\ncreatepolicy.fractional.L2::evict_first.b64 pl, 1.0;\ncp.async.bulk.tensor.2d.global.shared::cta.bulk_group.L2::cache_hint [%0, {%2, %3}], [%1], pl;\n}"::"l"(tm),"r"(src),"r"(c0),"r"(c1):"memory"); }
__device__ __forceinline__ void bulk_commit(){ asm volatile("cp.async.bulk.commit_group;":::"memory"); }
__device__ __forceinline__ void bulk_wait_rd(){ asm volatile("cp.async.bulk.wait_group.read 0;":::"memory"); }
__device__ __forceinline__ void bulk_wait(){ asm volatile("cp.async.bulk.wait_group 0;":::"memory"); }
__device__ __forceinline__ void mbar_arrive_cl(uint32_t a){ asm volatile("mbarrier.arrive.shared::cluster.b64 _, [%0];"::"r"(a):"memory"); }
__device__ __forceinline__ void tma4d(uint32_t dst,const CUtensorMap* tm,int c2,int c3,uint32_t mb){
  asm volatile("cp.async.bulk.tensor.4d.shared::cluster.global.mbarrier::complete_tx::bytes [%0], [%1, {0, 0, %3, %4}], [%2];"::"r"(dst),"l"(tm),"r"(mb),"r"(c2),"r"(c3):"memory"); }
__device__ __forceinline__ void tma4dm(uint32_t dst,const CUtensorMap* tm,int c2,int c3,uint32_t mb){
  asm volatile("cp.async.bulk.tensor.4d.shared::cluster.global.mbarrier::complete_tx::bytes.multicast::cluster [%0], [%1, {0, 0, %3, %4}], [%2], %5;"::"r"(dst),"l"(tm),"r"(mb),"r"(c2),"r"(c3),"h"((uint16_t)3):"memory"); }

template<int N> __device__ __forceinline__ void mainloop(float* acc,int nkb,uint32_t sb,int lane,uint32_t pos,uint32_t eb){
  uint32_t pst=0;
  #pragma unroll
  for(int i=0;i<N/2;i++){ acc[i]=0.f; acc[96+i]=0.f; }
  #pragma unroll 1
  for(int kb=0;kb<nkb;kb++,pos++){
    const uint32_t st=pos&3;
    mbar_wait(sb+W_BAR+st*8,(pos>>2)&1);
    if(kb==nkb-1&&(threadIdx.x&127)==0) mbar_arrive(sb+W_BAR+144);
    const uint32_t a=sb+st*STG;
    const uint32_t da=((a>>4)&0x3fff)|(1u<<16);
    const uint32_t db=da+1024+(255u<<16);
    wg_arrive();
    #pragma unroll
    for(int k=0;k<4;k++){ wgmma<N>(acc,da+2*k,db+(k>>1)*N*4+(k&1)*128,kb|k); wgmma<N>(acc+96,da+512+2*k,db+(k>>1)*N*4+(k&1)*128,kb|k); }
    wg_commit();
    if(kb>0){ wg_wait<1>(); if(lane<2) mbar_arrive_cl(eb+pst*8); }
    pst=st;
  }
  wg_wait<0>();
  if(lane<2) mbar_arrive_cl(eb+pst*8);
}
__device__ __forceinline__ uint32_t act2(uint32_t u,uint32_t bb,float c1,float c3){
  uint32_t s; asm("add.rn.bf16x2 %0, %1, %2;":"=r"(s):"r"(u),"r"(bb));
  float r[2]={__uint_as_float(s<<16), __uint_as_float(s&0xffff0000u)};
  #pragma unroll
  for(int i=0;i<2;i++){
    const float z=r[i]*fmaf(r[i]*r[i],c3,c1);
    r[i]=r[i]*rcp(1.f+ex2(z));
  }
  return pack_bf16(r[0],r[1]);
}
template<int NT> __device__ __forceinline__ void stage_pk(const uint32_t* p,uint32_t ra,int lane){
  const int sw=lane&7, hi=lane>>4;
  #pragma unroll
  for(int T=0;T<NT;T++) stsm4n(ra+(T>>2)*BOXS+((((2*T+hi)&7)^sw)<<4),p[4*T],p[4*T+1],p[4*T+2],p[4*T+3]);
}
__device__ __noinline__ void post_pass(uint32_t sl,int nbox,uint32_t ba,float c1,float c3){
  const int lane=threadIdx.x&31, r=lane>>3, c=lane&7;
  __syncwarp();
  #pragma unroll 1
  for(int j=0;j<nbox;j++){
    uint4 u[4]; uint32_t a[4];
    #pragma unroll
    for(int i=0;i<4;i++){ const int rr=4*i+r; a[i]=sl+j*BOXS+rr*128+((c^(rr&7))<<4); u[i]=lds4(a[i]); }
    const uint4 bb=lds4(ba+j*128+c*16);
    #pragma unroll
    for(int i=0;i<4;i++){
      uint4& v=u[i];
      v.x=act2(v.x,bb.x,c1,c3); v.y=act2(v.y,bb.y,c1,c3); v.z=act2(v.z,bb.z,c1,c3); v.w=act2(v.w,bb.w,c1,c3);
      sts4(a[i],v);
    }
  }
}
__device__ __forceinline__ void wg16_rs(float* d,const uint32_t* a,uint32_t db,int sc){
  asm volatile("{\n.reg .pred p;\n.reg .b64 xb;\nmov.b64 xb, {%12, 192};\nsetp.ne.b32 p, %13, 0;\nwgmma.mma_async.sync.aligned.m64n16k16.f32.bf16.bf16 {%0,%1,%2,%3,%4,%5,%6,%7}, {%8,%9,%10,%11}, xb, p, 1, 1, 0;\n}"
   :"+f"(d[0]),"+f"(d[1]),"+f"(d[2]),"+f"(d[3]),"+f"(d[4]),"+f"(d[5]),"+f"(d[6]),"+f"(d[7]):"r"(a[0]),"r"(a[1]),"r"(a[2]),"r"(a[3]),"r"(db),"r"(sc));
}
template<int NS> __device__ __forceinline__ void pu_item(const WParams& P,int rbk,int a,uint32_t pos,uint32_t sb,int tid,uint32_t& e0,int& sq){
  constexpr int MT=10/NS, NKB=pu_st(NS), BPS=40/NKB, H0=(MT+1)/2;
  const int lane=tid&31, wg=tid>>7, wq=(tid>>5)&3;
  const int seg=rbk*4+a/NS, part=a%NS;
  const uint32_t go=(uint32_t)((seg*32+wq*8+(lane>>3))*D+part*MT*64+(lane&7)*8);
  uint4 xx[MT][2], gg[MT][2];
  auto ldx=[&](int m){
    #pragma unroll
    for(int j=m*H0;j<m*H0+H0&&j<MT;j++)
      #pragma unroll
      for(int i=0;i<2;i++){ const uint32_t o=go+i*4*D+j*64; xx[j][i]=ldg_rlx4((const uint32_t*)(P.x+o)); gg[j][i]=ldg_rlx4((const uint32_t*)(g_gate+o)); }
  };
  if(NS>1){ ldx(0); ldx(1); }
  float acc[MT][16];
  #pragma unroll
  for(int i=0;i<MT*16;i++) acc[i>>4][i&15]=0.f;
  uint32_t pst=0;
  #pragma unroll 1
  for(int kb=0;kb<NKB;kb++,pos++){
    const uint32_t st=pos&3;
    mbar_wait(sb+W_BAR+st*8,(pos>>2)&1);
    if(kb==NKB-1&&(tid&127)==0) mbar_arrive(sb+W_BAR+144);
    const uint32_t sa=((sb+st*STG)>>4)&0x3fff, da=sa|(8u<<16), db=(sa+BPS*MT*256)|(32u<<16);
    wg_arrive();
    #pragma unroll
    for(int j=0;j<BPS;j++)
      #pragma unroll
      for(int k=0;k<2;k++)
        #pragma unroll
        for(int m=0;m<MT;m++) wg32_pu(acc[m],da+(j*MT+m)*256+k*16,db+j*128+k*64,kb|j|k);
    wg_commit();
    if(kb>0){ wg_wait<1>(); if(lane<2) mbar_arrive(sb+W_BAR+32+pst*8); }
    pst=st;
  }
  wg_wait<0>();
  if(lane<2) mbar_arrive(sb+W_BAR+32+pst*8);
  const uint32_t wa=sb+W_SLOT+((lane>>4)*8+(lane&7))*128+(((2*wq+((lane>>3)&1))^(lane&7))<<4);
  const uint32_t rd=sb+W_SLOT+(wq*8+(lane>>3))*128+(((lane&7)^(lane>>3))<<4);
  #pragma unroll
  for(int m=0;m<2;m++){
    mbar_wait(sb+W_BAR+96+wg*16+m*8,e0);
    if(m*H0<MT){
      #pragma unroll
      for(int j=0;j<H0&&m*H0+j<MT;j++){ const float* q=acc[m*H0+j<MT?m*H0+j:0];
        #pragma unroll
        for(int i=0;i<2;i++) stsm4t(wa+m*SLOT+j*4096+i*2048,pack_bf16(q[8*i],q[8*i+1]),pack_bf16(q[8*i+2],q[8*i+3]),pack_bf16(q[8*i+4],q[8*i+5]),pack_bf16(q[8*i+6],q[8*i+7])); }
      if(NS==1) ldx(m);
      bar_sync(8+wg,128);
      #pragma unroll
      for(int j=0;j<H0&&m*H0+j<MT;j++)
        #pragma unroll
        for(int i=0;i<2;i++){
          const uint4 u=lds4((rd^(i*64))+m*SLOT+j*4096+i*512), x=xx[m*H0+j<MT?m*H0+j:0][i], g=gg[m*H0+j<MT?m*H0+j:0][i];
          *(uint4*)(P.out+go+i*4*D+(m*H0+j)*64)=make_uint4(fin1(u.x,x.x,g.x),fin1(u.y,x.y,g.y),fin1(u.z,x.z,g.z),fin1(u.w,x.w,g.w));
        }
    }
    bar_arrive(sq,160); sq^=1;
  }
  e0^=1;
}
template<int N> __device__ __forceinline__ void gemm_item(int type,uint32_t pos,uint32_t sb,int tid,uint32_t ra,uint32_t& e0,uint32_t& eb,int& sq,uint32_t em){
  const int lane=tid&31, wg=tid>>7;
  const uint32_t E0=sb+W_BAR+96+wg*16;
  float acc[192];
  mainloop<N>(acc,type==T_M2?24:10,sb,lane,pos,em);
  uint32_t p[2][N/4];
  #pragma unroll
  for(int m=0;m<2;m++)
    #pragma unroll
    for(int i=0;i<N/4;i++) p[m][i]=pack_bf16(acc[96*m+2*i],acc[96*m+2*i+1]);
  const float c1=type==T_M1?-2.302208198144325f:-1.4426950408889634f, c3=type==T_M1?-0.10294323958f:0.f;
  const int wq=(tid>>5)&3;
  if(type!=T_KV){ mbar_wait(sb+W_BAR+224+wg*8,eb); eb^=1; }
  #pragma unroll
  for(int m=0;m<2;m++){
    mbar_wait(E0+m*8,e0);
    stage_pk<N/16>(p[m],ra+m*SLOT,lane);
    if(type!=T_KV) post_pass(sb+W_SLOT+m*SLOT+wq*2048,N/64,sb+W_BAR+256+wg*384,c1,c3);
    fence_async();
    bar_arrive(sq,160); sq^=1;
  }
  e0^=1;
}
__device__ __forceinline__ int n_it(int c,int r){ return c==T_OP?4*nsp(r):(c==T_QA?32:(c==T_M2?4:(r?0:(c==T_M1?128:(c==T_KV?(1024-KVUP)/2:0))))); }
__device__ __forceinline__ void flag_wait(int rbk,int a,int lane){
  const bool e=EKM&&rbk==NRB-1;
  const uint32_t need=e?1:4*rbk+4; const uint32_t* f=g_flag+a*96+(lane%3)*32+(e?1+lane/3:0); int gd=0;
  while(!__all_sync(~0u,lane>=(e?12:3)||ld_acq(f)>=need)){ __nanosleep(FNS); if(++gd>WGUARD){ g_err=22; break; } }
}
__device__ __forceinline__ void cnt_wait(int c,uint32_t thr){
  int gd=0;
  while(ld_acq(g_cnt+c)<thr){ __nanosleep(40); if(++gd>WGUARD){ g_err=23; break; } }
}
__global__ void __launch_bounds__(384,1) k_work(const __grid_constant__ WParams P){
  extern __shared__ __align__(1024) uint8_t sm[];
  const uint32_t sb=(uint32_t)__cvta_generic_to_shared(sm);
  const int tid=threadIdx.x, warp=__shfl_sync(~0u,tid>>5,0), lane=tid&31;
  const uint32_t FULL=sb+W_BAR, EMPTY=sb+W_BAR+32, IFULL=sb+W_BAR+64, IEMPTY=sb+W_BAR+80, EF=sb+W_BAR+96, REQ=sb+W_BAR+128, TOK=sb+W_BAR+136;
  volatile int* idesc=(volatile int*)(sm+W_BAR+160);
  if(tid==352) ST(0);
  if(tid==0){
    for(int i=0;i<NST;i++){ mbar_init(FULL+i*8,1); mbar_init(EMPTY+i*8,8); mbar_init(EF+i*8,1); }
    for(int i=0;i<2;i++){ mbar_init(IFULL+i*8,1); mbar_init(IEMPTY+i*8,6); mbar_init(sb+W_BAR+224+i*8,1); }
    mbar_init(REQ,1); mbar_init(TOK,1); mbar_init(sb+W_BAR+144,1);
    { mbar_init(sb+W_BAR+240,1); mbar_init(sb+W_BAR+248,1); uint32_t sm_; asm volatile("mov.u32 %0, %%smid;":"=r"(sm_)); idesc[6]=sm_; }
    asm volatile("fence.mbarrier_init.release.cluster;":::"memory");
  }
  {
    bool done=false;
    if(!P.pair&&tid==32) done=(int)ld_rlx(g_cnt+C_NEXT+T_OP*32+RTB-1)>=n_it(T_OP,RTB-1)&&(int)ld_rlx(g_cnt+C_NEXT+T_QA*32+NRB-1)>=n_it(T_QA,NRB-1)&&(int)ld_rlx(g_cnt+C_NEXT+T_M2*32+NRB-1)>=n_it(T_M2,NRB-1);
    if(__syncthreads_or(done)) return;
  }
  #define S0(i)
  S0(0)
  if(P.pair) cluster_sync();
  S0(1)
  S0(2)
  if(warp>=8){
    asm volatile("setmaxnreg.dec.sync.aligned.u32 40;");
    if(warp==11){
      uint32_t it=0, pos=0;
      auto publish=[&](int type,int rbk,int a,int erl){
        if(lane==0){
          const uint32_t sl=it&1;
          int idx=0;
          if(type==T_KV){
            if(WMJ&&a>=KVUP){ const int j=(a-KVUP)>>1, q=j/(8-KVR); rbk=2*(KVR+j-q*(8-KVR))+(a&1); a=q; }
            else if(a<128*WMW){ const int j=a>>1, q=j/WMW; rbk=2*(j-q*WMW)+(a&1); a=q; }
            else { rbk=2*(a>>7)+(a&1); a=(a>>1)&63; }
          }
          if(type==T_M1){ rbk=a>>3; a&=7; }
          mbar_wait(IEMPTY+sl*8,((it>>1)&1)^1);
          idesc[sl*8]=type; idesc[sl*8+1]=rbk; idesc[sl*8+2]=a; idesc[sl*8+3]=pos; idesc[sl*8+4]=idx; idesc[sl*8+5]=erl;
          mbar_arrive(IFULL+sl*8);
          pos+=type==T_M2?24:(type==T_OP?pu_st(nsp(rbk)):10);
        }
        __syncwarp();
        it++;
      };
      bool fin=false, rq=false;
      if(P.pair){
        const uint32_t i0=blockIdx.x<128?KVR:0;
        int quota=0, tk;
        while(true){
          if(it) mbar_wait(REQ,(it&1)^1);
          if(it<i0) tk=it*128+((blockIdx.x+(it>=ROT0?(it-ROT0+1)*ROT:0))&127);
          else {
            const uint32_t mb=sb+W_BAR+240+(it&1)*8;
            tk=4096;
            if(blockIdx.x&1){
              int gd=0; while(!mbar_try_cl(mb,((it-i0)>>1)&1)){ if(++gd>WGUARD){ g_err=24; break; } }
              tk=idesc[(it&1)*8+7];
            } else {
              if(it==i0){
                asm volatile("griddepcontrol.wait;":::"memory");
                uint32_t o; asm volatile("ld.shared::cluster.u32 %0, [%1];":"=r"(o):"r"(mapa(sb+W_BAR+160+24,1)):"memory");
                const uint32_t m=idesc[6]; uint32_t q=KVQ+KVR-i0;
                #pragma unroll
                for(int i=0;i<3;i++){ const uint32_t v=ld_rlx(g_sml+lane+32*i); if(v==m||v==o) q=min(q,KVR-i0+(lane+32*i<3*KVJ?0:1)); }
                quota=__reduce_min_sync(~0u,q);
              }
              if(lane==0){
                const bool go=CONT&&quota>512&&ld_rlx(g_flag)>1;
                if(go&&quota<=1024-KVX) tk=4097;
                else if(quota--){ tk=(int)atomicAdd(g_cnt+C_NEXT+T_KV*32,1u); if(tk>=n_it(T_KV,0)) tk=go?4097:4096; }
                asm volatile("st.shared::cluster.u32 [%0], %1;\nmbarrier.arrive.release.cluster.shared::cluster.b64 _, [%2];"::"r"(mapa(sb+W_BAR+160+(it&1)*32+28,1)),"r"(tk),"r"(mapa(mb,1)):"memory");
              }
              tk=__shfl_sync(~0u,tk,0);
            }
            if(tk>=4096) break;
            tk=KVUP+2*tk+(blockIdx.x&1);
          }
          publish(T_KV,0,tk,2);
        }
        if(tk==4096){ publish(T_END,0,0,0); fin=true; }
      }
      int guard=0;
      const int cl=lane>>2, cj=lane&3;
      int sidx=-1, nit=0;
      if(lane==0) ST(1);
      while(true){
        int type=T_END, rbk=0, a=0, erl=0;
        if(!fin){
          if(rq) mbar_wait(REQ,(it&1)^1);
          rq=true;
          if(sidx>=0){ type=T_KV; a=sidx; sidx=-1; }
          else {
            while(true){
              const uint4 nx=ldg_rlx4(g_cnt+C_NEXT+cl*32+cj*4);
              int cand=(int)nx.x<n_it(cl,4*cj)?4*cj*4096+nx.x:((int)nx.y<n_it(cl,4*cj+1)?(4*cj+1)*4096+nx.y:((int)nx.z<n_it(cl,4*cj+2)?(4*cj+2)*4096+nx.z:((int)nx.w<n_it(cl,4*cj+3)?(4*cj+3)*4096+nx.w:65536)));
              cand=min(cand,__shfl_xor_sync(~0u,cand,1)); cand=min(cand,__shfl_xor_sync(~0u,cand,2));
              const int cr=cand>>12, ca=cand&4095, qr=__shfl_sync(~0u,cr,4*T_QA);
              const bool has=cr<NRB;
              if(lane==0&&nit==0) ST(5);
              const uint32_t* fp=nullptr; uint32_t thr=0, sl1=0; bool only1=false, no1=cl>=T_M2;
              if(has&&cl<=T_M2){
                if(cl==T_QA){ if(cj<3){ fp=g_flag+ca*96+cj*32; thr=4*cr+4; sl1=cr==NRB-1?E15:EARLY; } else { fp=g_cnt+C_KV+min(cr+1,NRB-1); thr=64; only1=true; } }
                else if(cj==0){ fp=g_cnt+(cl==T_OP?C_QA:C_M1)+cr; thr=cl==T_OP?32:8; sl1=thr; }
                else if(cj==1){ if(cl==T_OP){ fp=g_cnt+C_M2+cr; thr=4; } if(cr<OPE||qr<=cr) no1=true; }
              }
              __syncwarp();
              if(lane==0&&nit==0) ST(2);
              uint32_t v=0; if(fp) v=ld_acq(fp);
              __syncwarp();
              if(lane==0&&nit==0) ST(3+(v&0));
              nit++;
              uint32_t b2=__ballot_sync(~0u,has&&(v>=thr||only1)), b1=__ballot_sync(~0u,has&&!no1&&v+sl1>=thr);
              b2&=b2>>1; b2&=b2>>2; b1&=b1>>1; b1&=b1>>2;
              b2&=0x111111u; b1&=0x111u;
              if(!__ballot_sync(~0u,has)) break;
              if(b2|b1){
                const int rs=(int)__shfl_sync(~0u,v,4*T_QA);
                const uint32_t bu=__ballot_sync(~0u,cl<=T_QA||qr>=NRB||(cl==T_KV?2*((2*ca+KVUP)>>7)<=(rs>>2)+KLEAD:(cl==T_M1?ca>>3:cr)<=qr+MLEAD));
                int got=-1;
                while(got<0&&(b2|b1)){
                  uint32_t bb=(b2&bu)?(b2&bu):(b1?b1:b2);
                  if(Q15&&(((b1|b2)>>(4*T_QA))&1)&&qr>=NRB-Q15) bb=1u<<(4*T_QA);
                  if(NUO&&!((bu>>(4*T_KV))&1)&&(bb&0x0fffffu)) bb&=0x0fffffu;
                  if(NUO>1&&(bb&0x0fffu)&&!(NUO>2&&((bb>>(4*T_KV))&1))) bb&=0x0fffu;
                  #define RD(c) ((bb>>(4*(c)))&1)
                  const int w=RD(T_KV)?T_KV:(RD(T_M2)?T_M2:(RD(T_M1)?T_M1:(RD(T_OP)?T_OP:T_QA)));
                  if(lane==4*w){ const int tk=(int)atomicAdd(g_cnt+C_NEXT+cl*32+cr,1u); if(tk<n_it(cl,cr)) got=cr*4096+(cl==T_KV?KVUP+2*tk:tk)+(tk!=ca?65536:0); }
                  got=__shfl_sync(~0u,got,4*w);
                  if(got>=0){ type=w; rbk=(got>>12)&15; a=got&4095; if(w==T_KV) sidx=a+1; erl=!((b2>>(4*w))&1)||(w==T_QA&&got>=65536); }
                  b2&=~(1u<<(4*w)); b1&=~(1u<<(4*w));
                }
                if(got>=0) break;
              } else {
                __nanosleep(100);
                if(++guard>WGUARD){ g_err=21; break; }
              }
            }
          }
        }
        __syncwarp();
        publish(type,rbk,a,erl);
        if(type==T_END){ if(fin) break; fin=true; }
      }
    } else if(warp==8){
      if(lane==0){
        uint32_t st=0, ph=1;
        for(uint32_t it=0;;it++){
          const uint32_t sl=it&1;
          mbar_wait(IFULL+sl*8,(it>>1)&1);
          const int type=idesc[sl*8], rbk=idesc[sl*8+1], a=idesc[sl*8+2], erl=idesc[sl*8+5];
          mbar_arrive(IEMPTY+sl*8);
          if(type==T_END) break;
          if(type==T_OP){
            const int ns=nsp(rbk), nkb=pu_st(ns), bps=40/nkb, ub=40960/ns, seg=rbk*4+a/ns, trig=rbk>=LATE?nkb-1:max(nkb-TRIG,0);
            const uint8_t* pp=g_p+seg*81920; const CUtensorMap* um=&P.m[ns==1?M_U1:(ns==2?M_U2:(ns==5?M_U5:M_U10))]; const int c1=(a%ns)*(20/ns);
            if(erl) cnt_wait(C_QA+rbk,32);
            FAG();
            for(int kb=0;kb<nkb;kb++){
              mbar_wait(EMPTY+st*8,ph);
              const uint32_t d=sb+st*STG, fb=FULL+st*8;
              mbar_expect(fb,bps*(ub+2048));
              asm volatile("cp.async.bulk.tensor.3d.shared::cluster.global.mbarrier::complete_tx::bytes.L2::cache_hint [%0], [%1, {0, %3, %4}], [%2], %5;"::"r"(d),"l"(um),"r"(fb),"r"(c1),"r"(seg*40+kb*bps),"l"(PL_EF):"memory");
              bulk_g2s(d+bps*ub,pp,bps*2048,fb); pp+=bps*2048;
              if(kb==trig) mbar_arrive(REQ);
              if(++st==NST){ st=0; ph^=1; }
            }
            continue;
          }
          int ma=M_XN,mb,cg=a*3,nkb=10,nbox=3; const int row0=rbk*128;
          if(type==T_KV){ mb=a<32?M_WK:M_WV; cg=(a&31)*3; }
          else if(type==T_M1){ ma=M_Y; mb=M_W1; }
          else if(type==T_QA){ mb=M_WQ; }
          else {
            const int nt=a&3; cg=nt<2?nt*3:2+nt*2; nbox=nt<2?3:2;
            ma=M_H2; mb=nt<2?M_W2:M_W2B; nkb=24;
          }
          if(erl!=2) FAG();
          const CUtensorMap* A=&P.m[ma]; const CUtensorMap* B=&P.m[mb];
          const int trig=(type<=T_QA&&rbk>=LATE)?nkb-1:max(nkb-TRIG,0), r=rbk&1, f0=(erl==2&&it==0)?NST:0;
          for(int kb=0;kb<nkb;kb++){
            mbar_wait(EMPTY+st*8,ph);
            const uint32_t d=sb+st*STG, fb=FULL+st*8;
            mbar_expect(fb,16384+nbox*8192);
            if(kb>=f0) tma2d(d,A,kb*64,row0,fb);
            if(erl==2) tma4dm(d+16384+r*12288,B,cg,2*kb+r,fb);
            else { tma4d(d+16384,B,cg,2*kb,fb); if(type==T_KV) tma4d(d+28672,B,cg,2*kb+1,fb); }
            if(kb==trig) mbar_arrive(REQ);
            if(kb==f0-1){
              asm volatile("griddepcontrol.wait;":::"memory"); asm volatile("griddepcontrol.launch_dependents;");
              for(int i=0;i<NST;i++) tma2d(sb+i*STG,A,i*64,row0,FULL+i*8);
            }
            if(++st==NST){ st=0; ph^=1; }
          }
        }
      }
      __syncwarp();
    } else if(warp<11){
      const int wg=warp-9;
      const uint32_t S0=sb+W_SLOT, E0=EF+wg*16; int sq=4+2*wg;
      for(uint32_t it=wg;;it+=2){
        mbar_wait(IFULL+wg*8,(it>>1)&1);
        const int type=idesc[wg*8], rbk=idesc[wg*8+1], a=idesc[wg*8+2], erl=idesc[wg*8+5];
        __syncwarp();
        if(lane==0) mbar_arrive(IEMPTY+wg*8);
        if(type==T_END) break;
        const int row0=rbk*128;
        int map=-1,col0=a*192,nbox=3,cnt=-1;
        if(type==T_KV){ map=a<32?M_K:M_V; col0=(a&31)*192; cnt=C_KV+rbk; }
        else if(type==T_M1){ map=M_H; cnt=C_M1+rbk; }
        else if(type==T_M2){ const int nt=a&3; col0=nt<2?nt*192:128+nt*128; nbox=nt<2?3:2; map=M_GATE; cnt=C_M2+rbk; }
        else if(type==T_OP) map=M_OUT;
        if((type==T_M1||type==T_M2)&&lane==0){ const uint32_t bb=sb+W_BAR+224+wg*8; mbar_expect(bb,nbox*128); bulk_g2s(sb+W_BAR+256+wg*384,(type==T_M1?P.b1:P.b2)+col0,nbox*128,bb); }
        const char* kp=(const char*)g_km+(uint32_t)(rbk*393216+a*3072);
        if(it&&lane==0) mbar_wait(TOK,(it&1)^1);
        if(map<0){
          if(lane==0){
            FAG();
            for(int m=0;m<2;m++){
              mbar_expect(E0+m*8,SLOT);
              for(int j=0;j<3;j++) tma2dh(S0+m*SLOT+j*BOXS,&P.m[M_K],col0+j*64,row0+m*64,E0+m*8,PL_EF);
            }
            mbar_expect(sb+W_BAR+224+wg*8,12288);
          }
          if(erl){ __syncwarp(); flag_wait(rbk,a,lane); FAG(); }
          { __syncwarp(); bar_sync(sq,160); sq^=1; }
          if(lane==0){ for(int j=0;j<4;j++) bulk_g2s(S0+j*3072,kp+j*98304,3072,sb+W_BAR+224+wg*8); }
          { __syncwarp(); bar_sync(sq,160); sq^=1; }
          if(lane==0) mbar_arrive(TOK);
          { __syncwarp(); bar_sync(sq,160); sq^=1; } if(lane==0) red_rel(g_cnt+C_QA+rbk);
        } else if(map==M_OUT){
          if(lane==0){ mbar_arrive(E0); mbar_arrive(E0+8); }
          { __syncwarp(); bar_sync(sq,160); sq^=1; }
          { __syncwarp(); bar_sync(sq,160); sq^=1; }
          if(lane==0) mbar_arrive(TOK);
        } else {
          if(lane==0){ mbar_arrive(E0); mbar_arrive(E0+8); }
          for(int m=0;m<2;m++){
            { __syncwarp(); bar_sync(sq,160); sq^=1; }
            if(lane==0){
              if(type==T_KV&&rbk>=KEF){ for(int j=0;j<nbox;j++) tma_st_ef(&P.m[map],S0+m*SLOT+j*BOXS,col0+j*64,row0+m*64); }
              else for(int j=0;j<nbox;j++) tma_st(&P.m[map],S0+m*SLOT+j*BOXS,col0+j*64,row0+m*64);
              bulk_commit();
            }
          }
          if(lane==0){
            bulk_wait_rd(); mbar_arrive(TOK);
            bulk_wait(); FAG(); red_rel(g_cnt+cnt);
          }
        }
        __syncwarp();
      }
      if(lane==0) bulk_wait();
    }
  } else {
    asm volatile("setmaxnreg.inc.sync.aligned.u32 232;");
    const int wg=warp>>2, wq=warp&3, g=lane>>2, t=lane&3;
    const uint32_t E0=EF+wg*16;
    const uint32_t ra=sb+W_SLOT+(16*wq+(lane&7)+((lane>>3)&1)*8)*128;
    uint32_t e0=0, eb=0; int sq=4+2*wg;
    const uint32_t rank=blockIdx.x&P.pair;
    #pragma unroll 1
    for(uint32_t it=0;;it++){
      mbar_wait(IFULL+wg*8,it&1);
      const int type=idesc[wg*8], rbk=idesc[wg*8+1], a=idesc[wg*8+2]; const uint32_t pos=idesc[wg*8+3], em=mapa(EMPTY,idesc[wg*8+5]==2?lane&1:rank);
      __syncwarp();
      if(lane==0) mbar_arrive(IEMPTY+wg*8);
      if(type==T_END) break;
      mbar_wait(sb+W_BAR+144,wg^1);
      if(type==T_OP){
        const int ns=nsp(rbk);
        if(ns_used(1)&&ns==1) pu_item<1>(P,rbk,a,pos,sb,tid,e0,sq);
        if(ns_used(2)&&ns==2) pu_item<2>(P,rbk,a,pos,sb,tid,e0,sq);
        if(ns_used(5)&&ns==5) pu_item<5>(P,rbk,a,pos,sb,tid,e0,sq);
        if(ns_used(10)&&ns==10) pu_item<10>(P,rbk,a,pos,sb,tid,e0,sq);
      } else {
        if(type!=T_QA){
          if(type>=T_M1||(a&3)<2) gemm_item<192>(type,pos,sb,tid,ra,e0,eb,sq,em); else gemm_item<128>(type,pos,sb,tid,ra,e0,eb,sq,em);
        } else {
          float acc[192];
          QT(0);
          mainloop<192>(acc,10,sb,lane,pos,em);
          QT(1);
          const int sgl=wq>>1, rh=wq&1;
          {
            uint32_t q[96];
            float s[2][16], sm[2][8];
            #pragma unroll
            for(int i=95;i>=0;i--) q[i]=pack_bf16(acc[2*i],acc[2*i+1]);
            QT(2);
            #pragma unroll
            for(int m=0;m<2;m++){
              const uint32_t dk=(((sb+W_SLOT+m*SLOT)>>4)&0x3fff)|(1u<<16);
              float u[32];
              mbar_wait(E0+m*8,e0);
              #pragma unroll
              for(int i=0;i<32;i++) u[i]=0.f;
              wg_arrive();
              #pragma unroll
              for(int T=0;T<12;T++) wgmma_rs<64>(u,q+48*m+4*T,dk+(T>>2)*(BOXS/16)+(T&3)*2,T);
              wg_commit();
              wg_wait<0>();
              if(m==0){ bar_arrive(sq,160); sq^=1; }
              #pragma unroll
              for(int i=0;i<16;i++) s[m][i]=sgl?u[16+i]:u[i];
            }
            QT(3);
            mbar_wait(sb+W_BAR+224+wg*8,eb); eb^=1;
            #pragma unroll
            for(int i=0;i<16;i++) sm[i>>3][i&7]=0.f;
            wg_arrive();
            #pragma unroll
            for(int T=0;T<12;T++)
              #pragma unroll
              for(int m=0;m<2;m++) wg16_rs(sm[m],q+48*m+4*T,((((sb+W_SLOT)>>4)&0x3fff)|(8u<<16))+m*384+T*16,T);
            wg_commit();
            wg_wait<0>();
            bar_arrive(sq,160); sq^=1;
            QT(4);
            const float NEG=rb(-1e9f);
            #pragma unroll
            for(int m=0;m<2;m++){
              float sc[5][4];
              float mx[2]={-3.4e38f,-3.4e38f};
              #pragma unroll
              for(int n=0;n<5;n++)
                #pragma unroll
                for(int i=0;i<4;i+=2){
                  const float u0=n?s[m][n?4*n-4+i:0]:(sgl?sm[m][4+i]:sm[m][i]);
                  const float u1=n?s[m][n?4*n-3+i:0]:(sgl?sm[m][5+i]:sm[m][i+1]);
                  const uint32_t r=pack_bf16(u0,u1);
                  const uint32_t w=pack_bf16(__uint_as_float(r<<16)*0.07216878364870322f,__uint_as_float(r&0xffff0000u)*0.07216878364870322f);
                  float v0=__uint_as_float(w<<16), v1=__uint_as_float(w&0xffff0000u);
                  if(n>0){ const int key=8*(n-1)+2*t, row=16*rh+g+4*i; if(key>row) v0=NEG; if(key+1>row) v1=NEG; }
                  sc[n][i]=v0; sc[n][i+1]=v1; mx[i>>1]=fmaxf(mx[i>>1],fmaxf(v0,v1));
                }
              float sum[2]={0.f,0.f};
              #pragma unroll
              for(int r=0;r<2;r++){ mx[r]=fmaxf(mx[r],__shfl_xor_sync(~0u,mx[r],1)); mx[r]=fmaxf(mx[r],__shfl_xor_sync(~0u,mx[r],2)); }
              #pragma unroll
              for(int n=0;n<5;n++)
                #pragma unroll
                for(int i=0;i<4;i++){ const float e=ex2((sc[n][i]-mx[i>>1])*1.4426950408889634f); sc[n][i]=e; sum[i>>1]+=e; }
              #pragma unroll
              for(int r=0;r<2;r++){ sum[r]+=__shfl_xor_sync(~0u,sum[r],1); sum[r]+=__shfl_xor_sync(~0u,sum[r],2); sum[r]=rcp(sum[r]); }
              uint8_t* pd=g_p+(uint32_t)((rbk*4+m*2+sgl)*81920+rh*256+lane*4);
              #pragma unroll
              for(int n=0;n<5;n++){
                uint8_t* q=pd+(n?a*2048+(n-1)*512:(32+(a>>2))*2048+(a&3)*512);
                stg1(q,pack_bf16(sc[n][0]*sum[0],sc[n][1]*sum[0])); stg1(q+128,pack_bf16(sc[n][2]*sum[1],sc[n][3]*sum[1]));
              }
            }
          }
          QT(5);
          bar_arrive(sq,160); sq^=1;
          e0^=1;
        }
      }
    }
  }
  if(P.pair) cluster_sync();
}
typedef CUresult (*EncFn)(CUtensorMap*,CUtensorMapDataType,cuuint32_t,void*,const cuuint64_t*,const cuuint64_t*,const cuuint32_t*,const cuuint32_t*,CUtensorMapInterleave,CUtensorMapSwizzle,CUtensorMapL2promotion,CUtensorMapFloatOOBfill);
static EncFn enc(){
  static EncFn fn=nullptr;
  if(!fn){ void* p=nullptr; cudaDriverEntryPointQueryResult qr; cudaGetDriverEntryPoint("cuTensorMapEncodeTiled",&p,cudaEnableDefault,&qr); fn=(EncFn)p; }
  return fn;
}
static CUtensorMap mku(const void* base,uint32_t b1,uint32_t b2){
  CUtensorMap m; cuuint64_t gd[3]={256,20,NSEG*40}; cuuint64_t gs[2]={2048,40960}; cuuint32_t bd[3]={256,b1,b2}; cuuint32_t es[3]={1,1,1};
  enc()(&m,CU_TENSOR_MAP_DATA_TYPE_FLOAT64,3,(void*)base,gd,gs,bd,es,CU_TENSOR_MAP_INTERLEAVE_NONE,CU_TENSOR_MAP_SWIZZLE_NONE,CU_TENSOR_MAP_L2_PROMOTION_L2_128B,CU_TENSOR_MAP_FLOAT_OOB_FILL_NONE);
  return m;
}
static CUtensorMap mk2d(const void* base,uint64_t cols,uint64_t rows,uint32_t bc,uint32_t br){
  EncFn fn=enc();
  CUtensorMap m; cuuint64_t gd[2]={cols,rows}; cuuint64_t gs[1]={cols*2}; cuuint32_t bd[2]={bc,br}; cuuint32_t es[2]={1,1};
  fn(&m,CU_TENSOR_MAP_DATA_TYPE_BFLOAT16,2,(void*)base,gd,gs,bd,es,CU_TENSOR_MAP_INTERLEAVE_NONE,bc==32?CU_TENSOR_MAP_SWIZZLE_64B:CU_TENSOR_MAP_SWIZZLE_128B,CU_TENSOR_MAP_L2_PROMOTION_L2_128B,CU_TENSOR_MAP_FLOAT_OOB_FILL_NONE);
  return m;
}
static CUtensorMap mkw(const void* base){
  CUtensorMap m; cuuint64_t gd[3]={HD,D/2,2}; cuuint64_t gs[2]={HD*4,HD*2}; cuuint32_t bd[3]={64,8,2}; cuuint32_t es[3]={1,1,1};
  enc()(&m,CU_TENSOR_MAP_DATA_TYPE_BFLOAT16,3,(void*)base,gd,gs,bd,es,CU_TENSOR_MAP_INTERLEAVE_NONE,CU_TENSOR_MAP_SWIZZLE_128B,CU_TENSOR_MAP_L2_PROMOTION_L2_128B,CU_TENSOR_MAP_FLOAT_OOB_FILL_NONE);
  return m;
}
static CUtensorMap mk4(const void* base,uint64_t cols,uint64_t rows,uint32_t ng,uint32_t nh){
  CUtensorMap m; cuuint64_t gd[4]={64,32,cols/64,rows/32}; cuuint64_t gs[3]={cols*2,128,cols*64}; cuuint32_t bd[4]={64,32,ng,nh}; cuuint32_t es[4]={1,1,1,1};
  enc()(&m,CU_TENSOR_MAP_DATA_TYPE_BFLOAT16,4,(void*)base,gd,gs,bd,es,CU_TENSOR_MAP_INTERLEAVE_NONE,CU_TENSOR_MAP_SWIZZLE_128B,CU_TENSOR_MAP_L2_PROMOTION_L2_128B,CU_TENSOR_MAP_FLOAT_OOB_FILL_NONE);
  return m;
}
template<class T> static T* sym(T& s){ void* p; cudaGetSymbolAddress(&p,s); return (T*)p; }
}

#define G2 12
#define XPQ Wq
#define XPO Wo
int g_reconly=0; int g_kvgrid=132;
extern "C" void kernel_launch(void* const* d_in, const int* in_sizes, int n_in, void* d_out, int out_size) {
  using namespace rk;
  const bf16* x=(const bf16*)d_in[0]; const bf16* mem0=(const bf16*)d_in[1];
  const bf16* Wq=(const bf16*)d_in[2]; const bf16* Wk=(const bf16*)d_in[3]; const bf16* Wv=(const bf16*)d_in[4]; const bf16* Wo=(const bf16*)d_in[5];
  const bf16* w1=(const bf16*)d_in[8]; const bf16* b1=(const bf16*)d_in[9]; const bf16* w2=(const bf16*)d_in[10]; const bf16* b2=(const bf16*)d_in[11];
  cudaStream_t st=cudaStreamPerThread;
  cudaFuncSetAttribute(k_rec,cudaFuncAttributeMaxDynamicSharedMemorySize,SM_TOTAL);
  cudaFuncSetAttribute(k_work,cudaFuncAttributeMaxDynamicSharedMemorySize,W_TOTAL);
  bf16* k=(bf16*)sym(g_k); bf16* v=(bf16*)sym(g_v);
  WParams P;
  P.m[M_XN]=mk2d(sym(g_xn),D,S,64,128); P.m[M_Y]=mk2d(sym(g_y),D,S,64,128); P.m[M_H]=mk2d(sym(g_h),F,S,64,64); P.m[M_H2]=mk2d(sym(g_h),F,S,64,128);
  P.m[M_K]=mk2d(k,HD,S,64,64); P.m[M_V]=mk2d(v,HD,S,64,64); P.m[M_GATE]=mk2d(sym(g_gate),D,S,64,64);
  P.m[M_WQ]=mk4(Wq,HD,D,3,2); P.m[M_WK]=mk4(Wk,HD,D,3,1); P.m[M_WV]=mk4(Wv,HD,D,3,1);
  P.m[M_W1]=mk4(w1,F,D,3,2); P.m[M_W2]=mk4(w2,D,F,3,2); P.m[M_W2B]=mk4(w2,D,F,2,2);
  P.m[M_U1]=mku(sym(g_u),20,1); P.m[M_U2]=mku(sym(g_u),10,2); P.m[M_U5]=mku(sym(g_u),4,4); P.m[M_U10]=mku(sym(g_u),2,5);
  P.x=x; P.b1=b1; P.b2=b2; P.out=(bf16*)d_out; P.pair=1;
  cudaFuncSetAttribute(k_pre,cudaFuncAttributeMaxDynamicSharedMemorySize,SM_TOTAL);
  {
    cudaLaunchConfig_t cfg={}; cfg.gridDim=dim3(NCTA); cfg.blockDim=dim3(PRE_T); cfg.dynamicSmemBytes=SM_TOTAL; cfg.stream=st;
    cudaLaunchAttribute at[1]; at[0].id=cudaLaunchAttributeClusterDimension; at[0].val.clusterDim.x=3; at[0].val.clusterDim.y=1; at[0].val.clusterDim.z=1; cfg.attrs=at; cfg.numAttrs=1;
    cudaLaunchKernelEx(&cfg,k_pre,x,mem0,(const char*)Wk,(const char*)Wv);
  }
  if(!(g_reconly&1)){
    cudaLaunchConfig_t cfg={}; cfg.gridDim=dim3(g_kvgrid); cfg.blockDim=dim3(384); cfg.dynamicSmemBytes=W_TOTAL; cfg.stream=st;
    cudaLaunchAttribute at[2]; at[0].id=cudaLaunchAttributeClusterDimension; at[0].val.clusterDim.x=2; at[0].val.clusterDim.y=1; at[0].val.clusterDim.z=1;
    at[1].id=cudaLaunchAttributeProgrammaticStreamSerialization; at[1].val.programmaticStreamSerializationAllowed=1; cfg.attrs=at; cfg.numAttrs=2;
    cudaLaunchKernelEx(&cfg,k_work,P);
  }
  if(!(g_reconly&4)){
    cudaLaunchConfig_t cfg={}; cfg.gridDim=dim3(NCTA); cfg.blockDim=dim3(256); cfg.dynamicSmemBytes=SM_TOTAL; cfg.stream=st;
    cudaLaunchAttribute at[2]; at[0].id=cudaLaunchAttributeClusterDimension; at[0].val.clusterDim.x=3; at[0].val.clusterDim.y=1; at[0].val.clusterDim.z=1;
    at[1].id=cudaLaunchAttributeProgrammaticStreamSerialization; at[1].val.programmaticStreamSerializationAllowed=1; cfg.attrs=at; cfg.numAttrs=2;
    RParams R; R.k=mk2d(k,HD,S,64,32); R.v=mk2d(v,HD,S,64,32); R.w[0]=mkw(XPQ); R.w[1]=mkw(Wk); R.w[2]=mkw(Wv); R.w[3]=mk2d(XPO,D,HD,32,32); R.u=mku(sym(g_u),1,10); R.x=x; R.out=(bf16*)d_out; R.wq=(const char*)XPQ; R.wo=(const char*)XPO;
    cudaLaunchKernelEx(&cfg,k_rec,R,0u);
  }
  if(!(g_reconly&2)){
    cudaLaunchConfig_t cfg={}; cfg.gridDim=dim3(G2); cfg.blockDim=dim3(384); cfg.dynamicSmemBytes=W_TOTAL; cfg.stream=st; P.pair=0;
    cudaLaunchAttribute at[1]; at[0].id=cudaLaunchAttributeProgrammaticStreamSerialization; at[0].val.programmaticStreamSerializationAllowed=1; cfg.attrs=at; cfg.numAttrs=PDL;
    cudaLaunchKernelEx(&cfg,k_work,P);
  }
}
```

```cpp
#include <cuda_runtime.h>
#include <cuda_bf16.h>
#include <stdint.h>
#include <cuda.h>

namespace rk {
typedef __nv_bfloat16 bf16;
constexpr int S=2048, D=640, H=32, DH=192, HD=6144, NSEG=64, F=1536;
constexpr uint32_t SENT=0xFFFFFFFFu;
#define GUARDN 400000
constexpr int GUARD=GUARDN;
constexpr int NCTA=96;

__device__ __align__(128) bf16 g_xn[S*D];
__device__ __align__(128) bf16 g_y[S*D];
__device__ __align__(128) bf16 g_h[S*F];
__device__ __align__(128) bf16 g_gate[S*D];
__device__ __align__(128) bf16 g_k[(size_t)S*HD];
__device__ __align__(128) bf16 g_v[(size_t)S*HD];
__device__ __align__(128) bf16 g_km[NSEG*8*HD];
__device__ __align__(128) uint32_t g_flag[NCTA*32];
__device__ __align__(1024) uint8_t g_u[(size_t)NSEG*40*40960];
__device__ __align__(1024) uint8_t g_p[(size_t)NSEG*40*2048];
#define NSTAB 0xAA55522222222222ull
#define EKM 0
#define RTB 14
__host__ __device__ constexpr int nsp(int rb){ return rb>=RTB?0:(int)((NSTAB>>(4*rb))&15); }
__host__ __device__ constexpr bool ns_used(int n){ for(int r=0;r<16;r++) if(nsp(r)==n) return true; return false; }
constexpr int C_NEXT=0, C_KV=256, C_M1=272, C_M2=288, C_RD=304, C_QA=320, C_NUM=384;
__device__ __align__(128) uint32_t g_cnt[C_NUM];
#define PDL 1
__device__ __align__(1024) unsigned long long g_acc[NSEG*2560];
constexpr unsigned long long ACC_INIT=0ull-32ull*((0x5A000000ull<<32)+0xD0000000ull+1ull);
__device__ __align__(128) uint32_t g_nrm[NCTA*2+32];
__device__ int g_err;
__device__ unsigned long long g_gt[128*4];
#define GT(i) do{ if(threadIdx.x==0){ unsigned long long g0; asm volatile("mov.u64 %0, %%globaltimer;":"=l"(g0)); g_gt[blockIdx.x*4+(i)]=g0; } }while(0)

__device__ __forceinline__ float rb(float x){ return __bfloat162float(__float2bfloat16(x)); }
__device__ __forceinline__ uint32_t pack_bf16(float lo,float hi){ uint32_t r; asm("cvt.rn.bf16x2.f32 %0, %1, %2;":"=r"(r):"f"(hi),"f"(lo)); return r; }
__device__ __forceinline__ uint32_t movm(uint32_t a){ uint32_t d; asm volatile("movmatrix.sync.aligned.m8n8.trans.b16 %0, %1;":"=r"(d):"r"(a)); return d; }
__device__ __forceinline__ uint4 ldg_rlx4(const uint32_t* p){ uint4 v; asm volatile("ld.relaxed.gpu.global.v4.u32 {%0,%1,%2,%3}, [%4];":"=r"(v.x),"=r"(v.y),"=r"(v.z),"=r"(v.w):"l"(p):"memory"); return v; }
__device__ __forceinline__ void stg_rlx1(uint32_t* p,uint32_t a){ asm volatile("st.relaxed.gpu.global.u32 [%0], %1;"::"l"(p),"r"(a):"memory"); }
__device__ __forceinline__ void stg_rlx2(uint32_t* p,uint32_t a,uint32_t b){ asm volatile("st.relaxed.gpu.global.v2.u32 [%0], {%1,%2};"::"l"(p),"r"(a),"r"(b):"memory"); }
__device__ __forceinline__ void stg1(void* p,uint32_t a){ asm volatile("st.global.u32 [%0], %1;"::"l"(p),"r"(a):"memory"); }
__device__ __forceinline__ void stg4(void* p,uint32_t a,uint32_t b,uint32_t c,uint32_t d){ asm volatile("st.global.v4.u32 [%0], {%1,%2,%3,%4};"::"l"(p),"r"(a),"r"(b),"r"(c),"r"(d):"memory"); }
__device__ __forceinline__ void bar_sync(int id,int n){ asm volatile("bar.sync %0, %1;"::"r"(id),"r"(n):"memory"); }
__device__ __forceinline__ void bar_arrive(int id,int n){ asm volatile("bar.arrive %0, %1;"::"r"(id),"r"(n):"memory"); }
__device__ __forceinline__ void mma16816(float* d,const uint32_t* a,uint32_t b0,uint32_t b1){
  asm volatile("mma.sync.aligned.m16n8k16.row.col.f32.bf16.bf16.f32 {%0,%1,%2,%3},{%4,%5,%6,%7},{%8,%9},{%0,%1,%2,%3};"
   :"+f"(d[0]),"+f"(d[1]),"+f"(d[2]),"+f"(d[3]):"r"(a[0]),"r"(a[1]),"r"(a[2]),"r"(a[3]),"r"(b0),"r"(b1));
}
__device__ __forceinline__ void mma1688(float* d,uint32_t a0,uint32_t a1,uint32_t b0){
  asm volatile("mma.sync.aligned.m16n8k8.row.col.f32.bf16.bf16.f32 {%0,%1,%2,%3},{%4,%5},{%6},{%0,%1,%2,%3};"
   :"+f"(d[0]),"+f"(d[1]),"+f"(d[2]),"+f"(d[3]):"r"(a0),"r"(a1),"r"(b0));
}
__device__ __forceinline__ void ldsm4t(uint32_t* r,uint32_t addr){ asm volatile("ldmatrix.sync.aligned.m8n8.x4.trans.shared.b16 {%0,%1,%2,%3}, [%4];":"=r"(r[0]),"=r"(r[1]),"=r"(r[2]),"=r"(r[3]):"r"(addr):"memory"); }
__device__ __forceinline__ void ldsm4(uint32_t* r,uint32_t addr){ asm volatile("ldmatrix.sync.aligned.m8n8.x4.shared.b16 {%0,%1,%2,%3}, [%4];":"=r"(r[0]),"=r"(r[1]),"=r"(r[2]),"=r"(r[3]):"r"(addr):"memory"); }
__device__ __forceinline__ void stsm4(uint32_t a,uint32_t r0,uint32_t r1,uint32_t r2,uint32_t r3){ asm volatile("stmatrix.sync.aligned.m8n8.x4.shared.b16 [%0], {%1,%2,%3,%4};"::"r"(a),"r"(r0),"r"(r1),"r"(r2),"r"(r3):"memory"); }
__device__ __forceinline__ void stsm2(uint32_t a,uint32_t r0,uint32_t r1){ asm volatile("stmatrix.sync.aligned.m8n8.x2.shared.b16 [%0], {%1,%2};"::"r"(a),"r"(r0),"r"(r1):"memory"); }
__device__ __forceinline__ void cp16(uint32_t dst,const void* src){ asm volatile("cp.async.cg.shared.global [%0], [%1], 16;"::"r"(dst),"l"(src):"memory"); }
__device__ __forceinline__ void cp_wait_all(){ asm volatile("cp.async.wait_all;":::"memory"); }
__device__ __forceinline__ void fence_async(){ asm volatile("fence.proxy.async.shared::cta;":::"memory"); }
__device__ __forceinline__ void sts4f(uint32_t a,const float* v){ asm volatile("st.shared.v4.f32 [%0], {%1,%2,%3,%4};"::"r"(a),"f"(v[0]),"f"(v[1]),"f"(v[2]),"f"(v[3]):"memory"); }
__device__ __forceinline__ void sts4(uint32_t a,uint4 v){ asm volatile("st.shared.v4.u32 [%0], {%1,%2,%3,%4};"::"r"(a),"r"(v.x),"r"(v.y),"r"(v.z),"r"(v.w):"memory"); }
__device__ __forceinline__ void sts4r(uint32_t a,const uint32_t* v){ asm volatile("st.shared.v4.u32 [%0], {%1,%2,%3,%4};"::"r"(a),"r"(v[0]),"r"(v[1]),"r"(v[2]),"r"(v[3]):"memory"); }
__device__ __forceinline__ void sts2(uint32_t a,uint32_t x,uint32_t y){ asm volatile("st.shared.v2.u32 [%0], {%1,%2};"::"r"(a),"r"(x),"r"(y):"memory"); }
__device__ __forceinline__ float4 lds4f(uint32_t a){ float4 v; asm volatile("ld.shared.v4.f32 {%0,%1,%2,%3}, [%4];":"=f"(v.x),"=f"(v.y),"=f"(v.z),"=f"(v.w):"r"(a):"memory"); return v; }
__device__ __forceinline__ float2 lds2f(uint32_t a){ float2 v; asm volatile("ld.shared.v2.f32 {%0,%1}, [%2];":"=f"(v.x),"=f"(v.y):"r"(a):"memory"); return v; }
__device__ __forceinline__ uint4 lds4(uint32_t a){ uint4 v; asm volatile("ld.shared.v4.u32 {%0,%1,%2,%3}, [%4];":"=r"(v.x),"=r"(v.y),"=r"(v.z),"=r"(v.w):"r"(a):"memory"); return v; }
__device__ __forceinline__ void lds4r(uint32_t* r,uint32_t a){ asm volatile("ld.shared.v4.u32 {%0,%1,%2,%3}, [%4];":"=r"(r[0]),"=r"(r[1]),"=r"(r[2]),"=r"(r[3]):"r"(a):"memory"); }
__device__ __forceinline__ uint2 lds2(uint32_t a){ uint2 v; asm volatile("ld.shared.v2.u32 {%0,%1}, [%2];":"=r"(v.x),"=r"(v.y):"r"(a):"memory"); return v; }
__device__ __forceinline__ float ex2(float x){ float r; asm("ex2.approx.ftz.f32 %0, %1;":"=f"(r):"f"(x)); return r; }
__device__ __forceinline__ float rcp(float x){ float r; asm("rcp.approx.ftz.f32 %0, %1;":"=f"(r):"f"(x)); return r; }
__device__ __forceinline__ void mbar_init(uint32_t a,int n){ asm volatile("mbarrier.init.shared.b64 [%0], %1;"::"r"(a),"r"(n):"memory"); }
__device__ __forceinline__ void mbar_expect(uint32_t a,int bytes){ asm volatile("mbarrier.arrive.expect_tx.shared.b64 _, [%0], %1;"::"r"(a),"r"(bytes):"memory"); }
__device__ __forceinline__ void mbar_arrive(uint32_t a){ asm volatile("mbarrier.arrive.shared.b64 _, [%0];"::"r"(a):"memory"); }
__device__ __forceinline__ bool mbar_try(uint32_t a,uint32_t par){ uint32_t ok; asm volatile("{\n.reg .pred p;\nmbarrier.try_wait.parity.shared.b64 p, [%1], %2;\nselp.u32 %0,1,0,p;\n}":"=r"(ok):"r"(a),"r"(par):"memory"); return ok; }
__device__ __forceinline__ bool mbar_test(uint32_t a,uint32_t par){ uint32_t ok; asm volatile("{\n.reg .pred p;\nmbarrier.test_wait.parity.shared.b64 p, [%1], %2;\nselp.u32 %0,1,0,p;\n}":"=r"(ok):"r"(a),"r"(par):"memory"); return ok; }
__device__ __forceinline__ bool mbar_try_cl(uint32_t a,uint32_t par){ uint32_t ok; asm volatile("{\n.reg .pred p;\nmbarrier.try_wait.parity.acquire.cluster.shared::cta.b64 p, [%1], %2;\nselp.u32 %0,1,0,p;\n}":"=r"(ok):"r"(a),"r"(par):"memory"); return ok; }
__device__ __forceinline__ void bulk_g2s(uint32_t dst,const void* src,int bytes,uint32_t mb){ asm volatile("cp.async.bulk.shared::cluster.global.mbarrier::complete_tx::bytes [%0], [%1], %2, [%3];"::"r"(dst),"l"(src),"r"(bytes),"r"(mb):"memory"); }
__device__ __forceinline__ uint32_t mapa(uint32_t a,uint32_t r){ uint32_t d; asm("mapa.shared::cluster.u32 %0, %1, %2;":"=r"(d):"r"(a),"r"(r)); return d; }
__device__ __forceinline__ void st_async2(uint32_t ra,uint32_t x,uint32_t y,uint32_t rmb){ asm volatile("st.async.weak.shared::cluster.mbarrier::complete_tx::bytes.v2.b32 [%0], {%1,%2}, [%3];"::"r"(ra),"r"(x),"r"(y),"r"(rmb):"memory"); }
__device__ __forceinline__ void st_async4(uint32_t ra,uint32_t x,uint32_t y,uint32_t z,uint32_t w,uint32_t rmb){ asm volatile("st.async.weak.shared::cluster.mbarrier::complete_tx::bytes.v4.b32 [%0], {%1,%2,%3,%4}, [%5];"::"r"(ra),"r"(x),"r"(y),"r"(z),"r"(w),"r"(rmb):"memory"); }
__device__ __forceinline__ void stg_rlx4(uint32_t* p,uint32_t a,uint32_t b,uint32_t c,uint32_t d){ asm volatile("st.relaxed.gpu.global.v4.u32 [%0], {%1,%2,%3,%4};"::"l"(p),"r"(a),"r"(b),"r"(c),"r"(d):"memory"); }
__device__ __forceinline__ void red64(void* p,uint32_t lo,uint32_t hi){ asm volatile("{\n.reg .b64 v;\nmov.b64 v, {%1,%2};\nred.relaxed.gpu.global.add.u64 [%0], v;\n}"::"l"(p),"r"(lo),"r"(hi):"memory"); }
__device__ __forceinline__ uint32_t amax2(uint32_t a,uint32_t b){ uint32_t r; asm("max.xorsign.abs.bf16x2 %0, %1, %2;":"=r"(r):"r"(a),"r"(b)); return r; }
__device__ __forceinline__ void cluster_sync(){ asm volatile("barrier.cluster.arrive.release.aligned;\nbarrier.cluster.wait.acquire.aligned;":::"memory"); }
__device__ __forceinline__ uint32_t ld_acq(const uint32_t* p){ uint32_t v; asm volatile("ld.acquire.gpu.global.u32 %0, [%1];":"=r"(v):"l"(p):"memory"); return v; }
__device__ __forceinline__ void fence_async_all(){ asm volatile("fence.proxy.async;":::"memory"); }
__device__ __forceinline__ void fence_async_g(){ asm volatile("fence.proxy.async.global;":::"memory"); }
__device__ __forceinline__ void fence_rel(){ asm volatile("fence.release.gpu;":::"memory"); }
__device__ __forceinline__ void fence_acq(){ asm volatile("fence.acquire.gpu;":::"memory"); }
__device__ __forceinline__ void fence_gpu(){ asm volatile("fence.acq_rel.gpu;":::"memory"); }

template<int NL,class V,class LDF,class OKF>
__device__ __forceinline__ int poll1(V* u,LDF ld,OKF ok,bool& dead,int code){
  #pragma unroll
  for(int i=0;i<NL;i++) u[i]=ld(i);
  int guard=0;
  while(true){
    bool f[NL]; bool a=true;
    #pragma unroll
    for(int i=0;i<NL;i++){ f[i]=ok(u[i]); a=a&&f[i]; }
    if(__all_sync(~0u,a)||dead) break;
    #pragma unroll
    for(int i=0;i<NL;i++) if(!f[i]) u[i]=ld(i);
    if(++guard>GUARD){ dead=true; g_err=code; }
  }
  return guard;
}
template<int NL,class V,class LDF,class OKF>
__device__ __forceinline__ int poll2(V* u,LDF ld,OKF ok,bool& dead,int code){
  int guard=0;
  while(true){
    bool f[NL]; bool a=true;
    #pragma unroll
    for(int i=0;i<NL;i++){ f[i]=ok(u[i]); a=a&&f[i]; }
    if(__all_sync(~0u,a)||dead) break;
    #pragma unroll
    for(int i=0;i<NL;i++) if(!f[i]) u[i]=ld(i);
    if(++guard>GUARD){ dead=true; g_err=code; }
  }
  return guard;
}
__device__ __forceinline__ void spin(uint32_t n){ uint32_t t0,t1; asm volatile("mov.u32 %0, %%clock;":"=r"(t0)); do{ asm volatile("mov.u32 %0, %%clock;":"=r"(t1)); }while(t1-t0<n); }
static_assert(!EKM||RTB<16,"final items wait for the recurrence");
template<int N> __device__ __forceinline__ void wgmma(float* d,uint32_t da,uint32_t db,int sc);
template<int N> __device__ __forceinline__ void wgmma_rs(float* d,const uint32_t* a,uint32_t db,int sc);
template<> __device__ __forceinline__ void wgmma<128>(float* d,uint32_t da,uint32_t db,int sc){
  asm volatile("{\n.reg .pred p;\n.reg .b64 xa, xb;\nmov.b64 xa, {%64, 0x40000040};\nmov.b64 xb, {%65, 0x40000040};\nsetp.ne.b32 p, %66, 0;\nwgmma.mma_async.sync.aligned.m64n128k16.f32.bf16.bf16 {%0,%1,%2,%3,%4,%5,%6,%7,%8,%9,%10,%11,%12,%13,%14,%15,%16,%17,%18,%19,%20,%21,%22,%23,%24,%25,%26,%27,%28,%29,%30,%31,%32,%33,%34,%35,%36,%37,%38,%39,%40,%41,%42,%43,%44,%45,%46,%47,%48,%49,%50,%51,%52,%53,%54,%55,%56,%57,%58,%59,%60,%61,%62,%63}, xa, xb, p, 1, 1, 0, 1;\n}"
   :"+f"(d[0]),"+f"(d[1]),"+f"(d[2]),"+f"(d[3]),"+f"(d[4]),"+f"(d[5]),"+f"(d[6]),"+f"(d[7]),"+f"(d[8]),"+f"(d[9]),"+f"(d[10]),"+f"(d[11]),"+f"(d[12]),"+f"(d[13]),"+f"(d[14]),"+f"(d[15]),"+f"(d[16]),"+f"(d[17]),"+f"(d[18]),"+f"(d[19]),"+f"(d[20]),"+f"(d[21]),"+f"(d[22]),"+f"(d[23]),"+f"(d[24]),"+f"(d[25]),"+f"(d[26]),"+f"(d[27]),"+f"(d[28]),"+f"(d[29]),"+f"(d[30]),"+f"(d[31]),"+f"(d[32]),"+f"(d[33]),"+f"(d[34]),"+f"(d[35]),"+f"(d[36]),"+f"(d[37]),"+f"(d[38]),"+f"(d[39]),"+f"(d[40]),"+f"(d[41]),"+f"(d[42]),"+f"(d[43]),"+f"(d[44]),"+f"(d[45]),"+f"(d[46]),"+f"(d[47]),"+f"(d[48]),"+f"(d[49]),"+f"(d[50]),"+f"(d[51]),"+f"(d[52]),"+f"(d[53]),"+f"(d[54]),"+f"(d[55]),"+f"(d[56]),"+f"(d[57]),"+f"(d[58]),"+f"(d[59]),"+f"(d[60]),"+f"(d[61]),"+f"(d[62]),"+f"(d[63]):"r"(da),"r"(db),"r"(sc));
}
template<> __device__ __forceinline__ void wgmma<192>(float* d,uint32_t da,uint32_t db,int sc){
  asm volatile("{\n.reg .pred p;\n.reg .b64 xa, xb;\nmov.b64 xa, {%96, 0x40000040};\nmov.b64 xb, {%97, 0x40000040};\nsetp.ne.b32 p, %98, 0;\nwgmma.mma_async.sync.aligned.m64n192k16.f32.bf16.bf16 {%0,%1,%2,%3,%4,%5,%6,%7,%8,%9,%10,%11,%12,%13,%14,%15,%16,%17,%18,%19,%20,%21,%22,%23,%24,%25,%26,%27,%28,%29,%30,%31,%32,%33,%34,%35,%36,%37,%38,%39,%40,%41,%42,%43,%44,%45,%46,%47,%48,%49,%50,%51,%52,%53,%54,%55,%56,%57,%58,%59,%60,%61,%62,%63,%64,%65,%66,%67,%68,%69,%70,%71,%72,%73,%74,%75,%76,%77,%78,%79,%80,%81,%82,%83,%84,%85,%86,%87,%88,%89,%90,%91,%92,%93,%94,%95}, xa, xb, p, 1, 1, 0, 1;\n}"
   :"+f"(d[0]),"+f"(d[1]),"+f"(d[2]),"+f"(d[3]),"+f"(d[4]),"+f"(d[5]),"+f"(d[6]),"+f"(d[7]),"+f"(d[8]),"+f"(d[9]),"+f"(d[10]),"+f"(d[11]),"+f"(d[12]),"+f"(d[13]),"+f"(d[14]),"+f"(d[15]),"+f"(d[16]),"+f"(d[17]),"+f"(d[18]),"+f"(d[19]),"+f"(d[20]),"+f"(d[21]),"+f"(d[22]),"+f"(d[23]),"+f"(d[24]),"+f"(d[25]),"+f"(d[26]),"+f"(d[27]),"+f"(d[28]),"+f"(d[29]),"+f"(d[30]),"+f"(d[31]),"+f"(d[32]),"+f"(d[33]),"+f"(d[34]),"+f"(d[35]),"+f"(d[36]),"+f"(d[37]),"+f"(d[38]),"+f"(d[39]),"+f"(d[40]),"+f"(d[41]),"+f"(d[42]),"+f"(d[43]),"+f"(d[44]),"+f"(d[45]),"+f"(d[46]),"+f"(d[47]),"+f"(d[48]),"+f"(d[49]),"+f"(d[50]),"+f"(d[51]),"+f"(d[52]),"+f"(d[53]),"+f"(d[54]),"+f"(d[55]),"+f"(d[56]),"+f"(d[57]),"+f"(d[58]),"+f"(d[59]),"+f"(d[60]),"+f"(d[61]),"+f"(d[62]),"+f"(d[63]),"+f"(d[64]),"+f"(d[65]),"+f"(d[66]),"+f"(d[67]),"+f"(d[68]),"+f"(d[69]),"+f"(d[70]),"+f"(d[71]),"+f"(d[72]),"+f"(d[73]),"+f"(d[74]),"+f"(d[75]),"+f"(d[76]),"+f"(d[77]),"+f"(d[78]),"+f"(d[79]),"+f"(d[80]),"+f"(d[81]),"+f"(d[82]),"+f"(d[83]),"+f"(d[84]),"+f"(d[85]),"+f"(d[86]),"+f"(d[87]),"+f"(d[88]),"+f"(d[89]),"+f"(d[90]),"+f"(d[91]),"+f"(d[92]),"+f"(d[93]),"+f"(d[94]),"+f"(d[95]):"r"(da),"r"(db),"r"(sc));
}
template<> __device__ __forceinline__ void wgmma_rs<64>(float* d,const uint32_t* a,uint32_t db,int sc){
  asm volatile("{\n.reg .pred p;\n.reg .b64 xb;\nmov.b64 xb, {%36, 0x40000040};\nsetp.ne.b32 p, %37, 0;\nwgmma.mma_async.sync.aligned.m64n64k16.f32.bf16.bf16 {%0,%1,%2,%3,%4,%5,%6,%7,%8,%9,%10,%11,%12,%13,%14,%15,%16,%17,%18,%19,%20,%21,%22,%23,%24,%25,%26,%27,%28,%29,%30,%31}, {%32,%33,%34,%35}, xb, p, 1, 1, 0;\n}"
   :"+f"(d[0]),"+f"(d[1]),"+f"(d[2]),"+f"(d[3]),"+f"(d[4]),"+f"(d[5]),"+f"(d[6]),"+f"(d[7]),"+f"(d[8]),"+f"(d[9]),"+f"(d[10]),"+f"(d[11]),"+f"(d[12]),"+f"(d[13]),"+f"(d[14]),"+f"(d[15]),"+f"(d[16]),"+f"(d[17]),"+f"(d[18]),"+f"(d[19]),"+f"(d[20]),"+f"(d[21]),"+f"(d[22]),"+f"(d[23]),"+f"(d[24]),"+f"(d[25]),"+f"(d[26]),"+f"(d[27]),"+f"(d[28]),"+f"(d[29]),"+f"(d[30]),"+f"(d[31]):"r"(a[0]),"r"(a[1]),"r"(a[2]),"r"(a[3]),"r"(db),"r"(sc));
}
#define PPF 0
#define PPN 61440
#define PPFA(i) (size_t)(i)
__device__ __align__(128) uint32_t g_sml[NCTA];
constexpr int PRE_T=704;
__global__ void __launch_bounds__(PRE_T) k_pre(const bf16* __restrict__ x,const bf16* __restrict__ mem0,const char* wk,const char* wv){
  const int warp=threadIdx.x>>5, lane=threadIdx.x&31;
  const int row=blockIdx.x*(PRE_T/32)+warp;
  asm volatile("griddepcontrol.launch_dependents;");
  if(threadIdx.x==0){ uint32_t sm_; asm volatile("mov.u32 %0, %%smid;":"=r"(sm_)); g_sml[blockIdx.x]=sm_; }
  uint2 u[5];
  static_assert(2*(NCTA-1)*PRE_T>=(NSEG-1)*1280,"init");
  {
    int i=blockIdx.x*PRE_T+threadIdx.x; constexpr int n=(NCTA-1)*PRE_T;
    if(blockIdx.x==NCTA-1){
      if(warp>=8) return;
      extern __shared__ uint32_t smx[];
      uint32_t w[10], mx=0;
      #pragma unroll
      for(int j=0;j<10;j++){ const int k=threadIdx.x+256*j; const uint16_t* mp=(const uint16_t*)mem0+(((k>>3)&3)*2+((k>>5)&1))*D+(k>>6)*16+(k&7);
        w[j]=mp[0]|((uint32_t)mp[8]<<16); mx=max(mx,max(w[j]&0x7fffu,(w[j]>>16)&0x7fffu)); }
      mx=__reduce_max_sync(~0u,mx); if(lane==0) smx[warp]=mx;
      bar_sync(1,256);
      #pragma unroll
      for(int j=0;j<8;j++) mx=max(mx,smx[j]);
      const uint32_t eb=min(max(mx>>7,40u),254u); const float sc=__uint_as_float((280u-eb)<<23);
      #pragma unroll
      for(int j=0;j<10;j++) g_acc[threadIdx.x+256*j]=((unsigned long long)(long long)__float2int_rn(__uint_as_float(w[j]&0xffff0000u)*sc)<<35)+((unsigned long long)(long long)__float2int_rn(__uint_as_float(w[j]<<16)*sc)<<6);
      if(threadIdx.x<NCTA*2) g_nrm[threadIdx.x]=SENT;
      if(threadIdx.x==0) g_nrm[NCTA*2]=(eb-29u)<<23;
      return;
    }
    const uint2* p=(const uint2*)(x+(size_t)min(row,S-1)*D);
    #pragma unroll
    for(int j=0;j<5;j++) asm volatile("ld.global.nc.v2.u32 {%0,%1}, [%2];":"=r"(u[j].x),"=r"(u[j].y):"l"(p+lane+32*j));
    #pragma unroll
    for(int j=0;j<2;j++){ const int k=1280+i+j*n; if(k<NSEG*1280) ((ulonglong2*)g_acc)[k]=make_ulonglong2(ACC_INIT,ACC_INIT); }
    if(i==0) g_err=0;
    if(i<NCTA*32) g_flag[i]=0;
    if(i<C_NUM) g_cnt[i]=0;
  }
  #define PFW { const int i=blockIdx.x*PRE_T+threadIdx.x; if(i<PPN){ asm volatile("prefetch.global.L2 [%0];"::"l"(wk+(size_t)i*128+(u[4].y&zr)):"memory"); asm volatile("prefetch.global.L2 [%0];"::"l"(wv+(size_t)i*128+(u[4].y&zr)):"memory"); } }
  const uint32_t zr=PPF==2?(uint32_t)((size_t)wk&1):0u;
  if(PPF) PFW
  if(row>=S) return;
  float v[20];
  #pragma unroll
  for(int i=0;i<5;i++){ v[4*i]=__uint_as_float(u[i].x<<16); v[4*i+1]=__uint_as_float(u[i].x&0xffff0000u); v[4*i+2]=__uint_as_float(u[i].y<<16); v[4*i+3]=__uint_as_float(u[i].y&0xffff0000u); }
  #pragma unroll
  for(int pass=0;pass<2;pass++){
    float s=0;
    #pragma unroll
    for(int i=0;i<20;i++) s+=v[i];
    #pragma unroll
    for(int o=16;o;o>>=1) s+=__shfl_xor_sync(~0u,s,o);
    float mean=s*(1.f/D);
    float q=0;
    #pragma unroll
    for(int i=0;i<20;i++){ float d=v[i]-mean; q+=d*d; }
    #pragma unroll
    for(int o=16;o;o>>=1) q+=__shfl_xor_sync(~0u,q,o);
    float var=rb(q*(1.f/D)), mb=rb(mean);
    float den=rb(sqrtf(rb(var+1e-5f)));
    const float id=1.f/den;
    uint2* o=(uint2*)((pass?g_y:g_xn)+(size_t)row*D);
    #pragma unroll
    for(int i=0;i<5;i++){
      uint32_t w[2];
      #pragma unroll
      for(int j=0;j<2;j++){
        const uint32_t d=pack_bf16(v[4*i+2*j]-mb,v[4*i+2*j+1]-mb);
        w[j]=pack_bf16(__uint_as_float(d<<16)*id,__uint_as_float(d&0xffff0000u)*id);
        v[4*i+2*j]=__uint_as_float(w[j]<<16); v[4*i+2*j+1]=__uint_as_float(w[j]&0xffff0000u);
      }
      o[lane+32*i]=make_uint2(w[0],w[1]);
    }
  }
}

#define TRO 0
#define ETL 1
#define FIN 0
#define SMM 1
#define NRD 1
#define XB 1
#define UW3 7
#define VC 2
#define IL 0
#define LBF 0
#define KORD 0x5498327610ull
__host__ __device__ constexpr int kord(int y){ return (int)((KORD>>(4*y))&15); }
#define LTID 2
#define TQ2 1
#define TPF 60
#define ULAY 0
#define WGO 1
#define UBP 4
#define URM 63
#define UEB 24
#define NOF 0
#define EXD 0
#define UEX 1
#define ADELAY 0
#define KP 4
#define UXP 16
#define OPF 99
#define XGP 0
#define W3O 250
#define FW 3
#define WPA 1
#define WPB 20
#define PD 990
#define PPOS 2
#define ADP 0
#define ADUP 64
#define ADDN 4
constexpr int SM_QS=0;
constexpr int SM_KS=49152;
constexpr int SM_OS=131072;
constexpr int SM_RED=180224;
constexpr int SM_P=SM_RED+3584;
constexpr int SM_PM=SM_RED+4096+3584;
constexpr int SM_MB=SM_PM+128;
constexpr int SM_MX=SM_PM+192, SM_SCL=SM_PM+224;
constexpr int SM_X5=SM_RED+8192+3584;
constexpr int SM_KX=SM_RED+16384;
constexpr int SM_VX=SM_KX+4096;
constexpr int SM_SCX=SM_VX+14336;
constexpr int SM_KRED=SM_SCX+6144;
constexpr int SM_VMX=SM_KRED+8192;
constexpr int SM_TOTAL=SM_VMX+3072, SM_NR=SM_VMX;
static_assert(SM_TOTAL<=232448,"smem");
__device__ __forceinline__ void wg32_rs(float* d,const uint32_t* a,uint32_t db){
  asm volatile("{\n.reg .b64 xb;\nmov.b64 xb, {%20, 0x40000040};\nwgmma.mma_async.sync.aligned.m64n32k16.f32.bf16.bf16 {%0,%1,%2,%3,%4,%5,%6,%7,%8,%9,%10,%11,%12,%13,%14,%15}, {%16,%17,%18,%19}, xb, 1, 1, 1, 0;\n}"
   :"+f"(d[0]),"+f"(d[1]),"+f"(d[2]),"+f"(d[3]),"+f"(d[4]),"+f"(d[5]),"+f"(d[6]),"+f"(d[7]),"+f"(d[8]),"+f"(d[9]),"+f"(d[10]),"+f"(d[11]),"+f"(d[12]),"+f"(d[13]),"+f"(d[14]),"+f"(d[15])
   :"r"(a[0]),"r"(a[1]),"r"(a[2]),"r"(a[3]),"r"(db));
}
__device__ __forceinline__ void wg32_rs0(float* d,const uint32_t* a,uint32_t db){
  asm volatile("{\n.reg .b64 xb;\nmov.b64 xb, {%20, 0x40000040};\nwgmma.mma_async.sync.aligned.m64n32k16.f32.bf16.bf16 {%0,%1,%2,%3,%4,%5,%6,%7,%8,%9,%10,%11,%12,%13,%14,%15}, {%16,%17,%18,%19}, xb, 0, 1, 1, 0;\n}"
   :"=f"(d[0]),"=f"(d[1]),"=f"(d[2]),"=f"(d[3]),"=f"(d[4]),"=f"(d[5]),"=f"(d[6]),"=f"(d[7]),"=f"(d[8]),"=f"(d[9]),"=f"(d[10]),"=f"(d[11]),"=f"(d[12]),"=f"(d[13]),"=f"(d[14]),"=f"(d[15])
   :"r"(a[0]),"r"(a[1]),"r"(a[2]),"r"(a[3]),"r"(db));
}
__device__ __forceinline__ void wg32_ss(float* d,uint32_t da,uint32_t db){
  asm volatile("{\n.reg .b64 xa, xb;\nmov.b64 xa, {%16, 0x00000180};\nmov.b64 xb, {%17, 0x40000040};\nwgmma.mma_async.sync.aligned.m64n32k16.f32.bf16.bf16 {%0,%1,%2,%3,%4,%5,%6,%7,%8,%9,%10,%11,%12,%13,%14,%15}, xa, xb, 1, 1, 1, 0, 0;\n}"
   :"+f"(d[0]),"+f"(d[1]),"+f"(d[2]),"+f"(d[3]),"+f"(d[4]),"+f"(d[5]),"+f"(d[6]),"+f"(d[7]),"+f"(d[8]),"+f"(d[9]),"+f"(d[10]),"+f"(d[11]),"+f"(d[12]),"+f"(d[13]),"+f"(d[14]),"+f"(d[15])
   :"r"(da),"r"(db));
}
__device__ __forceinline__ void wg32_ss0(float* d,uint32_t da,uint32_t db){
  asm volatile("{\n.reg .b64 xa, xb;\nmov.b64 xa, {%16, 0x00000180};\nmov.b64 xb, {%17, 0x40000040};\nwgmma.mma_async.sync.aligned.m64n32k16.f32.bf16.bf16 {%0,%1,%2,%3,%4,%5,%6,%7,%8,%9,%10,%11,%12,%13,%14,%15}, xa, xb, 0, 1, 1, 0, 0;\n}"
   :"=f"(d[0]),"=f"(d[1]),"=f"(d[2]),"=f"(d[3]),"=f"(d[4]),"=f"(d[5]),"=f"(d[6]),"=f"(d[7]),"=f"(d[8]),"=f"(d[9]),"=f"(d[10]),"=f"(d[11]),"=f"(d[12]),"=f"(d[13]),"=f"(d[14]),"=f"(d[15])
   :"r"(da),"r"(db));
}
#define TT(i)
template<int V> struct IC{ static constexpr int v=V; };
__device__ __forceinline__ uint32_t lds1(uint32_t a){ uint32_t v; asm volatile("ld.shared.u32 %0, [%1];":"=r"(v):"r"(a):"memory"); return v; }
__device__ __forceinline__ void sts1(uint32_t a,uint32_t x){ asm volatile("st.shared.u32 [%0], %1;"::"r"(a),"r"(x):"memory"); }

#define TS(i)
#define TSB(i)
#define PC(i) (void)np
#define TW(i)
#define TF(i)
#define TFP(i)

__device__ __forceinline__ void cp_commit(){ asm volatile("cp.async.commit_group;":::"memory"); }
template<int N> __device__ __forceinline__ void cp_wait(){ asm volatile("cp.async.wait_group %0;"::"n"(N):"memory"); }
__device__ __forceinline__ void tma2d(uint32_t dst,const CUtensorMap* tm,int c0,int c1,uint32_t mb){
  asm volatile("cp.async.bulk.tensor.2d.shared::cluster.global.mbarrier::complete_tx::bytes [%0], [%1, {%3, %4}], [%2];"::"r"(dst),"l"(tm),"r"(mb),"r"(c0),"r"(c1):"memory"); }
__device__ __forceinline__ void tma2d_pf(const CUtensorMap* tm,int c0,int c1){
  asm volatile("cp.async.bulk.prefetch.tensor.2d.L2.global [%0, {%1, %2}];"::"l"(tm),"r"(c0),"r"(c1):"memory"); }
constexpr unsigned long long PL_EF=0x12F0000000000000ull, PL_EN=0x1000000000000000ull;
__device__ __forceinline__ void tma2dh(uint32_t dst,const CUtensorMap* tm,int c0,int c1,uint32_t mb,unsigned long long pl){
  asm volatile("cp.async.bulk.tensor.2d.shared::cluster.global.mbarrier::complete_tx::bytes.L2::cache_hint [%0], [%1, {%3, %4}], [%2], %5;"::"r"(dst),"l"(tm),"r"(mb),"r"(c0),"r"(c1),"l"(pl):"memory"); }
__device__ __forceinline__ void tma2d_pfh(const CUtensorMap* tm,int c0,int c1,unsigned long long pl){
  asm volatile("cp.async.bulk.prefetch.tensor.2d.L2.global.L2::cache_hint [%0, {%1, %2}], %3;"::"l"(tm),"r"(c0),"r"(c1),"l"(pl):"memory"); }
#define HV 0
#define HK 0
#define HP 0
#define HUS 0
__device__ __forceinline__ uint32_t fin1(uint32_t s,uint32_t x,uint32_t gq){
  const uint32_t p=pack_bf16(__uint_as_float(s<<16)*__uint_as_float(gq<<16),__uint_as_float(s&0xffff0000u)*__uint_as_float(gq&0xffff0000u));
  return pack_bf16(__uint_as_float(x<<16)+__uint_as_float(p<<16),__uint_as_float(x&0xffff0000u)+__uint_as_float(p&0xffff0000u));
}
__device__ __forceinline__ void wg32_pu(float* d,uint32_t da,uint32_t db,int sc){
  asm volatile("{\n.reg .pred p;\n.reg .b64 xa, xb;\nmov.b64 xa, {%16, 32};\nmov.b64 xb, {%17, 8};\nsetp.ne.b32 p, %18, 0;\nwgmma.mma_async.sync.aligned.m64n32k16.f32.bf16.bf16 {%0,%1,%2,%3,%4,%5,%6,%7,%8,%9,%10,%11,%12,%13,%14,%15}, xa, xb, p, 1, 1, 0, 0;\n}"
   :"+f"(d[0]),"+f"(d[1]),"+f"(d[2]),"+f"(d[3]),"+f"(d[4]),"+f"(d[5]),"+f"(d[6]),"+f"(d[7]),"+f"(d[8]),"+f"(d[9]),"+f"(d[10]),"+f"(d[11]),"+f"(d[12]),"+f"(d[13]),"+f"(d[14]),"+f"(d[15])
   :"r"(da),"r"(db),"r"(sc));
}
__device__ __forceinline__ void stsm4t(uint32_t a,uint32_t r0,uint32_t r1,uint32_t r2,uint32_t r3){ asm volatile("stmatrix.sync.aligned.m8n8.x4.trans.shared.b16 [%0], {%1,%2,%3,%4};"::"r"(a),"r"(r0),"r"(r1),"r"(r2),"r"(r3):"memory"); }
__device__ __forceinline__ void red_rel(uint32_t* p){ asm volatile("red.release.gpu.global.add.u32 [%0], 1;"::"l"(p):"memory"); }
struct RParams { CUtensorMap k,v,w[4],u; const char* wq; const char* wo; const bf16* x; bf16* out; };
#define SO 0
#define SA 1
#define SEF 7
#define SPF 1
__global__ void __launch_bounds__(256,1) k_rec(const __grid_constant__ RParams P,const uint32_t zero){
  extern __shared__ __align__(1024) uint8_t sm[];
  int tid; asm volatile("mov.u32 %0, %%tid.x;":"=r"(tid));
  if(LTID>1) tid=__shfl_sync(~0u,tid,tid&31);
  __builtin_assume(tid>=0&&tid<256);
  const int warp=__shfl_sync(~0u,tid>>5,0), lane=tid&31, g=lane>>2, t=lane&3;
  const int b=blockIdx.x, h=b/3, c=b-3*h;
  const uint32_t sb=(uint32_t)__cvta_generic_to_shared(sm);
  const int kq=warp&3, mg=warp>>2, wt=warp-mg;
  const uint32_t s16=sb+lane*16;
  const uint32_t qs=lane*16+__shfl_sync(~0u,sb+(mg?SM_KS+kq*20480:SM_QS+kq*12288),0), m5u=__shfl_sync(~0u,sb+SM_X5+(kq>>1)*4096+(kq&1)*256,0), mo=((lane>>3)&1), os=sb+SM_OS+kq*12288+mo*6144+(lane>>4)*128+(lane&7)*16, us=sb+SM_VX+wt*2048+mo*512+(lane>>4)*128+(lane&7)*16;
  const uint32_t XS=sb+SM_MB, KVB=sb+SM_MB+8, XV=sb+SM_MB+16, XL=sb+SM_MB+24;
  #define tmK P.k
  #define tmV P.v
  GT(0);
  asm volatile("griddepcontrol.launch_dependents;");
  const int ntile=c==0?14:13, tile0=c==0?0:(1+13*c);
  uint32_t pw[40][4];
#define SG(i)
  SG(0);
  {
    static_assert(KP==4,"setup");
    const uint32_t qb=qs-lane*16, SBR=sb+SM_NR+128+warp*32, ob=sb+(mg?SM_OS:SM_RED)+kq*12288;
    unsigned long long plf, pln;
    asm volatile("createpolicy.fractional.L2::evict_first.b64 %0, 1.0;":"=l"(plf)); asm volatile("createpolicy.fractional.L2::evict_normal.b64 %0, 1.0;":"=l"(pln));
    const unsigned long long plq=(mg?(SEF&4):(SEF&2))?plf:pln, plo=(SEF&1)?plf:pln;
    auto wbox=[&](int rd,int sl,int mode){
      const int kb=rd?(sl<6?sl:sl-6):(sl<4?sl+6:sl), k=mg?(kb+5)%10:kb;
      const CUtensorMap* tm=&P.w[mg?(sl<(rd?6:4)?1:2):0];
      const int c0=h*DH+64*c, c1=80*kq+8*k;
      if(mode) asm volatile("cp.async.bulk.prefetch.tensor.3d.L2.global.L2::cache_hint [%0, {%1, %2, 0}], %3;"::"l"(tm),"r"(c0),"r"(c1),"l"(plq):"memory");
      else asm volatile("cp.async.bulk.tensor.3d.shared::cluster.global.mbarrier::complete_tx::bytes.L2::cache_hint [%0], [%1, {%3, %4, 0}], [%2], %5;"::"r"(qb+sl*2048),"l"(tm),"r"(SBR+((rd||(!mg&&sl>=4))?8:0)),"r"(c0),"r"(c1),"l"(plq):"memory");
    };
    if(lane==0){
      mbar_init(SBR,1); mbar_init(SBR+8,1); mbar_init(SBR+16,1);
      asm volatile("fence.mbarrier_init.release.cluster;":::"memory");
      mbar_expect(SBR,mg?20480:8192); mbar_expect(SBR+8,mg?20480:12288); mbar_expect(SBR+16,12288);
    }
    __syncwarp();
    if(lane<(mg?10:6)) wbox(0,lane,0);
    if(lane<6) asm volatile("cp.async.bulk.tensor.2d.shared::cluster.global.mbarrier::complete_tx::bytes.L2::cache_hint [%0], [%1, {%3, %4}], [%2], %5;"::"r"(ob+(mg?(lane>>1)*2048+(lane&1)*6144:lane*2048)),"l"(&P.w[3]),"r"(SBR+16),"r"((tile0+2*wt)*16),"r"(h*DH+((2*c+lane)%6)*32),"l"(plo):"memory");
    if(SPF&&lane<(mg?(SPF>1?10:0):4)) wbox(1,lane,1);
    __syncwarp();
    SG(1);
    float nr[4][2][4];
    #pragma unroll
    for(int i=0;i<32;i++) nr[i>>3][(i>>2)&1][i&3]=0.f;
    auto sq=[&](int n,const uint32_t* r){ mma16816(nr[n][0],r,r[0],r[2]); mma16816(nr[n][1],r,r[1],r[3]); };
    auto dg=[&](const float* d,int o){ return g==2*t?d[o]:(g==2*t+1?d[o+1]:0.f); };
    auto swait=[&](uint32_t a){ int gd=0; while(!mbar_try(a,0)){ if(++gd>GUARD){ g_err=9; break; } } };
    const int p8=((lane>>1)&3)+4*(lane&1), r16=(lane&7)+(lane>>4)*8;
    uint32_t ak[4], av[4], ao[2];
    #pragma unroll
    for(int j=0;j<4;j++){ ak[j]=qb+(p8+(lane>>4)*8)*128+(((2*j+mo)^p8)<<4); av[j]=qb+(p8+(lane>>4)*8)*128+(((2*((j+kq)&3)+mo)^p8)<<4); }
    #pragma unroll
    for(int i=0;i<2;i++) ao[i]=ob+r16*64+(((2*i+mo)^((lane>>1)&3))<<4);
    swait(SBR);
    SG(2);
    #pragma unroll
    for(int u=0;u<16;u++) ldsm4t(pw[u],ak[u&3]+(u>>2)*2048);
    if(SA&&!mg){
      uint32_t d0=0;
      #pragma unroll
      for(int u=0;u<16;u+=2) d0^=pw[u][0]^pw[u+1][0];
      if(lane+(d0&zero)<4) wbox(1,lane,0);
      __syncwarp();
    }
    swait(SBR+(mg?0:16));
    SG(3);
    uint32_t dp=0;
    {
      uint32_t a2[4];
      #pragma unroll
      for(int j=0;j<4;j++) a2[j]=mg?av[j]+8192:ao[j&1]+(j>>1)*1024;
      #pragma unroll
      for(int u=0;u<24;u++){ ldsm4t(pw[16+u],a2[u&3]+(u>>2)*2048); if(!SA) sq((u&1)*2,pw[16+u]); }
      #pragma unroll
      for(int u=0;u<40;u+=2) dp^=pw[u][0]^pw[u+1][0];
      dp&=zero;
    }
    if(lane+dp<(mg?10:(SA?0:4))) wbox(1,lane,0);
    __syncwarp();
    if(SA){
      #pragma unroll
      for(int u=0;u<24;u++) sq((u&1)*2,pw[16+u]);
    }
    SG(4);
    if(mg){
      swait(SBR+16);
      #pragma unroll 1
      for(int y=0;y<3;y++){
        uint32_t r[8][4];
        #pragma unroll
        for(int f=0;f<8;f++){ ldsm4t(r[f],ao[f&1]+y*2048+((f>>1)&1)*1024+(f>>2)*6144); sq(1+(f&1)*2,r[f]); }
        __syncwarp();
        #pragma unroll
        for(int f=0;f<8;f++) stsm4(os+y*2048+f*256,r[f][0],r[f][1],r[f][2],r[f][3]);
      }
    } else {
      bar_sync(5+dp,128);
      if(tid==96){
        mbar_init(XS,5); mbar_init(KVB,1); mbar_init(XV,1); mbar_init(XL,4);
        for(int i=0;i<4;i++){ mbar_init(sb+SM_PM+256+i*8,2); mbar_init(sb+SM_PM+288+i*8,4); }
        asm volatile("fence.mbarrier_init.release.cluster;":::"memory");
        mbar_expect(XS,XB?2048:4096); mbar_expect(XV,2048);
        int gd=0; while(ld_acq(g_cnt+C_KV)<64){ if(++gd>GUARD){ g_err=7; break; } } fence_async_g();
        mbar_expect(KVB,32*512);
        tma2d(sb+SM_KX,&tmK,h*DH+64*c,0,KVB);
        #pragma unroll 1
        for(int i=0;i<3;i++) tma2d(sb+SM_VX+i*4096,&tmV,h*DH+64*i,0,KVB);
        tma2d_pf(&tmK,h*DH+64*c,32); tma2d_pf(&tmV,h*DH+64*c,32);
      }
      if(tid==32) sts1(sb+SM_SCL+8,g_nrm[NCTA*2]);
      __syncwarp();
    }
    SG(5);
    swait(SBR+8);
    SG(6);
    #pragma unroll 1
    for(int y=0;y<(mg?10:6);y+=2){
      uint32_t r[8][4];
      #pragma unroll
      for(int j=0;j<8;j++) ldsm4t(r[j],(y<6?ak[j&3]:av[j&3])+y*2048+(j>>2)*2048);
      __syncwarp();
      #pragma unroll
      for(int j=0;j<8;j++) sts4r(qs+y*2048+j*512,r[j]);
      if(y>=6){
        #pragma unroll
        for(int j=0;j<8;j++) sq((j&1)*2,r[j]);
      }
    }
    SG(7);
    float d4[4][2];
    #pragma unroll
    for(int i=0;i<4;i++){ d4[i][0]=dg(nr[i][0],0); d4[i][1]=dg(nr[i][1],2); }
    float nv=mg?(d4[0][0]+d4[0][1])+(d4[2][0]+d4[2][1]):0.f;
    #pragma unroll
    for(int o=16;o;o>>=1) nv+=__shfl_xor_sync(~0u,nv,o);
    const uint32_t no=__reduce_max_sync(~0u,__float_as_uint(mg?fmaxf(d4[1][0]+d4[3][0],d4[1][1]+d4[3][1]):fmaxf(d4[0][0]+d4[2][0],d4[0][1]+d4[2][1])));
    if(lane==0){
      sts2(sb+SM_NR+warp*8,__float_as_uint(nv),no);
      #pragma unroll
      for(int i=0;i<3;i++) asm volatile("mbarrier.inval.shared.b64 [%0];"::"r"(SBR+i*8):"memory");
    }
  }
  fence_async();
  __syncthreads();
  SG(8);
  {
    float a=0.f; uint32_t o=0;
    if(warp==0){
      #pragma unroll
      for(int w=0;w<8;w++){ const uint2 x=lds2(sb+SM_NR+w*8); a+=__uint_as_float(x.x); o=max(o,x.y); }
      o=min(o,0x7f800000u);
    }
    asm volatile("barrier.cluster.arrive.relaxed.aligned;"::"r"(o):"memory");
    if(tid==0) stg_rlx2(g_nrm+b*2,min(__float_as_uint(a),0x7f800000u),o);
    asm volatile("barrier.cluster.wait.acquire.aligned;":::"memory");
  }
  SG(9);
  uint32_t pd=PD;
  bool dead=false;
  const uint32_t qrd=sb+SM_RED+1024+((lane>>3)&1)*4096+(lane>>4)*128+(lane&7)*16+kq*256;
  uint32_t rsc[2];
  rsc[0]=mapa(sb,c==2?0:c+1); rsc[1]=mapa(sb,c==0?2:c-1);
  GT(1);
  auto loop=[&](auto MGc){
  constexpr int MG=decltype(MGc)::v;
  uint32_t buf[8][4], um[2][2]={{0,0},{0,0}}, ex0=0, ex1=0;
  uint32_t eo1=(uint32_t)((32+(h>>2))*40960+(tile0+2*wt)*1024+(h&3)*128+lane*4), eo2=(uint32_t)(h*3072+(4*c+kq)*256+lane*4);
  uint32_t so=(uint32_t)((kq*10+MG*5)*512+(g&1)*256+(g>>1)*64+t*16)^zero;
  bool kvok=false;
  #define EXPU { char* um_=(char*)g_u+eo1; _Pragma("unroll") for(int i=0;i<2;i++) if(i==0||2*wt+1<ntile){ stg1(um_+i*1024,um[i][0]); stg1(um_+i*1024+512,um[i][1]); } }
  #define EXPK { char* ep=(char*)g_km+eo2; stg1(ep,ex0); stg1(ep+128,ex1); }
  #define UBULK { const uint32_t o_=(us-sb)&~2047u; asm volatile("{\n.reg .pred p;\nelect.sync _|p, 0xffffffff;\n@p cp.async.bulk.global.shared::cta.bulk_group.L2::cache_hint [%0], [%1], %2, %3;\n@p cp.async.bulk.commit_group;\n}" \
      ::"l"((char*)g_u+(uint32_t)(s*1638400+h*40960+tile0*1024-SM_VX+o_)),"r"(sb+o_),"r"(2*wt+1<ntile?2048:1024),"l"(s<HUS?PL_EF:PL_EN):"memory"); }
  uint32_t t0; asm volatile("mov.u32 %0, %%clock;":"=r"(t0)); t0-=4096;
  #define MB0(k) mb[k][0]
  #define MB1(k) mb[k][1]
  #pragma unroll 1
  for(int s=0;s<NSEG;s++){
    const bool last=s==NSEG-1;
    float u[2][16];
    const char* src=(const char*)g_acc+so;
    uint4 m[5];
    #define SPIN(T,N) { uint32_t t1; do{ asm volatile("mov.u32 %0, %%clock;":"=r"(t1)); }while((int)(t1-(T))<(int)(N)); }
    #define PLD { SPIN(t0,pd) _Pragma("unroll") for(int p=0;p<5;p++) m[p]=ldg_rlx4((const uint32_t*)(src+p*512)); SPIN(t0,pd) TFP(21); }
    {
      if(!kvok){ int gd=0; while(!mbar_try(KVB,s&1)){ if(dead) break; if(++gd>GUARD){ dead=true; g_err=6; } } }
      TFP(16);
      const uint32_t da=(((sb+SM_OS)>>4)&0x3fff)|(8u<<16);
      const uint32_t dv=(((sb+SM_VX)>>4)&0x3fff)|(1u<<16);
      const uint32_t vb[3]={dv+c*256,dv+(c==2?0:c+1)*256,dv+(c==0?2:c-1)*256};
      asm volatile("wgmma.fence.sync.aligned;":::"memory");
      if constexpr(MG){
        #pragma unroll
        for(int y=0;y<24;y++){
          const int i=WGO?(y&1):(y>=12), x=WGO?(y>>1):(y%12);
          if(x==0) wg32_ss0(u[i],da+i*16,vb[0]); else wg32_ss(u[i],da+(x*2+i)*16,vb[x>>2]+(x&3)*2);
          if(y==WPB){ EXPU SPIN(t0,0) }
        }
      } else {
        #pragma unroll
        for(int y=0;y<24;y++){
          const int i=WGO?(y&1):(y>=12), x=WGO?(y>>1):(y%12);
          if(x==0) wg32_rs0(u[i],pw[16+i],vb[0]); else wg32_rs(u[i],pw[16+x*2+i],vb[x>>2]+(x&3)*2);
          if(y==WPA&&warp!=3){ EXPU EXPK }
        }
      }
      asm volatile("wgmma.commit_group.sync.aligned;":::"memory");
      TFP(18);
      if(!MG&&warp==3){
        EXPK
        if(lane==0&&s+2<NSEG){ tma2d_pfh(&tmK,h*DH+64*c,(s+2)*32,HP&1?PL_EF:PL_EN); tma2d_pfh(&tmV,h*DH+64*c,(s+2)*32,HP&2?PL_EF:PL_EN); }
        if(TPF&&lane==0&&b<80&&(uint32_t)(s-TPF)<4u) asm volatile("cp.async.bulk.prefetch.tensor.3d.L2.global [%0, {0, %1, %2}];"::"l"(&P.u),"r"(b%20),"r"((RTB*4+b/20)*40+(s-TPF)*10):"memory");
        __syncwarp();
        if(b<80&&lane<2&&s+2<NSEG) asm volatile("prefetch.global.L2 [%0];"::"l"(g_acc+(size_t)(s+2)*2560+b*32+lane*16));
      }
      PLD
      if(MG&&WPB==30){ EXPU }
      if(!MG&&WPA==30&&warp!=3){ EXPU EXPK }
    }
    const uint32_t mx=s16+SM_RED+kq*4096, m5=m5u+lane*8;
    {
      asm volatile("wgmma.wait_group.sync.aligned 0;":::"memory");
      TFP(19);
      if(MG||warp!=3){
        if(UEX) asm volatile("cp.async.bulk.wait_group 0;":::"memory");
        bar_sync(7,256);
        TFP(20);
        #pragma unroll
        for(int i=0;i<2;i++)
          #pragma unroll
          for(int kk=0;kk<2;kk++)
            stsm4(us+i*1024+kk*256,pack_bf16(u[i][8*kk],u[i][8*kk+1]),pack_bf16(u[i][8*kk+2],u[i][8*kk+3]),pack_bf16(u[i][8*kk+4],u[i][8*kk+5]),pack_bf16(u[i][8*kk+6],u[i][8*kk+7]));
        if(!LBF) fence_async();
        #pragma unroll
        for(int i=0;i<8;i++) lds4r(buf[i],qs+i*512);
        if(LBF) fence_async();
      } else {
        #pragma unroll
        for(int i=0;i<8;i++) lds4r(buf[i],qs+i*512);
        bar_sync(7,256);
        asm volatile("{\n.reg .pred p, q;\nsetp.eq.u32 p, %0, 0;\nsetp.eq.and.u32 q, %1, 0, p;\n@q fence.release.gpu;\n@p st.relaxed.gpu.global.u32 [%2], %3;\n}"::"r"(lane),"r"((s&3)|NOF),"l"(g_flag+b*32),"r"(s):"memory");
      }
      SPIN(t0,pd)
      TFP(17);
    }
    uint32_t mb[10][2];
    float acc[4][4];
    #pragma unroll
    for(int i=0;i<4;i++){ acc[i][0]=acc[i][1]=acc[i][2]=acc[i][3]=0.f; }
    #define KST(k) { _Pragma("unroll") for(int j=0;j<4;j++){ \
      if((k)<6){ mma16816(acc[j],buf[((k)&1)*4+j],MB0(k),MB1(k)); if(MG||(k)<4) lds4r(buf[((k)&1)*4+j],qs+((k)*4+j+8)*512); } \
      else mma16816(acc[j],pw[(k)>=6?((k)-6)*4+j:0],MB0(k),MB1(k)); } }
    {
      auto okf=[&](const uint4& v){ return ((v.x|v.z)&63u)==0; };
      const int np=poll2<5>(m,[&](int i){ return ldg_rlx4((const uint32_t*)(src+i*512)); },okf,dead,1);
      TW(0); PC(0); TFP(14);
      if(ADP){ if(np) pd=min(pd+ADUP,2000u); else pd=max(pd-ADDN,(uint32_t)ADP); }
      #pragma unroll
      for(int p=0;p<5;p++){
        mb[p][0]=pack_bf16((float)(int)__funnelshift_r(m[p].x,m[p].y,3),(float)(int)m[p].y);
        mb[p][1]=pack_bf16((float)(int)__funnelshift_r(m[p].z,m[p].w,3),(float)(int)m[p].w);
        if(p==0) sts2(MG?m5:mx-lane*8+3072,mb[0][0],mb[0][1]);
        if(p==2||p==4) sts4(mx+((MG?0:4)+(p>>2))*512,make_uint4(mb[p-1][0],mb[p-1][1],mb[p][0],mb[p][1]));
        if(p<IL) KST(p)
      }
      bar_arrive((MG?12:8)+kq,64);
      if(UEX&&UBP==1&&(MG||warp!=3)) UBULK
    }
    #define XGET { bar_sync((MG?8:12)+kq,64); const uint2 x=lds2(MG?mx-lane*8+3072:m5); mb[5][0]=x.x; mb[5][1]=x.y; \
      _Pragma("unroll") for(int p=0;p<2;p++){ const uint4 y=lds4(mx+((MG?4:0)+p)*512); mb[6+2*p][0]=y.x; mb[6+2*p][1]=y.y; mb[7+2*p][0]=y.z; mb[7+2*p][1]=y.w; } }
    #define XMAX { uint32_t a=amax2(amax2(amax2(mb[0][0],mb[0][1]),amax2(mb[1][0],mb[1][1])),amax2(amax2(amax2(mb[2][0],mb[2][1]),amax2(mb[3][0],mb[3][1])),amax2(mb[4][0],mb[4][1]))); \
      a=__reduce_max_sync(~0u,max(a&0x7fff0000u,(a<<16)&0x7fff0000u)); if(lane==0) sts1(sb+SM_MX+warp*4,a); }
    TS(0); TF(0);
    uint32_t ux[2][2][4];
    #define UXDEP (((ux[0][0][0]^ux[0][1][0])^(ux[1][0][0]^ux[1][1][0]))&zero)
    if constexpr(MG){
      #pragma unroll
      for(int y=IL;y<10;y++){
        KST(kord(y))
        if(y==XGP) XGET
        if(y==5) XMAX
        if(UEX&&UBP==y+2) UBULK
      }
      TF(1);
      {
        const uint32_t ra=s16+SM_KRED+kq*2048;
        #pragma unroll
        for(int i=0;i<4;i++) sts4f(ra+i*512,acc[i]);
      }
      bar_arrive(1,256);
#define VK(u) ((u)>>2)
      #pragma unroll
      for(int i=0;i<4;i++){ acc[i][0]=acc[i][1]=acc[i][2]=acc[i][3]=0.f; }
      #pragma unroll
      for(int y=0;y<40;y++){
        constexpr int NS_=4*KP;
        const int u=y<8?y:(y<20?y-8+NS_:(y<12+NS_?y-12:y));
        const int sl=(u+40-NS_)&7;
        if(u<NS_){ mma16816(acc[u&3],buf[sl],MB0(VK(u)),MB1(VK(u))); if(u+8<NS_) lds4r(buf[sl],qs+(48-NS_+u)*512); }
        else mma16816(acc[u&3],pw[u],MB0(VK(u)),MB1(VK(u)));
        if(y>=OPF&&y<OPF+8) ldsm4(buf[(y-OPF)&7],os+((y-OPF)&7)*256);
        if(y>=UXP&&y<UXP+4) ldsm4(ux[(y-UXP)>>1][(y-UXP)&1],us+((y-UXP)>>1)*1024+((y-UXP)&1)*256);
      }
      TF(2);
      const uint32_t ra=s16+SM_RED+1536;
      #pragma unroll
      for(int i=1;i<4;i++) sts4f(ra+kq*4096+i*512,acc[i]);
      bar_sync(3,128);
      const float cs=__uint_as_float(lds1(sb+SM_SCL+8+(s&1)*4));
      float4 c1=lds4f(ra+((kq+3)&3)*4096+512), d2=lds4f(ra+((kq+2)&3)*4096+1024), e2=lds4f(ra+((kq+1)&3)*4096+1536);
      const uint32_t p0=pack_bf16(((acc[0][0]+c1.x)+(d2.x+e2.x))*cs,((acc[0][1]+c1.y)+(d2.y+e2.y))*cs), p1=pack_bf16(((acc[0][2]+c1.z)+(d2.z+e2.z))*cs,((acc[0][3]+c1.w)+(d2.w+e2.w))*cs);
      if(UEX) asm volatile("cp.async.bulk.wait_group.read 0;":::"memory");
      bar_arrive(2+UXDEP,256);
      const uint32_t v0=movm(p0), v1=movm(p1);
      const uint32_t off=SM_VMX+(kq>>1)*512+lane*16+(kq&1)*8;
      #pragma unroll
      for(int r=0;r<2;r++) st_async2(rsc[r]+(VC?SM_VMX+kq*256+lane*8:off)+(2-r)*1024,v0,v1,rsc[r]+SM_MB+16);
      sts2(sb+(VC>1?SM_VMX+kq*256+lane*8:off),v0,v1); __syncwarp(); if(lane==0) mbar_arrive(XL);
      TF(5);
      if(OPF>=40){
        #pragma unroll
        for(int i=0;i<8;i++) ldsm4(buf[i],os+i*256);
      }
    } else {
      uint32_t kb[8];
      #pragma unroll
      for(int y=IL;y<10;y++){
        KST(kord(y))
        if(y==7){
          const uint32_t ka=sb+SM_KX+(8*kq+(lane&7))*128+((((lane>>3)^(2*kq))^(lane&7))<<4);
          ldsm4(kb,ka); ldsm4(kb+4,ka^64);
        }
        if(y==XGP) XGET
        if(y==5) XMAX
        if(UEX&&UBP==y+2&&warp!=3) UBULK
      }
      TF(1);
      {
        const uint32_t qa=s16+SM_RED+kq*4096+1024;
        #pragma unroll
        for(int i=0;i<2;i++) stsm4(qa+i*512,pack_bf16(acc[2*i][0],acc[2*i][1]),pack_bf16(acc[2*i][2],acc[2*i][3]),pack_bf16(acc[2*i+1][0],acc[2*i+1][1]),pack_bf16(acc[2*i+1][2],acc[2*i+1][3]));
      }
      TF(2);
      bar_sync(1,256);
      TS(1); TF(3);
      const uint32_t ra=s16+SM_KRED+kq*512;
      const float cs=__uint_as_float(lds1(sb+SM_SCL+8+(s&1)*4));
      float4 a3=lds4f(ra), c3=lds4f(ra+2048), d3=lds4f(ra+4096), e3=lds4f(ra+6144);
      uint32_t q[4][2][4];
      #pragma unroll
      for(int i=0;i<4;i++){ ldsm4t(q[i][0],qrd^(i*256)); ldsm4t(q[i][1],(qrd^(i*256))+8192); }
      const uint32_t p2=pack_bf16(((a3.x+c3.x)+(d3.x+e3.x))*cs,((a3.y+c3.y)+(d3.y+e3.y))*cs), p3=pack_bf16(((a3.z+c3.z)+(d3.z+e3.z))*cs,((a3.w+c3.w)+(d3.w+e3.w))*cs);
      const uint32_t f2=movm(p2), f3=movm(p3);
      ex0=f2; ex1=f3;
      float sc[6][4];
      #pragma unroll
      for(int i=0;i<6;i++){ sc[i][0]=sc[i][1]=sc[i][2]=sc[i][3]=0.f; }
      #pragma unroll
      for(int i=0;i<4;i++)
        #pragma unroll
        for(int jp=0;jp<2;jp++){
          mma16816(sc[(i&1)*2+jp],q[i][jp],kb[2*i],kb[2*i+1]);
          if(i==1) mma16816(sc[4+jp],q[0][jp],f2,f3);
        }
      const uint32_t w0=__float_as_uint(((sc[0][0]+sc[0][2])+(sc[1][0]+sc[1][2]))+((sc[2][0]+sc[2][2])+(sc[3][0]+sc[3][2]))), w1=__float_as_uint(((sc[0][1]+sc[0][3])+(sc[1][1]+sc[1][3]))+((sc[2][1]+sc[2][3])+(sc[3][1]+sc[3][3])));
      const uint32_t w2=__float_as_uint((sc[4][0]+sc[4][2])+(sc[5][0]+sc[5][2])), w3=__float_as_uint((sc[4][1]+sc[4][3])+(sc[5][1]+sc[5][3]));
      if(XB){
        const uint32_t off=SM_SCX+(c*4+kq)*256+lane*8, x0=pack_bf16(__uint_as_float(w0),__uint_as_float(w1)), x1=pack_bf16(__uint_as_float(w2),__uint_as_float(w3));
        #pragma unroll
        for(int r=0;r<2;r++) st_async2(rsc[r]+off,x0,x1,rsc[r]+SM_MB);
        sts2(sb+off,x0,x1);
      } else {
        const uint32_t off=SM_SCX+(c*4+kq)*512+lane*16;
        #pragma unroll
        for(int r=0;r<2;r++) st_async4(rsc[r]+off,w0,w1,w2,w3,rsc[r]+SM_MB);
        sts4(sb+off,make_uint4(w0,w1,w2,w3));
      }
      __syncwarp(); if(lane==0) mbar_arrive(XS);
      if(EKM&&last){
        { char* ep=(char*)g_km+(uint32_t)((NSEG-1)*98304+h*3072+(4*c+kq)*256+((s16-sb)>>2)); stg1(ep,f2); stg1(ep+128,f3); }
        __syncwarp();
        if(lane==0){ fence_rel(); stg_rlx1(g_flag+b*32+1+kq,1); }
      }
      TS(2); TF(5);
    }
      #define UNIT {      \
          const uint4 x=lds4(sb+SM_MX), y=lds4(sb+SM_MX+16); const float cw=__uint_as_float(lds1(sb+SM_SCL+4)), cs=__uint_as_float(lds1(sb+SM_SCL+8+(s&1)*4)); \
          const float mm=__uint_as_float(max(max(max(x.x,x.y),max(x.z,x.w)),max(max(y.x,y.y),max(y.z,y.w))))*cs; \
          const uint32_t eo=min(max((__float_as_uint(cw*fmaxf(mm,1.f))>>23)&255u,37u),254u)-21u; \
          if((UW3>=7?lane==0:tid==64)){ sts1(sb+SM_SCL,eo*0x00800080u); sts1(sb+SM_SCL+12-(s&1)*4,(eo-3u)<<23); } \
        }
    if(!MG&&warp==3){
      bar_arrive(2,256);
      const float ssc=0.07216878364870322f*__uint_as_float(lds1(sb+SM_SCL+8+(s&1)*4));
      uint32_t kvc; asm volatile("ld.relaxed.gpu.global.u32 %0, [%1];":"=r"(kvc):"l"(g_cnt+(ETL&&last?C_QA+RTB:C_KV+(((s>>2)+1)&15))):"memory");
      const uint32_t idn=(lane>>3)==(lane&3)?((lane&4)?0x3f800000u:0x3f80u):0u;
      if(UW3==7&&s) UNIT
      TF(6);
      { int gd=0; while(!mbar_try(XS,s&1)){ if(dead) break; if(++gd>GUARD){ dead=true; g_err=2; } } }
      TF(7);
      float sv[10];
      if(SMM){
        uint32_t x[4][4], y[4][2];
        #pragma unroll
        for(int n=0;n<4;n++){
          const uint2 a_=lds2(sb+lane*8+SM_SCX+n*256), b_=lds2(sb+lane*8+SM_SCX+1024+n*256), c_=lds2(sb+lane*8+SM_SCX+2048+n*256);
          x[n][0]=a_.x; x[n][1]=a_.y; x[n][2]=b_.x; x[n][3]=b_.y; y[n][0]=c_.x; y[n][1]=c_.y;
        }
        float d[4][4];
        #pragma unroll
        for(int n=0;n<4;n++){ d[n][0]=d[n][1]=d[n][2]=d[n][3]=0.f; mma16816(d[n],x[n],idn,idn); }
        #pragma unroll
        for(int n=0;n<4;n++){ mma1688(d[n],y[n][0],y[n][1],idn); sv[2+2*n]=d[n][0]; sv[3+2*n]=d[n][1]; }
        sv[0]=(d[0][2]+d[1][2])+(d[2][2]+d[3][2]); sv[1]=(d[0][3]+d[1][3])+(d[2][3]+d[3][3]);
      } else {
        float4 u[12];
        #pragma unroll
        for(int n=0;n<12;n++){
          if(XB){ const uint2 x=lds2(sb+lane*8+SM_SCX+n*256); u[n]=make_float4(__uint_as_float(x.x<<16),__uint_as_float(x.x&0xffff0000u),__uint_as_float(x.y<<16),__uint_as_float(x.y&0xffff0000u)); }
          else u[n]=lds4f(s16+SM_SCX+n*512);
        }
        #pragma unroll
        for(int n=0;n<4;n++){ sv[2+2*n]=(u[n].x+u[4+n].x)+u[8+n].x; sv[3+2*n]=(u[n].y+u[4+n].y)+u[8+n].y; }
        sv[0]=(((u[0].z+u[1].z)+(u[2].z+u[3].z))+((u[4].z+u[5].z)+(u[6].z+u[7].z)))+((u[8].z+u[9].z)+(u[10].z+u[11].z));
        sv[1]=(((u[0].w+u[1].w)+(u[2].w+u[3].w))+((u[4].w+u[5].w)+(u[6].w+u[7].w)))+((u[8].w+u[9].w)+(u[10].w+u[11].w));
      }
      if(!NRD){
        #pragma unroll
        for(int n=0;n<5;n++){
          const uint32_t r=pack_bf16(sv[2*n],sv[2*n+1]);
          const uint32_t w=pack_bf16(__uint_as_float(r<<16)*ssc,__uint_as_float(r&0xffff0000u)*ssc);
          sv[2*n]=__uint_as_float(w<<16); sv[2*n+1]=__uint_as_float(w&0xffff0000u);
        }
      }
      TF(8);
      float mx=fmaxf(fmaxf(fmaxf(sv[2],sv[3]),fmaxf(sv[4],sv[5])),fmaxf(fmaxf(fmaxf(sv[6],sv[7]),fmaxf(sv[8],sv[9])),fmaxf(sv[0],sv[1])));
      mx=fmaxf(mx,__shfl_xor_sync(~0u,mx,1)); mx=fmaxf(mx,__shfl_xor_sync(~0u,mx,2));
      if(NRD){
        const float k2=ssc*1.4426950408889634f;
        #pragma unroll
        for(int i=0;i<10;i++) sv[i]=ex2((sv[i]-mx)*k2);
      } else {
        mx*=-1.4426950408889634f;
        #pragma unroll
        for(int i=0;i<10;i++) sv[i]=ex2(fmaf(sv[i],1.4426950408889634f,mx));
      }
      sts1(sb+SM_PM+lane*4,pack_bf16(sv[0],sv[1]));
      sts4(s16+SM_P,make_uint4(pack_bf16(sv[2],sv[3]),pack_bf16(sv[4],sv[5]),pack_bf16(sv[6],sv[7]),pack_bf16(sv[8],sv[9])));
      if(UW3==8&&s) UNIT
      TF(9);
      bar_sync(4,256);
      asm volatile("mov.u32 %0, %%clock;":"=r"(t0)); t0+=W3O;
      TF(11);
      if(lane==0){
        mbar_expect(XS,XB?2048:4096); mbar_expect(XV,2048);
        if(ETL&&RTB<16&&last){
          const bool go=b<80&&kvc>=32;
          if(go){
            fence_acq(); fence_async_all();
            const int sq=b/20, seg=RTB*4+sq;
            #pragma unroll 1
            for(int sl=0;sl<4;sl++){
              const uint32_t f=sb+SM_PM+256+sl*8;
              mbar_expect(f,20480); mbar_expect(f,20480);
              asm volatile("cp.async.bulk.tensor.3d.shared::cluster.global.mbarrier::complete_tx::bytes.L2::cache_hint [%0], [%1, {0, %3, %4}], [%2], %5;"::"r"(sb+sl*40960),"l"(&P.u),"r"(f),"r"(b-20*sq),"r"(seg*40+sl*10),"l"(PL_EF):"memory");
              bulk_g2s(sb+sl*40960+20480,g_p+seg*81920+sl*20480,20480,f);
            }
          }
          sts1(sb+SM_PM+240,go?4:0);
        }
        if((s&3)==2){ int gd=0; while(kvc<64&&s<NSEG-4){ kvc=ld_acq(g_cnt+C_KV+(s>>2)+1); if(++gd>GUARD){ g_err=7; break; } } fence_acq(); fence_async_g(); }
      }
      __syncwarp();
      eo2=(uint32_t)(s*98304+h*3072+(4*c+kq)*256+((s16-sb)>>2))^zero;
      TF(13);
    } else {
      if constexpr(!MG){
        #pragma unroll
        for(int i=0;i<2;i++){ ldsm4(ux[i][0],us+i*1024); ldsm4(ux[i][1],us+i*1024+256); }
        if(s==0&&warp==2){
          int gd=0; uint32_t x[6];
          #pragma unroll 1
          while(true){
            bool ok=true;
            #pragma unroll
            for(int i=0;i<6;i++){ asm volatile("ld.relaxed.gpu.global.u32 %0, [%1];":"=r"(x[i]):"l"(g_nrm+lane*6+i):"memory"); ok=ok&&x[i]!=SENT; }
            if(__all_sync(~0u,ok)) break;
            if(++gd>GUARD){ g_err=8; break; }
          }
          const float cw=27.5f*sqrtf((__uint_as_float(x[0])+__uint_as_float(x[2]))+__uint_as_float(x[4]))*sqrtf(__uint_as_float(max(x[1],max(x[3],x[5]))));
          sts1(sb+SM_SCL+4,__reduce_max_sync(~0u,__float_as_uint(cw)&0x7fffffffu));
          __syncwarp();
          if(UW3>=7) UNIT
        }
        if(!UW3) UNIT
        TF(4);
        if(UEX) asm volatile("cp.async.bulk.wait_group.read 0;":::"memory");
        bar_sync(2+UXDEP,256);
        if(!last&&lane==0){
          tma2dh(sb+SM_VX+kq*4096,&tmV,h*DH+64*kq,(s+1)*32,KVB,HV?PL_EF:PL_EN);
          if(kq==0) mbar_expect(KVB,32*512);
          if(kq==1) tma2dh(sb+SM_KX,&tmK,h*DH+64*c,(s+1)*32,KVB,HK?PL_EF:PL_EN);
        }
        __syncwarp();
        if(UW3==2) UNIT
        if(UW3==4&&warp==2) UNIT
      }
      float ca[2][2][4];
      #pragma unroll
      for(int i=0;i<2;i++)
        #pragma unroll
        for(int j=0;j<2;j++){ ca[i][j][0]=ca[i][j][1]=ca[i][j][2]=ca[i][j][3]=0.f; }
      TF(6);
      { int gd=0; while(!mbar_try(XL,s&1)){ if(dead) break; if(++gd>GUARD){ dead=true; g_err=5; } } }
      TF(7);
      uint4 vm[6];
      const uint32_t s8=sb+lane*8+SM_VMX;
      #define VLD(i) { const uint2 a_=lds2(s8+(i)*512), b_=lds2(s8+(i)*512+256); vm[i]=make_uint4(a_.x,a_.y,b_.x,b_.y); }
      if(VC>1){ VLD(0) VLD(1) } else { vm[0]=lds4(s16+SM_VMX); vm[1]=lds4(s16+SM_VMX+512); }
      #define VB0(x) (((x)&1)?vm[(x)>>1].z:vm[(x)>>1].x)
      #define VB1(x) (((x)&1)?vm[(x)>>1].w:vm[(x)>>1].y)
      if constexpr(MG){
        #pragma unroll
        for(int x=0;x<12;x++){
          if(x==4){
            TF(8);
            { int gd=0; while(!mbar_try(XV,s&1)){ if(dead) break; if(++gd>GUARD){ dead=true; g_err=3; } } }
            TF(9);
            #pragma unroll
            for(int i=2;i<6;i++){ if(VC) VLD(i) else vm[i]=lds4(s16+SM_VMX+i*512); }
          }
          #pragma unroll
          for(int i=0;i<2;i++){
            mma16816(ca[i][x&1],buf[(x*2+i)&7],VB0(x),VB1(x));
            if(x<8) ldsm4(buf[(x*2+i)&7],os+(x*2+i+8)*256);
          }
        }
      } else {
        #pragma unroll
        for(int x=0;x<12;x++){
          if(x==4){
            if(UW3==3) UNIT
            if(UW3==5&&warp==2) UNIT
            TF(8);
            { int gd=0; while(!mbar_try(XV,s&1)){ if(dead) break; if(++gd>GUARD){ dead=true; g_err=3; } } }
            TF(9);
            #pragma unroll
            for(int i=2;i<6;i++){ if(VC) VLD(i) else vm[i]=lds4(s16+SM_VMX+i*512); }
          }
          #pragma unroll
          for(int i=0;i<2;i++) mma16816(ca[i][x&1],pw[16+x*2+i],VB0(x),VB1(x));
        }
      }
      if(!MG&&UW3==6) UNIT
      if(FIN>=3){
        #pragma unroll
        for(int i=0;i<2;i++){ um[i][0]=pack_bf16(ca[i][0][0]+ca[i][1][0],ca[i][0][1]+ca[i][1][1]); um[i][1]=pack_bf16(ca[i][0][2]+ca[i][1][2],ca[i][0][3]+ca[i][1][3]); }
      }
      TF(10);
      bar_sync(4+(FIN>=3?((um[0][0]^um[1][1])&zero):0),256);
      TS(3); TF(11);
      const uint4 pq=lds4(s16+SM_P); const uint32_t pm=lds1(sb+SM_PM+lane*4), on=lds1(sb+SM_SCL);
      kvok=mbar_test(KVB,(s&1)^1);
      const uint32_t one[4]={on,on,on,on};
      float d[2][4], e[4];
      #pragma unroll
      for(int i=0;i<4;i++){ d[0][i]=0.f; d[1][i]=0.f; e[i]=0.f; }
      if(FIN==0){
      mma16816(e,one,pq.x,pq.y); mma16816(d[0],ux[0][0],pq.x,pq.y); mma16816(d[1],ux[1][0],pq.x,pq.y);
      mma16816(e,one,pq.z,pq.w); mma16816(d[0],ux[0][1],pq.z,pq.w); mma16816(d[1],ux[1][1],pq.z,pq.w);
      mma1688(e,one[0],one[0],pm);
      #pragma unroll
      for(int i=0;i<2;i++){ um[i][0]=pack_bf16(ca[i][0][0]+ca[i][1][0],ca[i][0][1]+ca[i][1][1]); um[i][1]=pack_bf16(ca[i][0][2]+ca[i][1][2],ca[i][0][3]+ca[i][1][3]); mma1688(d[i],um[i][0],um[i][1],pm); }
      } else if(FIN==1){
        #pragma unroll
        for(int i=0;i<2;i++){ um[i][0]=pack_bf16(ca[i][0][0]+ca[i][1][0],ca[i][0][1]+ca[i][1][1]); um[i][1]=pack_bf16(ca[i][0][2]+ca[i][1][2],ca[i][0][3]+ca[i][1][3]); }
        float e2[4]={0.f,0.f,0.f,0.f};
        mma16816(e,one,pq.x,pq.y); mma16816(e2,one,pq.z,pq.w); mma16816(d[0],ux[0][0],pq.x,pq.y); mma16816(d[1],ux[1][0],pq.x,pq.y);
        mma1688(e,one[0],one[0],pm);
        mma16816(d[0],ux[0][1],pq.z,pq.w); mma16816(d[1],ux[1][1],pq.z,pq.w);
        mma1688(d[0],um[0][0],um[0][1],pm); mma1688(d[1],um[1][0],um[1][1],pm);
        e[0]+=e2[0]; e[1]+=e2[1];
      } else {
        #pragma unroll
        for(int i=0;i<2;i++){ um[i][0]=pack_bf16(ca[i][0][0]+ca[i][1][0],ca[i][0][1]+ca[i][1][1]); um[i][1]=pack_bf16(ca[i][0][2]+ca[i][1][2],ca[i][0][3]+ca[i][1][3]); }
        float e2[4]={0.f,0.f,0.f,0.f}, d2[2][4]={{0.f,0.f,0.f,0.f},{0.f,0.f,0.f,0.f}};
        mma16816(e,one,pq.x,pq.y); mma16816(e2,one,pq.z,pq.w); mma16816(d[0],ux[0][0],pq.x,pq.y); mma16816(d[1],ux[1][0],pq.x,pq.y);
        mma16816(d2[0],ux[0][1],pq.z,pq.w); mma16816(d2[1],ux[1][1],pq.z,pq.w);
        mma1688(e,one[0],one[0],pm);
        mma1688(d[0],um[0][0],um[0][1],pm); mma1688(d[1],um[1][0],um[1][1],pm);
        e[0]+=e2[0]; e[1]+=e2[1];
        #pragma unroll
        for(int i=0;i<8;i++) d[i>>2][i&3]+=d2[i>>2][i&3];
      }
      const float i0=rcp(e[0]), i1=rcp(e[1]);
      TF(12);
      const uint32_t ro=(tile0+2*wt)*512+t*64+g*8;
      char* dst=(char*)g_acc+(uint32_t)((s+1)*20480+ro);
      #pragma unroll
      for(int i=0;i<2;i++){
        if(!last&&(i==0||2*wt+1<ntile)){
          red64(dst+i*512,(__float_as_uint(fmaf(d[i][0],i0,12582912.f))<<6)+1u,__float_as_uint(fmaf(d[i][2],i0,12582912.f))<<3);
          red64(dst+i*512+256,(__float_as_uint(fmaf(d[i][1],i1,12582912.f))<<6)+1u,__float_as_uint(fmaf(d[i][3],i1,12582912.f))<<3);
        }
      }
      asm volatile("mov.u32 %0, %%clock;":"=r"(t0));
      {
        const uint32_t z=t0&zero;
        eo1=(uint32_t)(s*1638400+(32+(h>>2))*40960+(tile0+2*wt)*1024+(h&3)*128+((s16-sb)>>2))^z;
        if(!MG) eo2=(uint32_t)(s*98304+h*3072+(4*c+kq)*256+((s16-sb)>>2))^z;
      }
      TW(1);
      TS(4); TF(13);
    }
    so+=20480;
  }
  if(MG||warp!=3) EXPU
  if(!MG&&!EKM) EXPK
  };
  { if(mg) loop(IC<1>{}); else loop(IC<0>{}); }
  asm volatile("cp.async.bulk.wait_group 0;":::"memory");
  __syncthreads();
  if(tid==FW*32){ fence_rel(); stg_rlx1(g_flag+b*32,NSEG); if(RTB<16) asm volatile("red.relaxed.gpu.global.add.u32 [%0], 1;"::"l"(g_cnt+C_RD):"memory"); }
  GT(2);
  asm volatile("barrier.cluster.arrive.release.aligned;":::"memory");
  if(RTB<16&&b<80){
    const uint32_t TF_=sb+SM_PM+256, TE=TF_+32;
    const int sq=b/20, part=b-20*sq;
    auto cw=[&](int c_,uint32_t thr){ int gd=0; while(ld_acq(g_cnt+c_)<thr){ __nanosleep(20); if(++gd>GUARD){ g_err=10; break; } } };
    auto bw=[&](uint32_t a,uint32_t par){ int gd=0; while(!mbar_try(a,par)){ if(++gd>GUARD){ g_err=11; break; } } };
    if(warp==4||warp==5){
      if(lane==0){
        #pragma unroll 1
        for(int n=ETL?lds1(sb+SM_PM+240):0;n<4*(16-RTB);n++){
          const int rbk=RTB+(n>>2), seg=rbk*4+sq, sl=n&3;
          if(sl==0){ if(warp==4&&rbk==15) cw(C_RD,NCTA); else cw(C_QA+rbk,32); fence_async_all(); TT((warp-4)*2+(rbk&1)); }
          if(n>=4) bw(TE+sl*8,((n>>2)&1)^1);
          mbar_expect(TF_+sl*8,20480);
          if(warp==4) asm volatile("cp.async.bulk.tensor.3d.shared::cluster.global.mbarrier::complete_tx::bytes.L2::cache_hint [%0], [%1, {0, %3, %4}], [%2], %5;"::"r"(sb+sl*40960),"l"(&P.u),"r"(TF_+sl*8),"r"(part),"r"(seg*40+sl*10),"l"(PL_EF):"memory");
          else bulk_g2s(sb+sl*40960+20480,g_p+seg*81920+sl*20480,20480,TF_+sl*8);
        }
      }
      __syncwarp();
    } else if(warp<4){
      #pragma unroll 1
      for(int it=0;it<16-RTB;it++){
        const int rbk=RTB+it;
        const uint32_t go=(uint32_t)(((rbk*4+sq)*32+(tid>>2))*D+part*32+(tid&3)*8);
        uint4 x, gt;
        if(!TRO||it){ cw(C_M2+rbk,4); x=ldg_rlx4((const uint32_t*)(P.x+go)); gt=ldg_rlx4((const uint32_t*)(g_gate+go)); }
        float q[16], q2[16];
        #pragma unroll
        for(int i=0;i<16;i++){ q[i]=0.f; q2[i]=0.f; }
        #pragma unroll 1
        for(int sl=0;sl<4;sl++){
          bw(TF_+sl*8,it&1);
          if(tid==0&&(sl==0||sl==3)) TT(4+(rbk&1)*2+(sl&1));
          const uint32_t sa=((sb+sl*40960)>>4)&0x3fff, da=sa|(8u<<16), db=(sa+1280)|(32u<<16);
          asm volatile("wgmma.fence.sync.aligned;":::"memory");
          #pragma unroll
          for(int j=0;j<20;j++) wg32_pu((TQ2&&(j&1))?q2:q,da+(j>>1)*128+(j&1)*16,db+j*64,TQ2?sl|(j>>1):sl|j);
          asm volatile("wgmma.commit_group.sync.aligned;":::"memory");
          asm volatile("wgmma.wait_group.sync.aligned 0;":::"memory");
          if(lane==0) mbar_arrive(TE+sl*8);
        }
        if(TRO&&!it){ cw(C_M2+rbk,4); x=ldg_rlx4((const uint32_t*)(P.x+go)); gt=ldg_rlx4((const uint32_t*)(g_gate+go)); }
        if(TQ2){
          #pragma unroll
          for(int i=0;i<16;i++) q[i]+=q2[i];
        }
        const uint32_t sg=sb+SM_KRED+(it&1)*4096;
        if(warp<2){
          const uint32_t wa=sg+((lane>>4)*8+(lane&7))*128+(((2*warp+((lane>>3)&1))^(lane&7))<<4);
          #pragma unroll
          for(int i=0;i<2;i++) stsm4t(wa+i*2048,pack_bf16(q[8*i],q[8*i+1]),pack_bf16(q[8*i+2],q[8*i+3]),pack_bf16(q[8*i+4],q[8*i+5]),pack_bf16(q[8*i+6],q[8*i+7]));
        }
        bar_sync(1,128);
        const uint4 u=lds4(sg+(tid>>2)*128+(((tid&3)^((tid>>2)&7))<<4));
        *(uint4*)(P.out+go)=make_uint4(fin1(u.x,x.x,gt.x),fin1(u.y,x.y,gt.y),fin1(u.z,x.z,gt.z),fin1(u.w,x.w,gt.w));
      }
    }
  }
  GT(3);
  asm volatile("barrier.cluster.wait.acquire.aligned;":::"memory");
}
#define E14 4
#define ONES 1
#define ONE15 1
#define PPU 0
#define PRC 0
#define ALT 0
#define WMJ 1
#define WMW 1
#define KVX 500
#define NUO 0
#define PFI 0
#define PFO 0
#define KLEAD 16
#define MLEAD 16
#define FAG fence_async_g
#define KVQ 1024
#define ROT 38
#define ROT0 3
#define FNS 40
#define CONT 1
enum { M_XN=0,M_WK,M_WV,M_K,M_V,M_Y,M_H,M_H2,M_GATE,M_WQ,M_W1,M_W2,M_W2B,M_U1,M_U2,M_U5,M_U10,M_NUM,M_OUT };
struct WParams { CUtensorMap m[M_NUM]; const bf16* x; const bf16* b1; const bf16* b2; bf16* out; int pair; const char* wq; const char* wo; };
enum { T_RED=0,T_OP=1,T_QA=2,T_M2=3,T_M1=4,T_KV=5,T_END=6 };
#define KVR 6
#define KVJ 32
constexpr int KVUP=128*KVR;
#define TRIG 10
#define SOV 1
#define LATE 15
#define E15 6
#define OPE 15
#define Q15 3
#define HB 1
#define EARLY 3
constexpr int NRB=16;
constexpr int STG=45056, NST=4, SLOT=24576, BOXS=8192;
constexpr int W_SLOT=NST*STG;
constexpr int W_BAR=W_SLOT+2*SLOT;
constexpr int W_TOTAL=W_BAR+1024;
static_assert(W_TOTAL<=232448,"smem");
#define ST(i)
#define QT(i)
__device__ __forceinline__ void stsm4n(uint32_t a,uint32_t r0,uint32_t r1,uint32_t r2,uint32_t r3){ asm volatile("stmatrix.sync.aligned.m8n8.x4.shared.b16 [%0], {%1,%2,%3,%4};"::"r"(a),"r"(r0),"r"(r1),"r"(r2),"r"(r3)); }
#define WGUARD 2000000
__host__ __device__ constexpr int n_uns(){ int n=0; while(n<16&&nsp(n)==1) n++; return n; }
__host__ __device__ constexpr int n_op(){ int n=0; for(int r=0;r<NRB;r++) n+=4*nsp(r); return n; }
__host__ __device__ constexpr int n_red(){ return 0; }
__host__ __device__ constexpr int pu_st(int ns){ return ns==1?40:(ns==2?20:(ns==5?10:8)); }

__device__ __forceinline__ void wg_arrive(){ asm volatile("wgmma.fence.sync.aligned;":::"memory"); }
__device__ __forceinline__ void wg_commit(){ asm volatile("wgmma.commit_group.sync.aligned;":::"memory"); }
template<int N> __device__ __forceinline__ void wg_wait(){ asm volatile("wgmma.wait_group.sync.aligned %0;"::"n"(N):"memory"); }
__device__ __forceinline__ void mbar_wait(uint32_t a,uint32_t par){ int gd=0; while(!mbar_try(a,par)){ if(++gd>WGUARD){ g_err=20; break; } } }
__device__ __forceinline__ uint32_t ld_rlx(const uint32_t* p){ uint32_t v; asm volatile("ld.relaxed.gpu.global.u32 %0, [%1];":"=r"(v):"l"(p):"memory"); return v; }
__device__ __forceinline__ float4 ld_rlx4f(const float4* p){ float4 v; asm volatile("ld.relaxed.gpu.global.v4.f32 {%0,%1,%2,%3}, [%4];":"=f"(v.x),"=f"(v.y),"=f"(v.z),"=f"(v.w):"l"(p):"memory"); return v; }
__device__ __forceinline__ void tma_st(const CUtensorMap* tm,uint32_t src,int c0,int c1){
  asm volatile("cp.async.bulk.tensor.2d.global.shared::cta.bulk_group [%0, {%2, %3}], [%1];"::"l"(tm),"r"(src),"r"(c0),"r"(c1):"memory"); }
#define KEF 4
__device__ __forceinline__ void tma_st_ef(const CUtensorMap* tm,uint32_t src,int c0,int c1){
  asm volatile("{\n.reg .b64 pl;\ncreatepolicy.fractional.L2::evict_first.b64 pl, 1.0;\ncp.async.bulk.tensor.2d.global.shared::cta.bulk_group.L2::cache_hint [%0, {%2, %3}], [%1], pl;\n}"::"l"(tm),"r"(src),"r"(c0),"r"(c1):"memory"); }
__device__ __forceinline__ void bulk_commit(){ asm volatile("cp.async.bulk.commit_group;":::"memory"); }
__device__ __forceinline__ void bulk_wait_rd(){ asm volatile("cp.async.bulk.wait_group.read 0;":::"memory"); }
__device__ __forceinline__ void bulk_wait(){ asm volatile("cp.async.bulk.wait_group 0;":::"memory"); }
__device__ __forceinline__ void mbar_arrive_cl(uint32_t a){ asm volatile("mbarrier.arrive.shared::cluster.b64 _, [%0];"::"r"(a):"memory"); }
__device__ __forceinline__ void tma4d(uint32_t dst,const CUtensorMap* tm,int c2,int c3,uint32_t mb){
  asm volatile("cp.async.bulk.tensor.4d.shared::cluster.global.mbarrier::complete_tx::bytes [%0], [%1, {0, 0, %3, %4}], [%2];"::"r"(dst),"l"(tm),"r"(mb),"r"(c2),"r"(c3):"memory"); }
__device__ __forceinline__ void tma4dm(uint32_t dst,const CUtensorMap* tm,int c2,int c3,uint32_t mb){
  asm volatile("cp.async.bulk.tensor.4d.shared::cluster.global.mbarrier::complete_tx::bytes.multicast::cluster [%0], [%1, {0, 0, %3, %4}], [%2], %5;"::"r"(dst),"l"(tm),"r"(mb),"r"(c2),"r"(c3),"h"((uint16_t)3):"memory"); }

template<int N> __device__ __forceinline__ void mainloop(float* acc,int nkb,uint32_t sb,int lane,uint32_t pos,uint32_t eb){
  uint32_t pst=0;
  #pragma unroll
  for(int i=0;i<N/2;i++){ acc[i]=0.f; acc[96+i]=0.f; }
  #pragma unroll 1
  for(int kb=0;kb<nkb;kb++,pos++){
    const uint32_t st=pos&3;
    mbar_wait(sb+W_BAR+st*8,(pos>>2)&1);
    if(kb==nkb-1&&(threadIdx.x&127)==0) mbar_arrive(sb+W_BAR+144);
    const uint32_t a=sb+st*STG;
    const uint32_t da=((a>>4)&0x3fff)|(1u<<16);
    const uint32_t db=da+1024+(255u<<16);
    wg_arrive();
    #pragma unroll
    for(int k=0;k<4;k++){ wgmma<N>(acc,da+2*k,db+(k>>1)*N*4+(k&1)*128,kb|k); wgmma<N>(acc+96,da+512+2*k,db+(k>>1)*N*4+(k&1)*128,kb|k); }
    wg_commit();
    if(kb>0){ wg_wait<1>(); if(lane<2) mbar_arrive_cl(eb+pst*8); }
    pst=st;
  }
  wg_wait<0>();
  if(lane<2) mbar_arrive_cl(eb+pst*8);
}
__device__ __forceinline__ uint32_t act2(uint32_t u,uint32_t bb,float c1,float c3){
  uint32_t s; asm("add.rn.bf16x2 %0, %1, %2;":"=r"(s):"r"(u),"r"(bb));
  float r[2]={__uint_as_float(s<<16), __uint_as_float(s&0xffff0000u)};
  #pragma unroll
  for(int i=0;i<2;i++){
    const float z=r[i]*fmaf(r[i]*r[i],c3,c1);
    r[i]=r[i]*rcp(1.f+ex2(z));
  }
  return pack_bf16(r[0],r[1]);
}
template<int NT> __device__ __forceinline__ void stage_pk(const uint32_t* p,uint32_t ra,int lane){
  const int sw=lane&7, hi=lane>>4;
  #pragma unroll
  for(int T=0;T<NT;T++) stsm4n(ra+(T>>2)*BOXS+((((2*T+hi)&7)^sw)<<4),p[4*T],p[4*T+1],p[4*T+2],p[4*T+3]);
}
__device__ __noinline__ void post_pass(uint32_t sl,int nbox,uint32_t ba,float c1,float c3){
  const int lane=threadIdx.x&31, r=lane>>3, c=lane&7;
  __syncwarp();
  #pragma unroll 1
  for(int j=0;j<nbox;j++){
    uint4 u[4]; uint32_t a[4];
    #pragma unroll
    for(int i=0;i<4;i++){ const int rr=4*i+r; a[i]=sl+j*BOXS+rr*128+((c^(rr&7))<<4); u[i]=lds4(a[i]); }
    const uint4 bb=lds4(ba+j*128+c*16);
    #pragma unroll
    for(int i=0;i<4;i++){
      uint4& v=u[i];
      v.x=act2(v.x,bb.x,c1,c3); v.y=act2(v.y,bb.y,c1,c3); v.z=act2(v.z,bb.z,c1,c3); v.w=act2(v.w,bb.w,c1,c3);
      sts4(a[i],v);
    }
  }
}
__device__ __forceinline__ void wg16_rs(float* d,const uint32_t* a,uint32_t db,int sc){
  asm volatile("{\n.reg .pred p;\n.reg .b64 xb;\nmov.b64 xb, {%12, 192};\nsetp.ne.b32 p, %13, 0;\nwgmma.mma_async.sync.aligned.m64n16k16.f32.bf16.bf16 {%0,%1,%2,%3,%4,%5,%6,%7}, {%8,%9,%10,%11}, xb, p, 1, 1, 0;\n}"
   :"+f"(d[0]),"+f"(d[1]),"+f"(d[2]),"+f"(d[3]),"+f"(d[4]),"+f"(d[5]),"+f"(d[6]),"+f"(d[7]):"r"(a[0]),"r"(a[1]),"r"(a[2]),"r"(a[3]),"r"(db),"r"(sc));
}
template<int NS> __device__ __forceinline__ void pu_item(const WParams& P,int rbk,int a,uint32_t pos,uint32_t sb,int tid,uint32_t& e0,int& sq){
  constexpr int MT=10/NS, NKB=pu_st(NS), BPS=40/NKB, H0=(MT+1)/2;
  const int lane=tid&31, wg=tid>>7, wq=(tid>>5)&3;
  const int seg=rbk*4+a/NS, part=a%NS;
  const uint32_t go=(uint32_t)((seg*32+wq*8+(lane>>3))*D+part*MT*64+(lane&7)*8);
  uint4 xx[MT][2], gg[MT][2];
  auto ldx=[&](int m){
    #pragma unroll
    for(int j=m*H0;j<m*H0+H0&&j<MT;j++)
      #pragma unroll
      for(int i=0;i<2;i++){ const uint32_t o=go+i*4*D+j*64; xx[j][i]=ldg_rlx4((const uint32_t*)(P.x+o)); gg[j][i]=ldg_rlx4((const uint32_t*)(g_gate+o)); }
  };
  if(NS>1){ ldx(0); ldx(1); }
  float acc[MT][16];
  #pragma unroll
  for(int i=0;i<MT*16;i++) acc[i>>4][i&15]=0.f;
  uint32_t pst=0;
  #pragma unroll 1
  for(int kb=0;kb<NKB;kb++,pos++){
    const uint32_t st=pos&3;
    mbar_wait(sb+W_BAR+st*8,(pos>>2)&1);
    if(kb==NKB-1&&(tid&127)==0) mbar_arrive(sb+W_BAR+144);
    const uint32_t sa=((sb+st*STG)>>4)&0x3fff, da=sa|(8u<<16), db=(sa+BPS*MT*256)|(32u<<16);
    wg_arrive();
    #pragma unroll
    for(int j=0;j<BPS;j++)
      #pragma unroll
      for(int k=0;k<2;k++)
        #pragma unroll
        for(int m=0;m<MT;m++) wg32_pu(acc[m],da+(j*MT+m)*256+k*16,db+j*128+k*64,kb|j|k);
    wg_commit();
    if(kb>0){ wg_wait<1>(); if(lane<2) mbar_arrive(sb+W_BAR+32+pst*8); }
    pst=st;
  }
  wg_wait<0>();
  if(lane<2) mbar_arrive(sb+W_BAR+32+pst*8);
  const uint32_t wa=sb+W_SLOT+((lane>>4)*8+(lane&7))*128+(((2*wq+((lane>>3)&1))^(lane&7))<<4);
  const uint32_t rd=sb+W_SLOT+(wq*8+(lane>>3))*128+(((lane&7)^(lane>>3))<<4);
  #pragma unroll
  for(int m=0;m<2;m++){
    mbar_wait(sb+W_BAR+96+wg*16+m*8,e0);
    if(m*H0<MT){
      #pragma unroll
      for(int j=0;j<H0&&m*H0+j<MT;j++){ const float* q=acc[m*H0+j<MT?m*H0+j:0];
        #pragma unroll
        for(int i=0;i<2;i++) stsm4t(wa+m*SLOT+j*4096+i*2048,pack_bf16(q[8*i],q[8*i+1]),pack_bf16(q[8*i+2],q[8*i+3]),pack_bf16(q[8*i+4],q[8*i+5]),pack_bf16(q[8*i+6],q[8*i+7])); }
      if(NS==1) ldx(m);
      bar_sync(8+wg,128);
      #pragma unroll
      for(int j=0;j<H0&&m*H0+j<MT;j++)
        #pragma unroll
        for(int i=0;i<2;i++){
          const uint4 u=lds4((rd^(i*64))+m*SLOT+j*4096+i*512), x=xx[m*H0+j<MT?m*H0+j:0][i], g=gg[m*H0+j<MT?m*H0+j:0][i];
          *(uint4*)(P.out+go+i*4*D+(m*H0+j)*64)=make_uint4(fin1(u.x,x.x,g.x),fin1(u.y,x.y,g.y),fin1(u.z,x.z,g.z),fin1(u.w,x.w,g.w));
        }
    }
    bar_arrive(sq,160); sq^=1;
  }
  e0^=1;
}
template<int N> __device__ __forceinline__ void gemm_item(int type,uint32_t pos,uint32_t sb,int tid,uint32_t ra,uint32_t& e0,uint32_t& eb,int& sq,uint32_t em){
  const int lane=tid&31, wg=tid>>7;
  const uint32_t E0=sb+W_BAR+96+wg*16;
  float acc[192];
  mainloop<N>(acc,type==T_M2?24:10,sb,lane,pos,em);
  uint32_t p[2][N/4];
  #pragma unroll
  for(int m=0;m<2;m++)
    #pragma unroll
    for(int i=0;i<N/4;i++) p[m][i]=pack_bf16(acc[96*m+2*i],acc[96*m+2*i+1]);
  const float c1=type==T_M1?-2.302208198144325f:-1.4426950408889634f, c3=type==T_M1?-0.10294323958f:0.f;
  const int wq=(tid>>5)&3;
  if(type!=T_KV){ mbar_wait(sb+W_BAR+224+wg*8,eb); eb^=1; }
  #pragma unroll
  for(int m=0;m<2;m++){
    mbar_wait(E0+m*8,e0);
    stage_pk<N/16>(p[m],ra+m*SLOT,lane);
    if(type!=T_KV) post_pass(sb+W_SLOT+m*SLOT+wq*2048,N/64,sb+W_BAR+256+wg*384,c1,c3);
    fence_async();
    bar_arrive(sq,160); sq^=1;
  }
  e0^=1;
}
__device__ __forceinline__ int n_it(int c,int r){ return c==T_OP?4*nsp(r):(c==T_QA?32:(c==T_M2?4:(r?0:(c==T_M1?128:(c==T_KV?(1024-KVUP)/2:0))))); }
__device__ __forceinline__ void flag_wait(int rbk,int a,int lane){
  const bool e=EKM&&rbk==NRB-1;
  const uint32_t need=e?1:4*rbk+4; const uint32_t* f=g_flag+a*96+(lane%3)*32+(e?1+lane/3:0); int gd=0;
  while(!__all_sync(~0u,lane>=(e?12:3)||ld_acq(f)>=need)){ __nanosleep(FNS); if(++gd>WGUARD){ g_err=22; break; } }
}
__device__ __forceinline__ void cnt_wait(int c,uint32_t thr){
  int gd=0;
  while(ld_acq(g_cnt+c)<thr){ __nanosleep(40); if(++gd>WGUARD){ g_err=23; break; } }
}
__global__ void __launch_bounds__(384,1) k_work(const __grid_constant__ WParams P){
  extern __shared__ __align__(1024) uint8_t sm[];
  const uint32_t sb=(uint32_t)__cvta_generic_to_shared(sm);
  const int tid=threadIdx.x, warp=__shfl_sync(~0u,tid>>5,0), lane=tid&31;
  const uint32_t FULL=sb+W_BAR, EMPTY=sb+W_BAR+32, IFULL=sb+W_BAR+64, IEMPTY=sb+W_BAR+80, EF=sb+W_BAR+96, REQ=sb+W_BAR+128, TOK=sb+W_BAR+136;
  volatile int* idesc=(volatile int*)(sm+W_BAR+160);
  if(tid==352) ST(0);
  if(tid==0){
    for(int i=0;i<NST;i++){ mbar_init(FULL+i*8,1); mbar_init(EMPTY+i*8,8); mbar_init(EF+i*8,1); }
    for(int i=0;i<2;i++){ mbar_init(IFULL+i*8,1); mbar_init(IEMPTY+i*8,6); mbar_init(sb+W_BAR+224+i*8,1); }
    mbar_init(REQ,1); mbar_init(TOK,1); mbar_init(sb+W_BAR+144,1);
    { mbar_init(sb+W_BAR+240,1); mbar_init(sb+W_BAR+248,1); uint32_t sm_; asm volatile("mov.u32 %0, %%smid;":"=r"(sm_)); idesc[6]=sm_; }
    asm volatile("fence.mbarrier_init.release.cluster;":::"memory");
  }
  {
    bool done=false;
    if(!P.pair&&tid==32) done=(int)ld_rlx(g_cnt+C_NEXT+T_OP*32+RTB-1)>=n_it(T_OP,RTB-1)&&(int)ld_rlx(g_cnt+C_NEXT+T_QA*32+NRB-1)>=n_it(T_QA,NRB-1)&&(int)ld_rlx(g_cnt+C_NEXT+T_M2*32+NRB-1)>=n_it(T_M2,NRB-1);
    if(__syncthreads_or(done)) return;
  }
  #define S0(i)
  S0(0)
  if(P.pair) cluster_sync();
  S0(1)
  S0(2)
  if(warp>=8){
    asm volatile("setmaxnreg.dec.sync.aligned.u32 40;");
    if(warp==11){
      uint32_t it=0, pos=0;
      auto publish=[&](int type,int rbk,int a,int erl){
        if(lane==0){
          const uint32_t sl=it&1;
          int idx=0;
          if(type==T_KV){
            if(WMJ&&a>=KVUP){ const int j=(a-KVUP)>>1, q=j/(8-KVR); rbk=2*(KVR+j-q*(8-KVR))+(a&1); a=q; }
            else if(a<128*WMW){ const int j=a>>1, q=j/WMW; rbk=2*(j-q*WMW)+(a&1); a=q; }
            else { rbk=2*(a>>7)+(a&1); a=(a>>1)&63; }
          }
          if(type==T_M1){ rbk=a>>3; a&=7; }
          mbar_wait(IEMPTY+sl*8,((it>>1)&1)^1);
          idesc[sl*8]=type; idesc[sl*8+1]=rbk; idesc[sl*8+2]=a; idesc[sl*8+3]=pos; idesc[sl*8+4]=idx; idesc[sl*8+5]=erl;
          mbar_arrive(IFULL+sl*8);
          pos+=type==T_M2?24:(type==T_OP?pu_st(nsp(rbk)):10);
        }
        __syncwarp();
        it++;
      };
      bool fin=false, rq=false;
      if(P.pair){
        const uint32_t i0=blockIdx.x<128?KVR:0;
        int quota=0, tk;
        while(true){
          if(it) mbar_wait(REQ,(it&1)^1);
          if(it<i0) tk=it*128+((blockIdx.x+(it>=ROT0?(it-ROT0+1)*ROT:0))&127);
          else {
            const uint32_t mb=sb+W_BAR+240+(it&1)*8;
            tk=4096;
            if(blockIdx.x&1){
              int gd=0; while(!mbar_try_cl(mb,((it-i0)>>1)&1)){ if(++gd>WGUARD){ g_err=24; break; } }
              tk=idesc[(it&1)*8+7];
            } else {
              if(it==i0){
                asm volatile("griddepcontrol.wait;":::"memory");
                uint32_t o; asm volatile("ld.shared::cluster.u32 %0, [%1];":"=r"(o):"r"(mapa(sb+W_BAR+160+24,1)):"memory");
                const uint32_t m=idesc[6]; uint32_t q=KVQ+KVR-i0;
                #pragma unroll
                for(int i=0;i<3;i++){ const uint32_t v=ld_rlx(g_sml+lane+32*i); if(v==m||v==o) q=min(q,KVR-i0+(lane+32*i<3*KVJ?0:1)); }
                quota=__reduce_min_sync(~0u,q);
              }
              if(lane==0){
                const bool go=CONT&&quota>512&&ld_rlx(g_flag)>1;
                if(go&&quota<=1024-KVX) tk=4097;
                else if(quota--){ tk=(int)atomicAdd(g_cnt+C_NEXT+T_KV*32,1u); if(tk>=n_it(T_KV,0)) tk=go?4097:4096; }
                asm volatile("st.shared::cluster.u32 [%0], %1;\nmbarrier.arrive.release.cluster.shared::cluster.b64 _, [%2];"::"r"(mapa(sb+W_BAR+160+(it&1)*32+28,1)),"r"(tk),"r"(mapa(mb,1)):"memory");
              }
              tk=__shfl_sync(~0u,tk,0);
            }
            if(tk>=4096) break;
            tk=KVUP+2*tk+(blockIdx.x&1);
          }
          if(PFI&&it==PFI&&i0&&lane<15){
            asm volatile("cp.async.bulk.prefetch.L2.global [%0], 4096;"::"l"(P.wq+(blockIdx.x*15+lane)*4096):"memory");
            if(PFO) asm volatile("cp.async.bulk.prefetch.L2.global [%0], 4096;"::"l"(P.wo+(blockIdx.x*15+lane)*4096):"memory");
          }
          publish(T_KV,0,tk,2);
        }
        if(tk==4096){ publish(T_END,0,0,0); fin=true; }
      }
      int guard=0;
      const int cl=lane>>2, cj=lane&3;
      int sidx=-1, nit=0, ltp=-1, lrb=0;
      if(lane==0) ST(1);
      while(true){
        int type=T_END, rbk=0, a=0, erl=0;
        if(!fin){
          if(rq) mbar_wait(REQ,(it&1)^1);
          rq=true;
          if(sidx>=0){ type=T_KV; a=sidx; sidx=-1; }
          else {
            while(true){
              const uint4 nx=ldg_rlx4(g_cnt+C_NEXT+cl*32+cj*4);
              int cand=(int)nx.x<n_it(cl,4*cj)?4*cj*4096+nx.x:((int)nx.y<n_it(cl,4*cj+1)?(4*cj+1)*4096+nx.y:((int)nx.z<n_it(cl,4*cj+2)?(4*cj+2)*4096+nx.z:((int)nx.w<n_it(cl,4*cj+3)?(4*cj+3)*4096+nx.w:65536)));
              cand=min(cand,__shfl_xor_sync(~0u,cand,1)); cand=min(cand,__shfl_xor_sync(~0u,cand,2));
              const int cr=cand>>12, ca=cand&4095, qr=__shfl_sync(~0u,cr,4*T_QA);
              const bool has=cr<NRB;
              if(lane==0&&nit==0) ST(5);
              const uint32_t* fp=nullptr; uint32_t thr=0, sl1=0; bool only1=false, no1=cl>=T_M2;
              if(has&&cl<=T_M2){
                if(cl==T_QA){ if(cj<3){ fp=g_flag+ca*96+cj*32; thr=4*cr+4; sl1=cr==NRB-1?E15:(cr==NRB-2?E14:EARLY); } else { fp=g_cnt+C_KV+min(cr+1,NRB-1); thr=64; only1=true; } }
                else if(cj==0){ fp=g_cnt+(cl==T_OP?C_QA:C_M1)+cr; thr=cl==T_OP?32:8; sl1=thr; }
                else if(cj==1){ if(cl==T_OP){ fp=g_cnt+C_M2+cr; thr=4; } if(cr<OPE||qr<=cr) no1=true; }
              }
              __syncwarp();
              if(lane==0&&nit==0) ST(2);
              uint32_t v=0; if(fp) v=ld_acq(fp);
              __syncwarp();
              if(lane==0&&nit==0) ST(3+(v&0));
              nit++;
              uint32_t b2=__ballot_sync(~0u,has&&(v>=thr||only1)), b1=__ballot_sync(~0u,has&&!no1&&v+sl1>=thr);
              b2&=b2>>1; b2&=b2>>2; b1&=b1>>1; b1&=b1>>2;
              b2&=0x111111u; b1&=0x111u;
              if(ONE15&&lrb==NRB-1) b1&=~(1u<<(4*T_QA));
              if(!__ballot_sync(~0u,has)) break;
              if(b2|b1){
                const int rs=(int)__shfl_sync(~0u,v,4*T_QA);
                const uint32_t bu=__ballot_sync(~0u,cl<=T_QA||qr>=NRB||(cl==T_KV?2*((2*ca+KVUP)>>7)<=(rs>>2)+KLEAD:(cl==T_M1?ca>>3:cr)<=qr+MLEAD));
                int got=-1;
                while(got<0&&(b2|b1)){
                  uint32_t bb=(b2&bu)?(b2&bu):(b1?b1:b2);
                  if(Q15&&(((b1|b2)>>(4*T_QA))&1)&&qr>=NRB-Q15) bb=1u<<(4*T_QA);
                  if(NUO&&!((bu>>(4*T_KV))&1)&&(bb&0x0fffffu)) bb&=0x0fffffu;
                  if(NUO>1&&(bb&0x0fffu)&&!(NUO>2&&((bb>>(4*T_KV))&1))) bb&=0x0fffu;
                  if(ALT&&ltp==T_M1&&(bb&~(1u<<(4*T_M1)))) bb&=~(1u<<(4*T_M1));
                  if(ALT>1&&ltp!=T_M1&&ltp!=T_QA&&((bb>>(4*T_M1))&1)&&!((bb>>(4*T_KV))&1)) bb=1u<<(4*T_M1);
                  #define RD(c) ((bb>>(4*(c)))&1)
                  const int w=RD(T_KV)?T_KV:(RD(T_M2)?T_M2:(RD(T_M1)?T_M1:(RD(T_OP)?T_OP:T_QA)));
                  if(lane==4*w){ const int tk=(int)atomicAdd(g_cnt+C_NEXT+cl*32+cr,1u); if(tk<n_it(cl,cr)) got=cr*4096+(cl==T_KV?KVUP+2*tk:tk)+(tk!=ca?65536:0); }
                  got=__shfl_sync(~0u,got,4*w);
                  if(got>=0){ type=w; rbk=(got>>12)&15; a=got&4095; if(w==T_KV) sidx=a+1; erl=!((b2>>(4*w))&1)||(w==T_QA&&got>=65536); }
                  b2&=~(1u<<(4*w)); b1&=~(1u<<(4*w));
                }
                if(got>=0) break;
              } else {
                __nanosleep(100);
                if(++guard>WGUARD){ g_err=21; break; }
              }
            }
          }
        }
        __syncwarp();
        publish(type,rbk,a,erl); if(ONE15>0) ltp=(type==T_QA&&erl)||(ONES&&ltp==T_QA+16&&lrb==NRB-1)?T_QA+16:type; else ltp=type; if(type==T_QA) lrb=rbk;
        if(type==T_END){ if(fin) break; fin=true; }
      }
    } else if(warp==8){
      if(lane==0){
        uint32_t st=0, ph=1;
        for(uint32_t it=0;;it++){
          const uint32_t sl=it&1;
          mbar_wait(IFULL+sl*8,(it>>1)&1);
          const int type=idesc[sl*8], rbk=idesc[sl*8+1], a=idesc[sl*8+2], erl=idesc[sl*8+5];
          mbar_arrive(IEMPTY+sl*8);
          if(type==T_END) break;
          if(type==T_OP){
            const int ns=nsp(rbk), nkb=pu_st(ns), bps=40/nkb, ub=40960/ns, seg=rbk*4+a/ns, trig=rbk>=LATE?nkb-1:max(nkb-TRIG,0);
            const uint8_t* pp=g_p+seg*81920; const CUtensorMap* um=&P.m[ns==1?M_U1:(ns==2?M_U2:(ns==5?M_U5:M_U10))]; const int c1=(a%ns)*(20/ns);
            if(erl) cnt_wait(C_QA+rbk,32);
            FAG();
            for(int kb=0;kb<nkb;kb++){
              mbar_wait(EMPTY+st*8,ph);
              const uint32_t d=sb+st*STG, fb=FULL+st*8;
              mbar_expect(fb,bps*(ub+2048));
              asm volatile("cp.async.bulk.tensor.3d.shared::cluster.global.mbarrier::complete_tx::bytes.L2::cache_hint [%0], [%1, {0, %3, %4}], [%2], %5;"::"r"(d),"l"(um),"r"(fb),"r"(c1),"r"(seg*40+kb*bps),"l"(PL_EF):"memory");
              bulk_g2s(d+bps*ub,pp,bps*2048,fb); pp+=bps*2048;
              if(kb==trig) mbar_arrive(REQ);
              if(++st==NST){ st=0; ph^=1; }
            }
            continue;
          }
          int ma=M_XN,mb,cg=a*3,nkb=10,nbox=3; const int row0=rbk*128;
          if(type==T_KV){ mb=a<32?M_WK:M_WV; cg=(a&31)*3; }
          else if(type==T_M1){ ma=M_Y; mb=M_W1; }
          else if(type==T_QA){ mb=M_WQ; }
          else {
            const int nt=a&3; cg=nt<2?nt*3:2+nt*2; nbox=nt<2?3:2;
            ma=M_H2; mb=nt<2?M_W2:M_W2B; nkb=24;
          }
          if(erl!=2) FAG();
          const CUtensorMap* A=&P.m[ma]; const CUtensorMap* B=&P.m[mb];
          const int trig=(type<=T_QA&&rbk>=LATE)?nkb-1:max(nkb-TRIG,0), r=rbk&1, f0=(erl==2&&it==0)?NST:0;
          for(int kb=0;kb<nkb;kb++){
            mbar_wait(EMPTY+st*8,ph);
            const uint32_t d=sb+st*STG, fb=FULL+st*8;
            mbar_expect(fb,16384+nbox*8192);
            if(kb>=f0) tma2d(d,A,kb*64,row0,fb);
            if(erl==2) tma4dm(d+16384+r*12288,B,cg,2*kb+r,fb);
            else { tma4d(d+16384,B,cg,2*kb,fb); if(type==T_KV) tma4d(d+28672,B,cg,2*kb+1,fb); }
            if(kb==trig) mbar_arrive(REQ);
            if(kb==f0-1){
              asm volatile("griddepcontrol.wait;":::"memory"); asm volatile("griddepcontrol.launch_dependents;");
              for(int i=0;i<NST;i++) tma2d(sb+i*STG,A,i*64,row0,FULL+i*8);
            }
            if(++st==NST){ st=0; ph^=1; }
          }
        }
      }
      __syncwarp();
    } else if(warp<11){
      const int wg=warp-9;
      const uint32_t S0=sb+W_SLOT, E0=EF+wg*16; int sq=4+2*wg;
      for(uint32_t it=wg;;it+=2){
        mbar_wait(IFULL+wg*8,(it>>1)&1);
        const int type=idesc[wg*8], rbk=idesc[wg*8+1], a=idesc[wg*8+2], erl=idesc[wg*8+5];
        __syncwarp();
        if(lane==0) mbar_arrive(IEMPTY+wg*8);
        if(type==T_END) break;
        const int row0=rbk*128;
        int map=-1,col0=a*192,nbox=3,cnt=-1;
        if(type==T_KV){ map=a<32?M_K:M_V; col0=(a&31)*192; cnt=C_KV+rbk; }
        else if(type==T_M1){ map=M_H; cnt=C_M1+rbk; }
        else if(type==T_M2){ const int nt=a&3; col0=nt<2?nt*192:128+nt*128; nbox=nt<2?3:2; map=M_GATE; cnt=C_M2+rbk; }
        else if(type==T_OP) map=M_OUT;
        if((type==T_M1||type==T_M2)&&lane==0){ const uint32_t bb=sb+W_BAR+224+wg*8; mbar_expect(bb,nbox*128); bulk_g2s(sb+W_BAR+256+wg*384,(type==T_M1?P.b1:P.b2)+col0,nbox*128,bb); }
        const char* kp=(const char*)g_km+(uint32_t)(rbk*393216+a*3072);
        if(it&&lane==0) mbar_wait(TOK,(it&1)^1);
        if(map<0){
          if(lane==0){
            FAG();
            for(int m=0;m<2;m++){
              mbar_expect(E0+m*8,SLOT);
              for(int j=0;j<3;j++) tma2dh(S0+m*SLOT+j*BOXS,&P.m[M_K],col0+j*64,row0+m*64,E0+m*8,PL_EF);
            }
            mbar_expect(sb+W_BAR+224+wg*8,12288);
          }
          if(erl){ __syncwarp(); flag_wait(rbk,a,lane); FAG(); }
          { __syncwarp(); bar_sync(sq,160); sq^=1; }
          if(lane==0){ for(int j=0;j<4;j++) bulk_g2s(S0+j*3072,kp+j*98304,3072,sb+W_BAR+224+wg*8); }
          { __syncwarp(); bar_sync(sq,160); sq^=1; }
          if(lane==0) mbar_arrive(TOK);
          { __syncwarp(); bar_sync(sq,160); sq^=1; } if(lane==0) red_rel(g_cnt+C_QA+rbk);
        } else if(map==M_OUT){
          if(lane==0){ mbar_arrive(E0); mbar_arrive(E0+8); }
          { __syncwarp(); bar_sync(sq,160); sq^=1; }
          { __syncwarp(); bar_sync(sq,160); sq^=1; }
          if(lane==0) mbar_arrive(TOK);
        } else {
          if(lane==0){ mbar_arrive(E0); mbar_arrive(E0+8); }
          for(int m=0;m<2;m++){
            { __syncwarp(); bar_sync(sq,160); sq^=1; }
            if(lane==0){
              if(type==T_KV&&rbk>=KEF){ for(int j=0;j<nbox;j++) tma_st_ef(&P.m[map],S0+m*SLOT+j*BOXS,col0+j*64,row0+m*64); }
              else for(int j=0;j<nbox;j++) tma_st(&P.m[map],S0+m*SLOT+j*BOXS,col0+j*64,row0+m*64);
              bulk_commit();
            }
          }
          if(lane==0){
            bulk_wait_rd(); mbar_arrive(TOK);
            bulk_wait(); FAG(); red_rel(g_cnt+cnt);
          }
        }
        __syncwarp();
      }
      if(lane==0) bulk_wait();
    }
  } else {
    asm volatile("setmaxnreg.inc.sync.aligned.u32 232;");
    const int wg=warp>>2, wq=warp&3, g=lane>>2, t=lane&3;
    const uint32_t E0=EF+wg*16;
    const uint32_t ra=sb+W_SLOT+(16*wq+(lane&7)+((lane>>3)&1)*8)*128;
    uint32_t e0=0, eb=0; int sq=4+2*wg;
    const uint32_t rank=blockIdx.x&P.pair;
    #pragma unroll 1
    for(uint32_t it=0;;it++){
      mbar_wait(IFULL+wg*8,it&1);
      const int type=idesc[wg*8], rbk=idesc[wg*8+1], a=idesc[wg*8+2]; const uint32_t pos=idesc[wg*8+3], em=mapa(EMPTY,idesc[wg*8+5]==2?lane&1:rank);
      __syncwarp();
      if(lane==0) mbar_arrive(IEMPTY+wg*8);
      if(type==T_END) break;
      mbar_wait(sb+W_BAR+144,wg^1);
      if(type==T_OP){
        const int ns=nsp(rbk);
        if(ns_used(1)&&ns==1) pu_item<1>(P,rbk,a,pos,sb,tid,e0,sq);
        if(ns_used(2)&&ns==2) pu_item<2>(P,rbk,a,pos,sb,tid,e0,sq);
        if(ns_used(5)&&ns==5) pu_item<5>(P,rbk,a,pos,sb,tid,e0,sq);
        if(ns_used(10)&&ns==10) pu_item<10>(P,rbk,a,pos,sb,tid,e0,sq);
      } else {
        if(type!=T_QA){
          if(type>=T_M1||(a&3)<2) gemm_item<192>(type,pos,sb,tid,ra,e0,eb,sq,em); else gemm_item<128>(type,pos,sb,tid,ra,e0,eb,sq,em);
        } else {
          float acc[192];
          QT(0);
          mainloop<192>(acc,10,sb,lane,pos,em);
          QT(1);
          const int sgl=wq>>1, rh=wq&1;
          {
            uint32_t q[96];
            float s[2][16], sm[2][8];
            #pragma unroll
            for(int i=95;i>=0;i--) q[i]=pack_bf16(acc[2*i],acc[2*i+1]);
            QT(2);
            #pragma unroll
            for(int m=0;m<2;m++){
              const uint32_t dk=(((sb+W_SLOT+m*SLOT)>>4)&0x3fff)|(1u<<16);
              float u[32];
              mbar_wait(E0+m*8,e0);
              #pragma unroll
              for(int i=0;i<32;i++) u[i]=0.f;
              wg_arrive();
              #pragma unroll
              for(int T=0;T<12;T++) wgmma_rs<64>(u,q+48*m+4*T,dk+(T>>2)*(BOXS/16)+(T&3)*2,T);
              wg_commit();
              wg_wait<0>();
              if(m==0){ bar_arrive(sq,160); sq^=1; }
              #pragma unroll
              for(int i=0;i<16;i++) s[m][i]=sgl?u[16+i]:u[i];
            }
            QT(3);
            mbar_wait(sb+W_BAR+224+wg*8,eb); eb^=1;
            #pragma unroll
            for(int i=0;i<16;i++) sm[i>>3][i&7]=0.f;
            wg_arrive();
            #pragma unroll
            for(int T=0;T<12;T++)
              #pragma unroll
              for(int m=0;m<2;m++) wg16_rs(sm[m],q+48*m+4*T,((((sb+W_SLOT)>>4)&0x3fff)|(8u<<16))+m*384+T*16,T);
            wg_commit();
            wg_wait<0>();
            bar_arrive(sq,160); sq^=1;
            QT(4);
            const float NEG=rb(-1e9f);
            #pragma unroll
            for(int m=0;m<2;m++){
              float sc[5][4];
              float mx[2]={-3.4e38f,-3.4e38f};
              #pragma unroll
              for(int n=0;n<5;n++)
                #pragma unroll
                for(int i=0;i<4;i+=2){
                  const float u0=n?s[m][n?4*n-4+i:0]:(sgl?sm[m][4+i]:sm[m][i]);
                  const float u1=n?s[m][n?4*n-3+i:0]:(sgl?sm[m][5+i]:sm[m][i+1]);
                  const uint32_t r=pack_bf16(u0,u1);
                  const uint32_t w=pack_bf16(__uint_as_float(r<<16)*0.07216878364870322f,__uint_as_float(r&0xffff0000u)*0.07216878364870322f);
                  float v0=__uint_as_float(w<<16), v1=__uint_as_float(w&0xffff0000u);
                  if(n>0){ const int key=8*(n-1)+2*t, row=16*rh+g+4*i; if(key>row) v0=NEG; if(key+1>row) v1=NEG; }
                  sc[n][i]=v0; sc[n][i+1]=v1; mx[i>>1]=fmaxf(mx[i>>1],fmaxf(v0,v1));
                }
              float sum[2]={0.f,0.f};
              #pragma unroll
              for(int r=0;r<2;r++){ mx[r]=fmaxf(mx[r],__shfl_xor_sync(~0u,mx[r],1)); mx[r]=fmaxf(mx[r],__shfl_xor_sync(~0u,mx[r],2)); }
              #pragma unroll
              for(int n=0;n<5;n++)
                #pragma unroll
                for(int i=0;i<4;i++){ const float e=ex2((sc[n][i]-mx[i>>1])*1.4426950408889634f); sc[n][i]=e; sum[i>>1]+=e; }
              #pragma unroll
              for(int r=0;r<2;r++){ sum[r]+=__shfl_xor_sync(~0u,sum[r],1); sum[r]+=__shfl_xor_sync(~0u,sum[r],2); sum[r]=rcp(sum[r]); }
              uint8_t* pd=g_p+(uint32_t)((rbk*4+m*2+sgl)*81920+rh*256+lane*4);
              #pragma unroll
              for(int n=0;n<5;n++){
                uint8_t* q=pd+(n?a*2048+(n-1)*512:(32+(a>>2))*2048+(a&3)*512);
                stg1(q,pack_bf16(sc[n][0]*sum[0],sc[n][1]*sum[0])); stg1(q+128,pack_bf16(sc[n][2]*sum[1],sc[n][3]*sum[1]));
              }
            }
          }
          QT(5);
          bar_arrive(sq,160); sq^=1;
          e0^=1;
        }
      }
    }
  }
  if(P.pair) cluster_sync();
}
#define PRO 0
#define PRM(b) ((PRO&(b))?CU_TENSOR_MAP_L2_PROMOTION_L2_256B:CU_TENSOR_MAP_L2_PROMOTION_L2_128B)
typedef CUresult (*EncFn)(CUtensorMap*,CUtensorMapDataType,cuuint32_t,void*,const cuuint64_t*,const cuuint64_t*,const cuuint32_t*,const cuuint32_t*,CUtensorMapInterleave,CUtensorMapSwizzle,CUtensorMapL2promotion,CUtensorMapFloatOOBfill);
static EncFn enc(){
  static EncFn fn=nullptr;
  if(!fn){ void* p=nullptr; cudaDriverEntryPointQueryResult qr; cudaGetDriverEntryPoint("cuTensorMapEncodeTiled",&p,cudaEnableDefault,&qr); fn=(EncFn)p; }
  return fn;
}
static CUtensorMap mku(const void* base,uint32_t b1,uint32_t b2){
  CUtensorMap m; cuuint64_t gd[3]={256,20,NSEG*40}; cuuint64_t gs[2]={2048,40960}; cuuint32_t bd[3]={256,b1,b2}; cuuint32_t es[3]={1,1,1};
  enc()(&m,CU_TENSOR_MAP_DATA_TYPE_FLOAT64,3,(void*)base,gd,gs,bd,es,CU_TENSOR_MAP_INTERLEAVE_NONE,CU_TENSOR_MAP_SWIZZLE_NONE,PRM(1),CU_TENSOR_MAP_FLOAT_OOB_FILL_NONE);
  return m;
}
static CUtensorMap mk2d(const void* base,uint64_t cols,uint64_t rows,uint32_t bc,uint32_t br){
  EncFn fn=enc();
  CUtensorMap m; cuuint64_t gd[2]={cols,rows}; cuuint64_t gs[1]={cols*2}; cuuint32_t bd[2]={bc,br}; cuuint32_t es[2]={1,1};
  fn(&m,CU_TENSOR_MAP_DATA_TYPE_BFLOAT16,2,(void*)base,gd,gs,bd,es,CU_TENSOR_MAP_INTERLEAVE_NONE,bc==32?CU_TENSOR_MAP_SWIZZLE_64B:CU_TENSOR_MAP_SWIZZLE_128B,PRM(2),CU_TENSOR_MAP_FLOAT_OOB_FILL_NONE);
  return m;
}
static CUtensorMap mkw(const void* base){
  CUtensorMap m; cuuint64_t gd[3]={HD,D/2,2}; cuuint64_t gs[2]={HD*4,HD*2}; cuuint32_t bd[3]={64,8,2}; cuuint32_t es[3]={1,1,1};
  enc()(&m,CU_TENSOR_MAP_DATA_TYPE_BFLOAT16,3,(void*)base,gd,gs,bd,es,CU_TENSOR_MAP_INTERLEAVE_NONE,CU_TENSOR_MAP_SWIZZLE_128B,PRM(4),CU_TENSOR_MAP_FLOAT_OOB_FILL_NONE);
  return m;
}
static CUtensorMap mk4(const void* base,uint64_t cols,uint64_t rows,uint32_t ng,uint32_t nh){
  CUtensorMap m; cuuint64_t gd[4]={64,32,cols/64,rows/32}; cuuint64_t gs[3]={cols*2,128,cols*64}; cuuint32_t bd[4]={64,32,ng,nh}; cuuint32_t es[4]={1,1,1,1};
  enc()(&m,CU_TENSOR_MAP_DATA_TYPE_BFLOAT16,4,(void*)base,gd,gs,bd,es,CU_TENSOR_MAP_INTERLEAVE_NONE,CU_TENSOR_MAP_SWIZZLE_128B,PRM(8),CU_TENSOR_MAP_FLOAT_OOB_FILL_NONE);
  return m;
}
template<class T> static T* sym(T& s){ void* p; cudaGetSymbolAddress(&p,s); return (T*)p; }
}

#define G2 12
#define XPQ Wq
#define XPO Wo
int g_reconly=0; int g_kvgrid=132;
extern "C" void kernel_launch(void* const* d_in, const int* in_sizes, int n_in, void* d_out, int out_size) {
  using namespace rk;
  const bf16* x=(const bf16*)d_in[0]; const bf16* mem0=(const bf16*)d_in[1];
  const bf16* Wq=(const bf16*)d_in[2]; const bf16* Wk=(const bf16*)d_in[3]; const bf16* Wv=(const bf16*)d_in[4]; const bf16* Wo=(const bf16*)d_in[5];
  const bf16* w1=(const bf16*)d_in[8]; const bf16* b1=(const bf16*)d_in[9]; const bf16* w2=(const bf16*)d_in[10]; const bf16* b2=(const bf16*)d_in[11];
  cudaStream_t st=cudaStreamPerThread;
  cudaFuncSetAttribute(k_rec,cudaFuncAttributeMaxDynamicSharedMemorySize,SM_TOTAL);
  cudaFuncSetAttribute(k_work,cudaFuncAttributeMaxDynamicSharedMemorySize,W_TOTAL);
  bf16* k=(bf16*)sym(g_k); bf16* v=(bf16*)sym(g_v);
  WParams P;
  P.m[M_XN]=mk2d(sym(g_xn),D,S,64,128); P.m[M_Y]=mk2d(sym(g_y),D,S,64,128); P.m[M_H]=mk2d(sym(g_h),F,S,64,64); P.m[M_H2]=mk2d(sym(g_h),F,S,64,128);
  P.m[M_K]=mk2d(k,HD,S,64,64); P.m[M_V]=mk2d(v,HD,S,64,64); P.m[M_GATE]=mk2d(sym(g_gate),D,S,64,64);
  P.m[M_WQ]=mk4(Wq,HD,D,3,2); P.m[M_WK]=mk4(Wk,HD,D,3,1); P.m[M_WV]=mk4(Wv,HD,D,3,1);
  P.m[M_W1]=mk4(w1,F,D,3,2); P.m[M_W2]=mk4(w2,D,F,3,2); P.m[M_W2B]=mk4(w2,D,F,2,2);
  P.m[M_U1]=mku(sym(g_u),20,1); P.m[M_U2]=mku(sym(g_u),10,2); P.m[M_U5]=mku(sym(g_u),4,4); P.m[M_U10]=mku(sym(g_u),2,5);
  P.x=x; P.b1=b1; P.b2=b2; P.out=(bf16*)d_out; P.pair=1; P.wq=(const char*)Wq; P.wo=(const char*)Wo;
  cudaFuncSetAttribute(k_pre,cudaFuncAttributeMaxDynamicSharedMemorySize,SM_TOTAL);
  {
    cudaLaunchConfig_t cfg={}; cfg.gridDim=dim3(NCTA); cfg.blockDim=dim3(PRE_T); cfg.dynamicSmemBytes=SM_TOTAL; cfg.stream=st;
    cudaLaunchAttribute at[1]; at[0].id=cudaLaunchAttributeClusterDimension; at[0].val.clusterDim.x=3; at[0].val.clusterDim.y=1; at[0].val.clusterDim.z=1; cfg.attrs=at; cfg.numAttrs=1;
    cudaLaunchKernelEx(&cfg,k_pre,x,mem0,(const char*)Wk,(const char*)Wv);
  }
  if(!(g_reconly&1)){
    cudaLaunchConfig_t cfg={}; cfg.gridDim=dim3(g_kvgrid); cfg.blockDim=dim3(384); cfg.dynamicSmemBytes=W_TOTAL; cfg.stream=st;
    cudaLaunchAttribute at[2]; at[0].id=cudaLaunchAttributeClusterDimension; at[0].val.clusterDim.x=2; at[0].val.clusterDim.y=1; at[0].val.clusterDim.z=1;
    at[1].id=cudaLaunchAttributeProgrammaticStreamSerialization; at[1].val.programmaticStreamSerializationAllowed=1; cfg.attrs=at; cfg.numAttrs=2;
    cudaLaunchKernelEx(&cfg,k_work,P);
  }
  if(!(g_reconly&4)){
    cudaLaunchConfig_t cfg={}; cfg.gridDim=dim3(NCTA); cfg.blockDim=dim3(256); cfg.dynamicSmemBytes=SM_TOTAL; cfg.stream=st;
    cudaLaunchAttribute at[2]; at[0].id=cudaLaunchAttributeClusterDimension; at[0].val.clusterDim.x=3; at[0].val.clusterDim.y=1; at[0].val.clusterDim.z=1;
    at[1].id=cudaLaunchAttributeProgrammaticStreamSerialization; at[1].val.programmaticStreamSerializationAllowed=1; cfg.attrs=at; cfg.numAttrs=2;
    RParams R; R.k=mk2d(k,HD,S,64,32); R.v=mk2d(v,HD,S,64,32); R.w[0]=mkw(XPQ); R.w[1]=mkw(Wk); R.w[2]=mkw(Wv); R.w[3]=mk2d(XPO,D,HD,32,32); R.u=mku(sym(g_u),1,10); R.x=x; R.out=(bf16*)d_out; R.wq=(const char*)XPQ; R.wo=(const char*)XPO;
    cudaLaunchKernelEx(&cfg,k_rec,R,0u);
  }
  if(!(g_reconly&2)){
    cudaLaunchConfig_t cfg={}; cfg.gridDim=dim3(G2); cfg.blockDim=dim3(384); cfg.dynamicSmemBytes=W_TOTAL; cfg.stream=st; P.pair=0;
    cudaLaunchAttribute at[1]; at[0].id=cudaLaunchAttributeProgrammaticStreamSerialization; at[0].val.programmaticStreamSerializationAllowed=1; cfg.attrs=at; cfg.numAttrs=PDL;
    cudaLaunchKernelEx(&cfg,k_work,P);
  }
}
```
